```python
import torch

def _softmax(x, axis=-1):
    return torch.softmax(x, dim=axis)

def _gelu(x):
    return torch.nn.functional.gelu(x, approximate='tanh')

def _silu(x):
    return torch.nn.functional.silu(x)

def _sigmoid(x):
    return torch.sigmoid(x)

def _layernorm(x, axis=-1, eps=1e-05):
    m = x.mean(dim=axis, keepdim=True)
    v = x.var(dim=axis, keepdim=True, unbiased=False)
    return (x - m) / torch.sqrt(v + eps)

def _scatter_add(tgt, idx, src, axis=0):
    return tgt.clone().index_add_(axis, idx, src)

def _segment_sum(src, seg, n):
    out = torch.zeros((n,) + src.shape[1:], dtype=src.dtype)
    return out.index_add_(0, seg, src)

def _pad(x, pw):
    flat = tuple((v for pair in reversed(pw) for v in pair))
    return torch.nn.functional.pad(x, flat)
kernel_name = 'concat_heads__memory_aug_recurrent_mem_tr__ssm_conv_s4d__prompt'

def setup_inputs():

    _w = lambda a: (lambda t: t.to(torch.bfloat16) if t.is_floating_point() else t)(torch.as_tensor(a))

    def _A_setup():
        B, S, Dm = (1, 2048, 576)
        H, Dh = (32, 128)
        M, seg = (8, 32)
        seg = min(seg, S)
        S = S // seg * seg
        return {'x': _w((lambda *s: torch.randn(*s, dtype=torch.bfloat16) * 0.05)(B, S, Dm)), 'mem0': _w((lambda *s: torch.randn(*s, dtype=torch.bfloat16) * 0.4)(B, M, Dm)), 'Wq': _w((lambda *s: torch.randn(*s, dtype=torch.bfloat16) * 6.4)(Dm, H, Dh) * Dm ** (-0.5)), 'Wk': _w((lambda *s: torch.randn(*s, dtype=torch.bfloat16) * 6.4)(Dm, H, Dh) * Dm ** (-0.5)), 'Wv': _w((lambda *s: torch.randn(*s, dtype=torch.bfloat16) * 0.4)(Dm, H, Dh) * Dm ** (-0.5)), 'Wo': _w((lambda *s: torch.randn(*s, dtype=torch.bfloat16) * 0.4)(H, Dh, Dm) * (H * Dh) ** (-0.5)), 'seg_len': seg}
    _A_in = _A_setup()

    def _B_setup():
        Bsz, L, D, N = (1, 2048, 576, 128)
        return {'u': _w((lambda *s: torch.randn(*s, dtype=torch.bfloat16) * 0.05)(Bsz, L, D)), 'log_A_real': _w((lambda *s: torch.randn(*s, dtype=torch.bfloat16) * 3.2)(D, N) * 0.5), 'A_imag': _w((lambda *s: torch.randn(*s, dtype=torch.bfloat16) * 0.05)(D, N) * 3.14), 'C_real': _w((lambda *s: torch.randn(*s, dtype=torch.bfloat16) * 0.4)(D, N) / N ** 0.5), 'C_imag': _w((lambda *s: torch.randn(*s, dtype=torch.bfloat16) * 0.4)(D, N) / N ** 0.5), 'log_dt': _w((lambda *s: torch.randn(*s, dtype=torch.bfloat16) * 0.05)(D) * 0.5 - 4.0), 'D_skip': _w((lambda *s: torch.randn(*s, dtype=torch.bfloat16) * 0.05)(D))}
    _B_in = _B_setup()
    return {'A_x': _A_in['x'], 'A_mem0': _A_in['mem0'], 'A_Wq': _A_in['Wq'], 'A_Wk': _A_in['Wk'], 'A_Wv': _A_in['Wv'], 'A_Wo': _A_in['Wo'], 'A_seg_len': _A_in['seg_len'], 'B_u': _B_in['u'], 'B_log_A_real': _B_in['log_A_real'], 'B_A_imag': _B_in['A_imag'], 'B_C_real': _B_in['C_real'], 'B_C_imag': _B_in['C_imag'], 'B_log_dt': _B_in['log_dt'], 'B_D_skip': _B_in['D_skip']}

def reference(A_x, A_mem0, A_Wq, A_Wk, A_Wv, A_Wo, A_seg_len, B_u, B_log_A_real, B_A_imag, B_C_real, B_C_imag, B_log_dt, B_D_skip):

    def _A_ref(x, mem0, Wq, Wk, Wv, Wo, seg_len):
        B, S, Dm = x.shape
        H, Dh = (Wq.shape[1], Wq.shape[2])
        M = mem0.shape[1]
        scale = Dh ** (-0.5)
        n_seg = S // seg_len
        L = M + seg_len
        idx = torch.arange(L)
        mask = (idx[:, None] < M) | (idx[:, None] >= idx[None, :])
        mem = mem0
        outs = []
        for s in range(n_seg):
            xs = x[:, s * seg_len:(s + 1) * seg_len, :].clone()
            h = torch.concatenate([mem, xs], axis=1)
            q = torch.einsum('btd,dhe->bhte', h, Wq)
            k = torch.einsum('btd,dhe->bhte', h, Wk)
            v = torch.einsum('btd,dhe->bhte', h, Wv)
            scores = torch.einsum('bhqe,bhke->bhqk', q, k) * scale
            scores = torch.where(mask[None, None], scores, -1000000000.0)
            p = _softmax(scores, axis=-1)
            o = torch.einsum('bhqk,bhke->bhqe', p, v)
            o = torch.einsum('bhte,hed->btd', o, Wo)
            mem = o[:, :M, :].clone()
            outs.append(o[:, M:, :])
        return torch.concatenate(outs, axis=1)

    def _B_ref(u, log_A_real, A_imag, C_real, C_imag, log_dt, D_skip):
        L = u.shape[1]
        dt = torch.exp(log_dt)
        A = -torch.exp(log_A_real) + 1j * A_imag
        C = (C_real + 1j * C_imag) * dt[:, None]
        pos = (lambda x, dt: x.to(dt))(torch.arange(L), log_dt.dtype)
        P = torch.exp((A * dt[:, None])[:, :, None] * pos[None, None, :])
        K = 2.0 * torch.einsum('dn,dnl->dl', C, P).real
        L2 = 2 * L
        u_t = (lambda x, *d: x.permute(*d))(u, 0, 2, 1)
        Kf = (lambda x, *a, **k: torch.fft.rfft(x.float(), *a, **k))(K, L2)
        Uf = (lambda x, *a, **k: torch.fft.rfft(x.float(), *a, **k))(u_t, L2)
        y = (lambda x, *a, **k: torch.fft.irfft(x, *a, **k).to(torch.bfloat16))(Uf * Kf[None, :, :], L2)[:, :, :L]
        y = (lambda x, *d: x.permute(*d))(y, 0, 2, 1)
        return y + u * D_skip[None, None, :]
    a = _A_ref(A_x, A_mem0, A_Wq, A_Wk, A_Wv, A_Wo, A_seg_len)
    b = _B_ref(B_u, B_log_A_real, B_A_imag, B_C_real, B_C_imag, B_log_dt, B_D_skip)
    return torch.concatenate([a, b], axis=-1)
```

```cpp
#include <cuda_runtime.h>
#include <cuda_bf16.h>
#include <cuda.h>
#include <stdint.h>

typedef __nv_bfloat16 bf16;

namespace {

constexpr int DM = 576, NH = 32, DH = 128, SEG = 32, NSEG = 64, SEQ = 2048, NST = 128;
constexpr int OUTW = 2 * DM;
constexpr unsigned SPIN_LIM = 1u << 15;

constexpr int SLOT_BYTES = 768 * 32;
__device__ __align__(1024) uint4 g_acc[NSEG * SLOT_BYTES / 16];
__device__ __align__(1024) uint4 g_ox[NSEG * NH * 512];
__device__ __align__(1024) uint4 g_vx[NH * 2 * 512];
__device__ unsigned g_flag[NSEG * 4];
__device__ unsigned g_zero_cnt;

__device__ __forceinline__ uint32_t smem_u32(const void* p) { return (uint32_t)__cvta_generic_to_shared(p); }
__device__ __forceinline__ unsigned clk() { unsigned c; asm volatile("mov.u32 %0, %%clock;" : "=r"(c)::"memory"); return c; }
__device__ __forceinline__ uint32_t mapa(uint32_t a, uint32_t r) { uint32_t o; asm("mapa.shared::cluster.u32 %0, %1, %2;" : "=r"(o) : "r"(a), "r"(r)); return o; }
__device__ __forceinline__ void mbar_init(uint32_t b, uint32_t n) { asm volatile("mbarrier.init.shared::cta.b64 [%0], %1;" ::"r"(b), "r"(n) : "memory"); }
__device__ __forceinline__ void mbar_arrive(uint32_t b) { asm volatile("mbarrier.arrive.shared::cta.b64 _, [%0];" ::"r"(b) : "memory"); }
__device__ __forceinline__ void mbar_expect(uint32_t b, uint32_t tx) { asm volatile("mbarrier.arrive.expect_tx.shared::cta.b64 _, [%0], %1;" ::"r"(b), "r"(tx) : "memory"); }
__device__ __forceinline__ bool mbar_try(uint32_t b, uint32_t par) {
    uint32_t ok;
    asm volatile("{.reg .pred p; mbarrier.try_wait.parity.shared::cta.b64 p, [%1], %2; selp.u32 %0, 1, 0, p;}" : "=r"(ok) : "r"(b), "r"(par) : "memory");
    return ok;
}
__device__ __forceinline__ void mbar_wait(uint32_t b, uint32_t par) {
    asm volatile("{.reg .pred p, q; .reg .u32 c; mov.u32 c, 0;\n"
                 "W: mbarrier.try_wait.parity.shared::cta.b64 p, [%0], %1;\n"
                 "@p bra D;\n add.u32 c, c, 1; setp.lt.u32 q, c, %2;\n @q bra W;\n D:\n}" ::"r"(b), "r"(par), "n"(SPIN_LIM) : "memory");
}
__device__ __forceinline__ void cluster_sync() { asm volatile("barrier.cluster.arrive.aligned; barrier.cluster.wait.aligned;" ::: "memory"); }
__device__ __forceinline__ void fence_async_smem() { asm volatile("fence.proxy.async.shared::cta;" ::: "memory"); }
__device__ __forceinline__ void ldsm4(uint32_t* r, uint32_t a) { asm volatile("ldmatrix.sync.aligned.m8n8.x4.shared.b16 {%0,%1,%2,%3},[%4];" : "=r"(r[0]), "=r"(r[1]), "=r"(r[2]), "=r"(r[3]) : "r"(a) : "memory"); }
__device__ __forceinline__ void ldsm4t(uint32_t* r, uint32_t a) { asm volatile("ldmatrix.sync.aligned.m8n8.x4.trans.shared.b16 {%0,%1,%2,%3},[%4];" : "=r"(r[0]), "=r"(r[1]), "=r"(r[2]), "=r"(r[3]) : "r"(a) : "memory"); }
__device__ __forceinline__ void stsm1(uint32_t a, uint32_t r0) { asm volatile("stmatrix.sync.aligned.m8n8.x1.shared.b16 [%0],{%1};" ::"r"(a), "r"(r0) : "memory"); }
__device__ __forceinline__ void stsm2t(uint32_t a, uint32_t r0, uint32_t r1) { asm volatile("stmatrix.sync.aligned.m8n8.x2.trans.shared.b16 [%0],{%1,%2};" ::"r"(a), "r"(r0), "r"(r1) : "memory"); }
__device__ __forceinline__ void stsm4t(uint32_t a, uint32_t r0, uint32_t r1, uint32_t r2, uint32_t r3) { asm volatile("stmatrix.sync.aligned.m8n8.x4.trans.shared.b16 [%0],{%1,%2,%3,%4};" ::"r"(a), "r"(r0), "r"(r1), "r"(r2), "r"(r3) : "memory"); }
__device__ __forceinline__ void sts32(uint32_t a, uint32_t v) { asm volatile("st.shared.b32 [%0], %1;" ::"r"(a), "r"(v) : "memory"); }
__device__ __forceinline__ void sts64(uint32_t a, uint32_t x, uint32_t y) { asm volatile("st.shared.v2.b32 [%0], {%1,%2};" ::"r"(a), "r"(x), "r"(y) : "memory"); }
__device__ __forceinline__ void sts128(uint32_t a, uint32_t x, uint32_t y, uint32_t z, uint32_t w) { asm volatile("st.shared.v4.b32 [%0], {%1,%2,%3,%4};" ::"r"(a), "r"(x), "r"(y), "r"(z), "r"(w) : "memory"); }
__device__ __forceinline__ void lds64(uint32_t* r, uint32_t a) { asm volatile("ld.shared.v2.b32 {%0,%1},[%2];" : "=r"(r[0]), "=r"(r[1]) : "r"(a) : "memory"); }
__device__ __forceinline__ float2 lds64f(uint32_t a) { float2 v; asm volatile("ld.shared.v2.f32 {%0,%1},[%2];" : "=f"(v.x), "=f"(v.y) : "r"(a) : "memory"); return v; }
__device__ __forceinline__ void lds128(uint32_t* r, uint32_t a) { asm volatile("ld.shared.v4.b32 {%0,%1,%2,%3},[%4];" : "=r"(r[0]), "=r"(r[1]), "=r"(r[2]), "=r"(r[3]) : "r"(a) : "memory"); }
__device__ __forceinline__ void st_async64(uint32_t a, uint32_t x, uint32_t y, uint32_t bar) {
    asm volatile("st.async.weak.shared::cluster.mbarrier::complete_tx::bytes.v2.b32 [%0], {%1,%2}, [%3];" ::"r"(a), "r"(x), "r"(y), "r"(bar) : "memory");
}
__device__ __forceinline__ uint32_t pack_bf16(float lo, float hi) { uint32_t r; asm("cvt.rn.bf16x2.f32 %0, %1, %2;" : "=r"(r) : "f"(hi), "f"(lo)); return r; }
__device__ __forceinline__ float ex2(float x) { float r; asm("ex2.approx.ftz.f32 %0, %1;" : "=f"(r) : "f"(x)); return r; }
__device__ __forceinline__ float rcp(float x) { float r; asm("rcp.approx.ftz.f32 %0, %1;" : "=f"(r) : "f"(x)); return r; }
__device__ __forceinline__ void mma16(float* d, const uint32_t* a, uint32_t b0, uint32_t b1) {
    asm volatile("mma.sync.aligned.m16n8k16.row.col.f32.bf16.bf16.f32 {%0,%1,%2,%3},{%4,%5,%6,%7},{%8,%9},{%0,%1,%2,%3};"
                 : "+f"(d[0]), "+f"(d[1]), "+f"(d[2]), "+f"(d[3]) : "r"(a[0]), "r"(a[1]), "r"(a[2]), "r"(a[3]), "r"(b0), "r"(b1));
}
__device__ __forceinline__ void mma16z(float* d, const uint32_t* a, uint32_t b0, uint32_t b1) {
    asm volatile("mma.sync.aligned.m16n8k16.row.col.f32.bf16.bf16.f32 {%0,%1,%2,%3},{%4,%5,%6,%7},{%8,%9},{%10,%10,%10,%10};"
                 : "=f"(d[0]), "=f"(d[1]), "=f"(d[2]), "=f"(d[3]) : "r"(a[0]), "r"(a[1]), "r"(a[2]), "r"(a[3]), "r"(b0), "r"(b1), "f"(0.f));
}
__device__ __forceinline__ void mma8(float* d, uint32_t a0, uint32_t a1, uint32_t b0) {
    asm volatile("mma.sync.aligned.m16n8k8.row.col.f32.bf16.bf16.f32 {%0,%1,%2,%3},{%4,%5},{%6},{%0,%1,%2,%3};"
                 : "+f"(d[0]), "+f"(d[1]), "+f"(d[2]), "+f"(d[3]) : "r"(a0), "r"(a1), "r"(b0));
}
template <int ACC>
__device__ __forceinline__ void mma_sp(float* d, const uint32_t* a, const uint32_t* b) {
    if (ACC)
        asm volatile("mma.sp::ordered_metadata.sync.aligned.m16n8k32.row.col.f32.bf16.bf16.f32 {%0,%1,%2,%3},{%4,%5,%6,%7},{%8,%9,%10,%11},{%0,%1,%2,%3},%12,0x0;"
                     : "+f"(d[0]), "+f"(d[1]), "+f"(d[2]), "+f"(d[3])
                     : "r"(a[0]), "r"(a[1]), "r"(a[2]), "r"(a[3]), "r"(b[0]), "r"(b[1]), "r"(b[2]), "r"(b[3]), "r"(0xEEEE4444u));
    else
        asm volatile("mma.sp::ordered_metadata.sync.aligned.m16n8k32.row.col.f32.bf16.bf16.f32 {%0,%1,%2,%3},{%4,%5,%6,%7},{%8,%9,%10,%11},{%13,%13,%13,%13},%12,0x0;"
                     : "=f"(d[0]), "=f"(d[1]), "=f"(d[2]), "=f"(d[3])
                     : "r"(a[0]), "r"(a[1]), "r"(a[2]), "r"(a[3]), "r"(b[0]), "r"(b[1]), "r"(b[2]), "r"(b[3]), "r"(0xEEEE4444u), "f"(0.f));
}
__device__ __forceinline__ void mbar_arrive_if0(uint32_t b, uint32_t z) { asm volatile("{.reg .pred p; setp.eq.u32 p, %1, 0; @p mbarrier.arrive.shared::cta.b64 _, [%0];}" ::"r"(b), "r"(z) : "memory"); }
__device__ __forceinline__ void mbar_expect_if0(uint32_t b, uint32_t tx, uint32_t z) { asm volatile("{.reg .pred p; setp.eq.u32 p, %2, 0; @p mbarrier.arrive.expect_tx.shared::cta.b64 _, [%0], %1;}" ::"r"(b), "r"(tx), "r"(z) : "memory"); }
__device__ __forceinline__ float lds32f(uint32_t a) { float v; asm volatile("ld.shared.f32 %0,[%1];" : "=f"(v) : "r"(a) : "memory"); return v; }
__device__ __forceinline__ void wg_fence() { asm volatile("wgmma.fence.sync.aligned;" ::: "memory"); }
__device__ __forceinline__ void wg_commit() { asm volatile("wgmma.commit_group.sync.aligned;" ::: "memory"); }
template <int N> __device__ __forceinline__ void wg_wait() { asm volatile("wgmma.wait_group.sync.aligned %0;" ::"n"(N) : "memory"); }
__device__ __forceinline__ void delay(unsigned n) { if (n) { const unsigned t0 = clk(); while (clk() - t0 < n) {} } }
template <int ACC>
__device__ __forceinline__ void wg_rs_n32(float* d, const uint32_t* a, uint32_t dlo) {
    if (ACC)
        asm volatile("{.reg .b64 db; mov.b64 db, {%20, %21};\n"
                     "wgmma.mma_async.sync.aligned.m64n32k16.f32.bf16.bf16 {%0,%1,%2,%3,%4,%5,%6,%7,%8,%9,%10,%11,%12,%13,%14,%15},{%16,%17,%18,%19},db,1,1,1,0;}"
                     : "+f"(d[0]), "+f"(d[1]), "+f"(d[2]), "+f"(d[3]), "+f"(d[4]), "+f"(d[5]), "+f"(d[6]), "+f"(d[7]),
                       "+f"(d[8]), "+f"(d[9]), "+f"(d[10]), "+f"(d[11]), "+f"(d[12]), "+f"(d[13]), "+f"(d[14]), "+f"(d[15])
                     : "r"(a[0]), "r"(a[1]), "r"(a[2]), "r"(a[3]), "r"(dlo), "r"(0x40000040u));
    else
        asm volatile("{.reg .b64 db; mov.b64 db, {%20, %21};\n"
                     "wgmma.mma_async.sync.aligned.m64n32k16.f32.bf16.bf16 {%0,%1,%2,%3,%4,%5,%6,%7,%8,%9,%10,%11,%12,%13,%14,%15},{%16,%17,%18,%19},db,0,1,1,0;}"
                     : "=f"(d[0]), "=f"(d[1]), "=f"(d[2]), "=f"(d[3]), "=f"(d[4]), "=f"(d[5]), "=f"(d[6]), "=f"(d[7]),
                       "=f"(d[8]), "=f"(d[9]), "=f"(d[10]), "=f"(d[11]), "=f"(d[12]), "=f"(d[13]), "=f"(d[14]), "=f"(d[15])
                     : "r"(a[0]), "r"(a[1]), "r"(a[2]), "r"(a[3]), "r"(dlo), "r"(0x40000040u));
}
__device__ __forceinline__ uint32_t desc_lo(uint32_t addr) { return ((addr & 0x3FFFF) >> 4) | (1u << 16); }
__device__ __forceinline__ void tma2d(uint32_t dst, const CUtensorMap* m, int c0, int c1, uint32_t bar) {
    asm volatile("cp.async.bulk.tensor.2d.shared::cluster.global.mbarrier::complete_tx::bytes [%0], [%1, {%2,%3}], [%4];"
                 ::"r"(dst), "l"(m), "r"(c0), "r"(c1), "r"(bar) : "memory");
}
__device__ __forceinline__ void tma3d(uint32_t dst, const CUtensorMap* m, int c0, int c1, int c2, uint32_t bar) {
    asm volatile("cp.async.bulk.tensor.3d.shared::cluster.global.mbarrier::complete_tx::bytes [%0], [%1, {%2,%3,%4}], [%5];"
                 ::"r"(dst), "l"(m), "r"(c0), "r"(c1), "r"(c2), "r"(bar) : "memory");
}
__device__ __forceinline__ void tma3d_mc(uint32_t dst, const CUtensorMap* m, int c0, int c1, int c2, uint32_t bar, uint16_t mask) {
    asm volatile("cp.async.bulk.tensor.3d.shared::cluster.global.mbarrier::complete_tx::bytes.multicast::cluster [%0], [%1, {%2,%3,%4}], [%5], %6;"
                 ::"r"(dst), "l"(m), "r"(c0), "r"(c1), "r"(c2), "r"(bar), "h"(mask) : "memory");
}
__device__ __forceinline__ void bulk_g2s_mc(uint32_t dst, const void* src, uint32_t bytes, uint32_t bar, uint16_t mask) {
    asm volatile("cp.async.bulk.shared::cluster.global.mbarrier::complete_tx::bytes.multicast::cluster [%0], [%1], %2, [%3], %4;"
                 ::"r"(dst), "l"(src), "r"(bytes), "r"(bar), "h"(mask) : "memory");
}
__device__ __forceinline__ void tma2d_prefetch(const CUtensorMap* m, int c0, int c1) {
    asm volatile("cp.async.bulk.prefetch.tensor.2d.L2.global [%0, {%1,%2}];" ::"l"(m), "r"(c0), "r"(c1) : "memory");
}
__device__ __forceinline__ void bulk_s2c(uint32_t dst, uint32_t src, uint32_t bytes, uint32_t bar) {
    asm volatile("cp.async.bulk.shared::cluster.shared::cta.mbarrier::complete_tx::bytes [%0], [%1], %2, [%3];" ::"r"(dst), "r"(src), "r"(bytes), "r"(bar) : "memory");
}
__device__ __forceinline__ void bulk_s2g(void* dst, uint32_t src, uint32_t bytes) {
    asm volatile("cp.async.bulk.global.shared::cta.bulk_group [%0], [%1], %2;" ::"l"(dst), "r"(src), "r"(bytes) : "memory");
}
__device__ __forceinline__ void bulk_commit() { asm volatile("cp.async.bulk.commit_group;" ::: "memory"); }
__device__ __forceinline__ void bulk_wait0() { asm volatile("cp.async.bulk.wait_group 0;" ::: "memory"); }
__device__ __forceinline__ uint4 ld_poll(const void* p) {
    uint4 v;
    asm volatile("ld.relaxed.gpu.global.v4.u32 {%0,%1,%2,%3},[%4];" : "=r"(v.x), "=r"(v.y), "=r"(v.z), "=r"(v.w) : "l"(p) : "memory");
    return v;
}
__device__ __forceinline__ unsigned ld_acquire(const unsigned* p) { unsigned v; asm volatile("ld.acquire.gpu.global.u32 %0,[%1];" : "=r"(v) : "l"(p) : "memory"); return v; }
__device__ __forceinline__ void red_release(unsigned* p, unsigned v) { asm volatile("red.release.gpu.global.add.u32 [%0], %1;" ::"l"(p), "r"(v) : "memory"); }

__device__ __forceinline__ void publish(unsigned* p) {
    asm volatile("fence.proxy.async.global;" ::: "memory");
    asm volatile("red.relaxed.gpu.global.add.u32 [%0], 1;" ::"l"(p) : "memory");
}

constexpr uint32_t XB_BYTES = 36864;
constexpr uint32_t S_XB = 0;
constexpr uint32_t S_MEM = 73728;
constexpr uint32_t S_QM = 82944;
constexpr uint32_t S_KM = 83968;
constexpr uint32_t S_OM = 84992;
constexpr uint32_t S_SP = 87040;
constexpr uint32_t S_SUM = 89600;
constexpr uint32_t S_PX = 91136;
constexpr uint32_t S_VM = 181248;
constexpr uint32_t S_QX = 95232;
constexpr uint32_t S_KX = 103424;
constexpr uint32_t S_VX = 111616;
constexpr uint32_t S_SX = 144384;
constexpr uint32_t S_OX = 164864;
constexpr uint32_t S_WO = 181248;
constexpr uint32_t S_W = 73728;
constexpr uint32_t S_BAR = 230400;
constexpr uint32_t A_SMEM = S_BAR + 128;
constexpr uint32_t B_W = S_BAR, B_WO = S_BAR + 24, B_X = S_BAR + 32, B_S = S_BAR + 48, B_V = S_BAR + 56, B_VX = S_BAR + 64, B_SX = S_BAR + 80;

constexpr float SM_SCALE = 0.08838834764831845f * 1.4426950408889634f;
constexpr uint32_t ONES = 0x3F803F80u;
#define XLIM NSEG
#define XTMA_DELAY 0
#define POLL_AT 32
#define SX_DELAY 0
#define POLL_DELAY 0
#define POLL_DELAY_V POLL_DELAY
#define RCP_AT 2
constexpr uint32_t FULL_COUNT = 0x4200u;

#define STAMP(i) do {} while (0)

__device__ __forceinline__ void softmax_exp(float (&sv)[10]) {
    float m = fmaxf(fmaxf(fmaxf(sv[0], sv[1]), fmaxf(sv[2], sv[3])), fmaxf(fmaxf(sv[4], sv[5]), fmaxf(sv[6], sv[7])));
    m = fmaxf(m, fmaxf(sv[8], sv[9]));
    const float m1 = __shfl_xor_sync(0xffffffffu, m, 1), m2 = __shfl_xor_sync(0xffffffffu, m, 2), m3 = __shfl_xor_sync(0xffffffffu, m, 3);
    m = fmaxf(fmaxf(m, m1), fmaxf(m2, m3));
    const float mc = -m * SM_SCALE;
#pragma unroll
    for (int i = 0; i < 10; i++) sv[i] = ex2(fmaf(sv[i], SM_SCALE, mc));
}

__device__ __forceinline__ void x_scores(uint32_t sb, int seg, int wq, uint32_t L16, float (&sv)[10]) {
    mbar_wait(sb + B_SX + (seg & 1) * 8, (seg >> 1) & 1);
    const uint32_t sx = sb + S_SX + (seg & 1) * 10240 + wq * 1280 + (L16 >> 1);
    const int dg = (int)(L16 >> 6) - (int)((L16 >> 3) & 6) + 8 * wq;
#pragma unroll
    for (int T = 0; T < 5; T++) {
        const float2 a = lds64f(sx + T * 256), b = lds64f(sx + 5120 + T * 256);
        sv[2 * T] = a.x + b.x; sv[2 * T + 1] = a.y + b.y;
        if (T < 4) {
            if (dg < 8 * T) sv[2 * T] = -INFINITY;
            if (dg < 8 * T + 1) sv[2 * T + 1] = -INFINITY;
        }
    }
}
__device__ __forceinline__ void x_softmax(float (&sv)[10], uint32_t (&p)[5]) {
    softmax_exp(sv);
    float l = ((sv[0] + sv[1]) + (sv[2] + sv[3])) + ((sv[4] + sv[5]) + (sv[6] + sv[7])) + (sv[8] + sv[9]);
    const float l1 = __shfl_xor_sync(0xffffffffu, l, 1), l2 = __shfl_xor_sync(0xffffffffu, l, 2), l3 = __shfl_xor_sync(0xffffffffu, l, 3);
    const float r = rcp((l + l1) + (l2 + l3));
#pragma unroll
    for (int i = 0; i < 5; i++) p[i] = pack_bf16(sv[2 * i] * r, sv[2 * i + 1] * r);
}
__device__ __forceinline__ void x_pv(uint32_t sb, int seg, int c, int wq, uint32_t L16, const uint32_t (&p)[5]) {
    const uint32_t vx = sb + S_VX + (seg & 3) * 8192 + c * 4096 + L16;
    const uint32_t vm = sb + S_VM + (seg & 3) * 2048 + c * 1024 + (L16 >> 1);
    const uint32_t ox = sb + S_OX + (seg & 1) * 8192 + c * 4096 + wq * 1024 + (L16 & 0x70) * 8;
    const uint32_t sw = ((L16 >> 3) & 0x30) ^ (L16 & 0x70);
    float o[4][4];
    uint32_t a[4][4], am[4][2];
#pragma unroll
    for (int u = 0; u < 4; u++) lds128(a[u], vx + u * 1024);
#pragma unroll
    for (int u = 0; u < 4; u++) lds64(am[u], vm + u * 256);
#pragma unroll
    for (int u = 0; u < 4; u++) mma16z(o[u], a[u], p[0], p[1]);
    if (wq >= 2) {
#pragma unroll
        for (int u = 0; u < 4; u++) lds128(a[u], vx + u * 1024 + 512);
#pragma unroll
        for (int u = 0; u < 4; u++) mma16(o[u], a[u], p[2], p[3]);
    }
#pragma unroll
    for (int u = 0; u < 4; u++) mma8(o[u], am[u][0], am[u][1], p[4]);
#pragma unroll
    for (int u = 0; u < 2; u++)
        stsm4t(ox + (sw ^ (u * 64)), pack_bf16(o[2 * u][0], o[2 * u][1]), pack_bf16(o[2 * u][2], o[2 * u][3]),
               pack_bf16(o[2 * u + 1][0], o[2 * u + 1][1]), pack_bf16(o[2 * u + 1][2], o[2 * u + 1][3]));
}
__device__ __forceinline__ void ox_publish(int seg, uint32_t h) { bulk_wait0(); publish(&g_flag[seg * 4 + (h >> 3)]); }
__device__ __forceinline__ void ox_store(uint32_t sb, int seg, uint32_t h) {
    fence_async_smem();
    bulk_s2g(g_ox + (seg * NH + h) * 512, sb + S_OX + (seg & 1) * 8192, 8192);
    bulk_commit();
}

__device__ __forceinline__ void x_epilogue(uint32_t sb, const float (&d)[16], int seg, bool isv, int w, uint32_t L16) {
    uint32_t pk[8];
#pragma unroll
    for (int i = 0; i < 8; i++) pk[i] = pack_bf16(d[2 * i], d[2 * i + 1]);
    if (!isv) {
        const uint32_t a = sb + S_QX + (w >> 2) * 8192 + (seg & 1) * 4096 + (w & 3) * 256 + (L16 & 0xF0) + (L16 & 0x100) * 4;
        stsm4t(a, pk[0], pk[1], pk[2], pk[3]);
        stsm4t(a + 2048, pk[4], pk[5], pk[6], pk[7]);
    } else {
        const uint32_t a = sb + S_VX + (seg & 3) * 8192 + w * 1024 + L16;
        sts128(a, pk[0], pk[1], pk[2], pk[3]);
        sts128(a + 512, pk[4], pk[5], pk[6], pk[7]);
    }
}

template <int K0, int K1>
__device__ __forceinline__ void x_project(float (&d)[16], const uint32_t (&wA)[36][4], uint32_t desc) {
#pragma unroll
    for (int i = K0; i < K1; i++) {
        const uint32_t db = desc + (((i >> 2) * 4096 + (i & 3) * 32) >> 4);
        if (i == 0) wg_rs_n32<0>(d, wA[i], db); else wg_rs_n32<1>(d, wA[i], db);
    }
}

template <int ROLE>
__device__ __forceinline__ void chain_steps(const uint32_t sb, const uint32_t L16, const uint32_t L8, const int wq, const uint32_t j, const uint32_t h,
                                            const uint32_t peerA, const uint32_t peerB, const uint32_t (&wA)[36][4], const uint32_t (&woA)[8][4],
                                            const uint32_t (&woB)[4][4], const CUtensorMap* tmX, char* slot, const bf16* __restrict__ mem0
) {
    constexpr bool isv = ROLE >= 2;
    constexpr int wg = ROLE & 1;
    const int w = wg * 4 + wq;
    const uint32_t xdesc = desc_lo(sb + S_XB);
    const uint32_t zero = h >> 20;
    float sx[10];
#pragma unroll
    for (int i = 0; i < 10; i++) sx[i] = 0.f;
    uint4 v[6];
    if (wg == 0) {
        const int g = L16 >> 6, t2 = (L16 >> 3) & 6;
        const unsigned short* m = reinterpret_cast<const unsigned short*>(mem0);
#pragma unroll
        for (int i = 0; i < 6; i++) {
            const int c = i * 96 + wq * 24;
            v[i].x = m[t2 * DM + c + g] | ((uint32_t)m[(t2 + 1) * DM + c + g] << 16);
            v[i].y = m[t2 * DM + c + 8 + g] | ((uint32_t)m[(t2 + 1) * DM + c + 8 + g] << 16);
            v[i].z = *reinterpret_cast<const uint32_t*>(m + g * DM + c + 16 + t2);
            v[i].w = FULL_COUNT;
        }
        float xd[16];
        asm volatile("bar.arrive 1, 256;" ::: "memory");
        wg_fence();
        x_project<0, 36>(xd, wA, xdesc + (XB_BYTES >> 4));
        wg_commit();
        wg_wait<0>();
        x_epilogue(sb, xd, 1, isv, w, L16);
    }
    int s = 0;
#pragma unroll 1
    while (true) {
        const uint32_t par = s & 1;
        const uint32_t kx = sb + S_KX + par * 4096;
        if (wg == 0) {
            const uint32_t ma = sb + S_MEM + wq * 384 + L16;
            uint32_t bad = 0;
#pragma unroll
            for (int i = 0; i < 6; i++) { stsm2t(ma + i * 1536, v[i].x, v[i].y); stsm1(ma + i * 1536 + 256, v[i].z); bad |= v[i].w ^ FULL_COUNT; }
            unsigned c = 0;
            if (__builtin_expect(__any_sync(0xffffffffu, bad != 0), 0)) {
                do {
#pragma unroll
                    for (int i = 0; i < 6; i++) v[i] = ld_poll(slot + i * 4096);
                    bad = 0;
#pragma unroll
                    for (int i = 0; i < 6; i++) { stsm2t(ma + i * 1536, v[i].x, v[i].y); stsm1(ma + i * 1536 + 256, v[i].z); bad |= v[i].w ^ FULL_COUNT; }
                } while (++c < SPIN_LIM && __any_sync(0xffffffffu, bad != 0));
            }
            STAMP(9);
        } else {
            float xd[16];
            asm volatile("bar.sync 1, 256;" ::: "memory");
            wg_fence();
            x_project<0, 36>(xd, wA, xdesc + (par ^ 1) * (XB_BYTES >> 4));
            wg_commit();
            if (isv && wq == 0 && s >= 1) {
                if (L16 == 0) {
                    bulk_wait0();
                    bulk_g2s_mc(sb + S_VX + (s & 3) * 8192, g_vx + (h * 2 + par) * 512, 8192, sb + B_VX + par * 8, 3);
                }
                __syncwarp();
            }
            wg_wait<0>();
            x_epilogue(sb, xd, s + 1, isv, w, L16);
            STAMP(9);
        }
        __syncthreads();
        if (ROLE == 3 && wq == 1) { if (L16 == 0 && s >= 3) ox_store(sb, s - 3, h); __syncwarp(); }
        float c0[4], c1[4];
        uint32_t k0[4], k1[4];
        {
            const uint32_t a = sb + S_MEM + L16;
#pragma unroll
            for (int i = 0; i < 18; i++) {
                uint32_t b[4];
                ldsm4(b, a + i * 512);
                if (ROLE == 0 && i == 17) { ldsm4(k0, kx + wq * 1024 + L16); ldsm4(k1, kx + wq * 1024 + 512 + L16); }
                if (i == 0) { mma16z(c0, wA[0], b[0], b[1]); mma16z(c1, wA[1], b[2], b[3]); STAMP(0); }
                else { mma16(c0, wA[2 * i], b[0], b[1]); mma16(c1, wA[2 * i + 1], b[2], b[3]); }
            }
        }
        const uint32_t p0 = pack_bf16(c0[0] + c1[0], c0[1] + c1[1]), p1 = pack_bf16(c0[2] + c1[2], c0[3] + c1[3]);
        if (!isv) {
            stsm2t(sb + S_QM + w * 256 + L16, p0, p1);
            STAMP(1);
            __syncthreads();
            if (ROLE == 0 || __builtin_expect(wq == 0, 1)) {
                uint32_t q0[4], q1[4];
                ldsm4(q0, sb + S_QM + L16);
                if (ROLE == 1) ldsm4(k0, sb + S_KM + L16);
                ldsm4(q1, sb + S_QM + 512 + L16);
                if (ROLE == 1) ldsm4(k1, sb + S_KM + 512 + L16);
                float e0[4], o0[4], e1[4], o1[4];
                mma16z(e0, q0, k0[0], k0[1]);
                mma16z(o0, q0, k0[2], k0[3]);
                mma16z(e1, q1, k1[0], k1[1]);
                mma16z(o1, q1, k1[2], k1[3]);
                const uint32_t s0 = __float_as_uint((e0[0] + o0[2]) + (e1[0] + o1[2])), s1 = __float_as_uint((e0[1] + o0[3]) + (e1[1] + o1[3]));
                const uint32_t off = S_SP + j * 1280 + w * 256 + L8;
                st_async64(peerB + off, s0, s1, peerB + B_S);
                st_async64(peerA + off, s0, s1, peerA + B_S);
                sts64(sb + off, s0, s1);
                __syncwarp();
                if (ROLE == 0) mbar_arrive_if0(sb + B_S, L16); else mbar_expect_if0(sb + B_S, 1280 + 2048, L16);
                STAMP(2);
                if (ROLE == 1) {
                    if (L16 == 0) {
                        if (s + 3 < XLIM) mbar_expect(sb + B_X + (par ^ 1) * 8, XB_BYTES);
                        mbar_expect(sb + B_VX + (par ^ 1) * 8, 8192);
                        if (s == 2 && h == 0 && j == 0) g_zero_cnt = 0;
                    }
                    __syncwarp();
                    if (s + 3 < XLIM && j == par) {
                        mbar_wait(sb + B_S, par);
                        delay(XTMA_DELAY);
                        if (L16 == 0) tma3d_mc(sb + S_XB + (par ^ 1) * XB_BYTES, tmX, 0, (s + 3) * SEG, 0, sb + B_X + (par ^ 1) * 8, 7);
                        __syncwarp();
                    }
                }
            } else {
                if (s + 2 < XLIM) mbar_wait(sb + B_X + par * 8, ((s + 2) >> 1) & 1);
                const int rt = (wq == 3) ? 0 : 1;
                const uint32_t qa = sb + S_QX + par * 4096 + rt * 2048 + (L16 & 0x80) * 8 + (L16 & 0x170);
                const uint32_t kb0 = (wq == 2 ? kx + 2048 : sb + S_KM) + L16;
                const uint32_t kb1 = (wq == 2 ? kx + 3072 : kx) + L16;
                const uint32_t kb2 = kx + 1024 + L16;
                float a0[4], a1[4], a2[4];
#pragma unroll
                for (int hf = 0; hf < 2; hf++) {
                    uint32_t qa0[4], qa1[4], b0[4], b1[4], b2[4];
                    ldsm4(qa0, qa + hf * 512);
                    ldsm4(b0, kb0 + hf * 512);
                    ldsm4(b1, kb1 + hf * 512);
                    ldsm4(b2, kb2 + hf * 512);
                    ldsm4(qa1, qa + hf * 512 + 128);
                    if (hf == 0) { mma16z(a0, qa0, b0[0], b0[1]); mma16z(a1, qa0, b1[0], b1[1]); mma16z(a2, qa0, b2[0], b2[1]); }
                    else { mma16(a0, qa0, b0[0], b0[1]); mma16(a1, qa0, b1[0], b1[1]); mma16(a2, qa0, b2[0], b2[1]); }
                    mma16(a0, qa1, b0[2], b0[3]);
                    mma16(a1, qa1, b1[2], b1[3]);
                    mma16(a2, qa1, b2[2], b2[3]);
                }
                mbar_wait(sb + B_S, par);
                delay(SX_DELAY);
                const uint32_t dst = peerB + S_SX + par * 10240 + j * 5120 + rt * 2560 + L8;
                const uint32_t bar = peerB + B_SX + par * 8;
                const uint32_t T0 = (wq == 2 ? 2 : 4) * 256, T1 = (wq == 2 ? 3 : 0) * 256;
                st_async64(dst + T0, __float_as_uint(a0[0]), __float_as_uint(a0[1]), bar);
                st_async64(dst + 1280 + T0, __float_as_uint(a0[2]), __float_as_uint(a0[3]), bar);
                if (wq != 2) st_async64(dst + T1, __float_as_uint(a1[0]), __float_as_uint(a1[1]), bar);
                st_async64(dst + 1280 + T1, __float_as_uint(a1[2]), __float_as_uint(a1[3]), bar);
                if (wq == 1) st_async64(dst + 256, __float_as_uint(a2[0]), __float_as_uint(a2[1]), bar);
                if (wq != 2) st_async64(dst + 1280 + 256, __float_as_uint(a2[2]), __float_as_uint(a2[3]), bar);
            }
        } else {
            const uint32_t off = S_VM + (s & 3) * 2048 + w * 256 + L8;
            st_async64(peerA + off, p0, p1, peerA + B_S);
            st_async64(peerB + off, p0, p1, peerB + B_S);
            sts64(sb + off, p0, p1);
            STAMP(1);
            __syncwarp();
            mbar_expect_if0(sb + B_S, 320, L16);
            {
                uint32_t px[5];
                lds128(px, sb + S_PX + wq * 512 + L16);
                px[4] = __float_as_uint(lds32f(sb + S_PX + 2048 + wq * 128 + (L16 >> 2)));
                x_pv(sb, s + 2, wg, wq, L16, px);
            }
            if (ROLE == 3) {
                if (wq == 0) {
                    if (L16 == 0 && s + 1 < NSEG) {
                        fence_async_smem();
                        bulk_s2g(g_vx + (h * 2 + (par ^ 1)) * 512, sb + S_VX + ((s + 1) & 3) * 8192, 8192);
                        bulk_commit();
                    }
                } else if (wq == 1) {
                    if (L16 == 0) {
                        mbar_expect(sb + B_SX + par * 8, 7168);
                        if (s + 3 < XLIM) mbar_expect(sb + B_X + (par ^ 1) * 8, XB_BYTES);
                        if (s >= 3) ox_publish(s - 3, h);
                    }
                }
                __syncwarp();
                if (s >= 1) x_scores(sb, s - 1, wq, L16, sx);
                if (s + 2 < XLIM) mbar_wait(sb + B_X + par * 8, ((s + 2) >> 1) & 1);
            }
            STAMP(2);
        }
        if (s == NSEG - 1) break;
        slot += SLOT_BYTES;
        char* const rslot = slot + j * 8192;
        if (wg == 0) {
            if (!isv) mbar_wait(sb + B_VX + par * 8, (s >> 1) & 1);
            uint32_t va[4][4];
            const uint32_t vx = sb + S_VX + (s & 3) * 8192 + wq * 2048 + L16;
            const uint32_t vm = sb + S_VM + (s & 3) * 2048 + wq * 512 + L8;
#pragma unroll
            for (int i = 0; i < 4; i++) lds128(va[i], vx + i * 512);
            STAMP(10);
            mbar_wait(sb + B_S, par);
            STAMP(3);
            float sv[10];
#pragma unroll
            for (int T = 0; T < 5; T++) {
                const float2 a = lds64f(sb + S_SP + T * 256 + L8), b = lds64f(sb + S_SP + 1280 + T * 256 + L8);
                sv[2 * T] = a.x + b.x; sv[2 * T + 1] = a.y + b.y;
            }
            uint32_t p[5];
            softmax_exp(sv);
#pragma unroll
            for (int i = 0; i < 5; i++) p[i] = pack_bf16(sv[2 * i], sv[2 * i + 1]);
            uint32_t vm0[2], vm1[2];
            lds64(vm0, vm);
            lds64(vm1, vm + 256);
            const uint32_t ones[4] = {ONES, ONES, ONES, ONES};
            float sum[4], o0[4], o1[4];
            mma16z(o0, va[0], p[0], p[1]);
            mma16z(o1, va[2], p[0], p[1]);
            mma16z(sum, ones, p[0], p[1]);
            mma16(o0, va[1], p[2], p[3]);
            mma16(o1, va[3], p[2], p[3]);
            mma16(sum, ones, p[2], p[3]);
            mma8(o0, vm0[0], vm0[1], p[4]);
            mma8(o1, vm1[0], vm1[1], p[4]);
            mma8(sum, ONES, ONES, p[4]);
            stsm4t(sb + S_OM + wq * 512 + L16, pack_bf16(o0[0], o0[1]), pack_bf16(o0[2], o0[3]), pack_bf16(o1[0], o1[1]), pack_bf16(o1[2], o1[3]));
            sts64(sb + S_SUM + wq * 256 + L8, __float_as_uint(sum[0]), __float_as_uint(sum[1]));
        }
        STAMP(4);
        __syncthreads();
        {
            float a0[4], a1[4], e[4];
            uint32_t b[4][4];
#pragma unroll
            for (int i = 0; i < 4; i++) ldsm4(b[i], sb + S_OM + i * 512 + L16);
            float2 sc = lds64f(sb + S_SUM + L8);
            float sr = lds32f(sb + S_SUM + ((L16 >> 4) & 0x1C));
            float r0, r1, rr;
#pragma unroll
            for (int i = 0; i < 4; i++) {
                if (i == 0) {
                    mma16z(a0, woA[0], b[0][0], b[0][1]); mma16z(a1, woA[1], b[0][2], b[0][3]);
                    STAMP(5);
                    mma_sp<0>(e, b[0], woB[0]);
                } else {
                    if (i == RCP_AT) {
                        const uint32_t z = __float_as_uint(a0[0]) & zero;
                        mma16(a0, woA[2 * i], b[i][0], b[i][1]); mma16(a1, woA[2 * i + 1], b[i][2], b[i][3]);
                        mma_sp<1>(e, b[i], woB[i]);
                        r0 = rcp(__uint_as_float(__float_as_uint(sc.x) | z));
                        r1 = rcp(__uint_as_float(__float_as_uint(sc.y) | z));
                        rr = rcp(__uint_as_float(__float_as_uint(sr) | z));
                    } else {
                        mma16(a0, woA[2 * i], b[i][0], b[i][1]); mma16(a1, woA[2 * i + 1], b[i][2], b[i][3]);
                        mma_sp<1>(e, b[i], woB[i]);
                    }
                }
            }
            asm volatile("red.relaxed.gpu.global.add.noftz.v4.bf16x2 [%0], {%1,%2,%3,%4};"
                         ::"l"(rslot), "r"(pack_bf16((a0[0] + a1[0]) * r0, (a0[1] + a1[1]) * r1)), "r"(pack_bf16((a0[2] + a1[2]) * r0, (a0[3] + a1[3]) * r1)),
                           "r"(pack_bf16((e[0] + e[2]) * rr, (e[1] + e[3]) * rr)), "r"(0x3F80u) : "memory");
        }
        STAMP(6);
        if (wg == 0) {
            const uint32_t xb = xdesc + par * (XB_BYTES >> 4);
            float xd[16];
            asm volatile("bar.sync 4, 128;" ::: "memory");
            wg_fence();
            x_project<0, POLL_AT>(xd, wA, xb);
            wg_commit();
            x_project<POLL_AT, 36>(xd, wA, xb);
            wg_commit();
            wg_wait<1>();
            asm volatile("bar.arrive 1, 256;" ::: "memory");
            delay(isv ? POLL_DELAY_V : POLL_DELAY);
            STAMP(7);
#pragma unroll
            for (int i = 0; i < 6; i++) v[i] = ld_poll(slot + i * 4096);
            wg_wait<0>();
            x_epilogue(sb, xd, s + 2, isv, w, L16);
            STAMP(8);
        } else {
            if (isv) {
                uint32_t px[5];
                x_softmax(sx, px);
                sts128(sb + S_PX + wq * 512 + L16, px[0], px[1], px[2], px[3]);
                sts32(sb + S_PX + 2048 + wq * 128 + (L16 >> 2), px[4]);
            }
            STAMP(10);
        }
        s++;
    }
    if (ROLE == 0) { mbar_wait(sb + B_VX + 8, ((NSEG - 1) >> 1) & 1); mbar_wait(sb + B_S, 1); }
    if (isv) {
        __syncthreads();
        uint32_t px[5];
        if (ROLE == 3) {
            if (wq == 1 && L16 == 0) ox_store(sb, NSEG - 3, h);
            __syncwarp();
            x_softmax(sx, px);
            x_pv(sb, NSEG - 2, 0, wq, L16, px);
            x_pv(sb, NSEG - 2, 1, wq, L16, px);
            if (wq == 1 && L16 == 0) ox_publish(NSEG - 3, h);
            __syncwarp();
            asm volatile("bar.arrive 1, 256;" ::: "memory");
            asm volatile("bar.sync 2, 128;" ::: "memory");
            if (wq == 1 && L16 == 0) { ox_store(sb, NSEG - 2, h); ox_publish(NSEG - 2, h); }
        } else {
            mbar_wait(sb + B_S, 1);
            x_scores(sb, NSEG - 1, wq, L16, sx);
            x_softmax(sx, px);
            asm volatile("bar.sync 1, 256;" ::: "memory");
            x_pv(sb, NSEG - 1, 0, wq, L16, px);
            x_pv(sb, NSEG - 1, 1, wq, L16, px);
            asm volatile("bar.sync 3, 128;" ::: "memory");
            if (wq == 0 && L16 == 0) { ox_store(sb, NSEG - 1, h); ox_publish(NSEG - 1, h); }
        }
    }
}

__global__ void __launch_bounds__(256, 1)
chain_kernel(const __grid_constant__ CUtensorMap tmWq, const __grid_constant__ CUtensorMap tmWk, const __grid_constant__ CUtensorMap tmWv,
             const __grid_constant__ CUtensorMap tmWo, const __grid_constant__ CUtensorMap tmX, const bf16* __restrict__ mem0) {
    extern __shared__ __align__(1024) uint8_t smem[];
    const uint32_t sb = smem_u32(smem);
    const int tid = threadIdx.x;
    const uint32_t L16 = __shfl_sync(0xffffffffu, (tid & 31) * 16, tid & 31);
    const uint32_t L8 = __shfl_sync(0xffffffffu, (tid & 31) * 8, tid & 31);
    const int w = __shfl_sync(0xffffffffu, tid >> 5, 0), wg = w >> 2, wq = w & 3;
    uint32_t j, h;
    asm("mov.u32 %0, %%cluster_ctarank;" : "=r"(j));
    asm("mov.u32 %0, %%clusterid.x;" : "=r"(h));
    j = __shfl_sync(0xffffffffu, j, 0);
    h = __shfl_sync(0xffffffffu, h, 0);
    const bool isv = (j == 2);
    const uint32_t peerA = mapa(sb, isv ? 0 : (j ^ 1)), peerB = mapa(sb, isv ? 1 : 2);

    if (tid == 0) {
        for (int c = 0; c < 3; c++) mbar_init(sb + B_W + 8 * c, 1);
        mbar_init(sb + B_WO, 1);
        mbar_init(sb + B_X, 1); mbar_init(sb + B_X + 8, 1);
        mbar_init(sb + B_S, isv ? 8 : 5);
        mbar_init(sb + B_VX, 1); mbar_init(sb + B_VX + 8, 1);
        mbar_init(sb + B_SX, 1); mbar_init(sb + B_SX + 8, 1);
        asm volatile("fence.mbarrier_init.release.cluster;" ::: "memory");
        const CUtensorMap* m0 = isv ? &tmWv : &tmWq;
        const CUtensorMap* m1 = isv ? &tmWv : &tmWk;
        const int c0 = h * 128 + (isv ? 0 : 64 * j), c1 = h * 128 + (isv ? 64 : 64 * j);
        mbar_expect(sb + B_X, XB_BYTES);
        tma3d(sb + S_XB, &tmX, 0, 0, 0, sb + B_X);
        for (int c = 0; c < 3; c++) {
            mbar_expect(sb + B_W + 8 * c, 49152);
            tma2d(sb + S_W + c * 24576, m0, c0, c * 192, sb + B_W + 8 * c);
            tma2d(sb + S_W + 73728 + c * 24576, m1, c1, c * 192, sb + B_W + 8 * c);
        }
        mbar_expect(sb + B_X + 8, XB_BYTES);
        tma3d(sb + S_XB + XB_BYTES, &tmX, 0, 32, 0, sb + B_X + 8);
        for (int b = 0; b < 3; b++) tma2d_prefetch(&tmWo, 192 * j + 64 * b, h * 128);
    }
    {
        uint4* z = g_acc + blockIdx.x * 1024 + tid;
#pragma unroll
        for (int i = 0; i < 4; i++) z[i * 256] = make_uint4(0, 0, 0, 0);
        if (blockIdx.x == 0) g_flag[tid] = 0;
        __threadfence();
        __syncthreads();
        if (tid == 0) red_release(&g_zero_cnt, 1);
        asm volatile("griddepcontrol.launch_dependents;" ::: "memory");
    }

    uint32_t wA[36][4], woA[8][4], woB[4][4];
    {
        const int m = (tid & 31) >> 3, r = tid & 7;
        const int blk = (!isv && wg == 1) ? ((wq & 2) * 2 + (wq & 1) + (m & 1) * 2) : (2 * wq + (m & 1));
        const uint32_t a = sb + S_W + wg * 73728 + ((m >> 1) * 8 + r) * 128 + ((blk ^ r) << 4);
#pragma unroll
        for (int c = 0; c < 3; c++) {
            mbar_wait(sb + B_W + 8 * c, 0);
#pragma unroll
            for (int i = 12 * c; i < 12 * c + 12; i++) ldsm4t(wA[i], a + i * 2048);
        }
    }
    fence_async_smem();
    cluster_sync();
    if (tid == 0) {
        mbar_expect(sb + B_WO, 49152);
        for (int b = 0; b < 3; b++) tma2d(sb + S_WO + b * 16384, &tmWo, 192 * j + 64 * b, h * 128, sb + B_WO);
    }
    {
        float xd[16];
        mbar_wait(sb + B_X, 0);
        wg_fence();
        x_project<0, 36>(xd, wA, desc_lo(sb + S_XB));
        wg_commit();
        wg_wait<0>();
        x_epilogue(sb, xd, 0, isv, w, L16);
        fence_async_smem();
        __syncthreads();
        if (tid == 0) {
            mbar_expect(sb + B_X, XB_BYTES);
            tma3d(sb + S_XB, &tmX, 0, 64, 0, sb + B_X);
            if (!isv) mbar_expect(sb + B_VX, 8192);
            else {
                bulk_s2c(peerA + S_VX, sb + S_VX, 8192, peerA + B_VX);
                bulk_s2c(peerB + S_VX, sb + S_VX, 8192, peerB + B_VX);
            }
        }
        __syncwarp();
        mbar_wait(sb + B_X + 8, 0);
    }
    {
        mbar_wait(sb + B_WO, 0);
        const int m = (tid & 31) >> 3, r = tid & 7;
        const int ca = 3 * w + (m & 1), cb = 3 * w + 2;
        const uint32_t aA = sb + S_WO + (ca >> 3) * 16384 + ((m >> 1) * 8 + r) * 128 + (((ca & 7) ^ r) << 4);
        const int eB = ((m & 2) + ((r >> 1) & 1)) * 8 + 4 * (m & 1) + 2 * (r >> 2) + (r & 1);
        const uint32_t aB = sb + S_WO + (cb >> 3) * 16384 + eB * 128 + (((cb & 7) ^ (eB & 7)) << 4);
#pragma unroll
        for (int i = 0; i < 8; i++) ldsm4t(woA[i], aA + i * 2048);
#pragma unroll
        for (int i = 0; i < 4; i++) ldsm4t(woB[i], aB + i * 4096);
        if (tid == 0) {
            unsigned c = 0;
            while (ld_acquire(&g_zero_cnt) < 96 && ++c < SPIN_LIM) {}
        }
    }
    char* slot = reinterpret_cast<char*>(g_acc) + (tid >> 2) * 128 + (tid & 3) * 16;
    __syncwarp();
    cluster_sync();

#define CHAIN_ARGS sb, L16, L8, wq, j, h, peerA, peerB, wA, woA, woB, &tmX, slot, mem0
    if (!isv) { if (wg == 0) chain_steps<0>(CHAIN_ARGS); else chain_steps<1>(CHAIN_ARGS); }
    else { if (wg == 0) chain_steps<2>(CHAIN_ARGS); else chain_steps<3>(CHAIN_ARGS); }
    __syncwarp();
    cluster_sync();
}

__device__ float g_K[DM * SEQ];

__global__ void naive_outproj(const bf16* __restrict__ Wo, bf16* __restrict__ out) {
    __shared__ float o[4096];
    const int t = blockIdx.x, seg = t >> 5, r = t & 31;
    const bf16* ox = reinterpret_cast<const bf16*>(g_ox);
    for (int i = threadIdx.x; i < 4096; i += blockDim.x) {
        int h = i >> 7, e = i & 127;
        o[i] = __bfloat162float(ox[(seg * 32 + h) * 4096 + (e >> 6) * 2048 + r * 64 + ((((e & 63) >> 3) ^ (r & 7)) << 3) + (e & 7)]);
    }
    __syncthreads();
    float acc = 0;
    for (int i = 0; i < 4096; i++) acc += o[i] * __bfloat162float(Wo[i * DM + threadIdx.x]);
    out[t * OUTW + threadIdx.x] = __float2bfloat16(acc);
}
__global__ void naive_kgen(const bf16* logA, const bf16* Aim, const bf16* Cr, const bf16* Ci, const bf16* logdt) {
    const int d = blockIdx.x;
    const float dt = __bfloat162float(__float2bfloat16(expf(__bfloat162float(logdt[d]))));
    for (int l = threadIdx.x; l < SEQ; l += blockDim.x) {
        const float pos = __bfloat162float(__float2bfloat16((float)l));
        float acc = 0;
        for (int n = 0; n < NST; n++) {
            float ar = -__bfloat162float(__float2bfloat16(expf(__bfloat162float(logA[d * NST + n])))) * dt;
            float ai = __bfloat162float(Aim[d * NST + n]) * dt;
            float cr = __bfloat162float(Cr[d * NST + n]) * dt, ci = __bfloat162float(Ci[d * NST + n]) * dt;
            float mg = expf(ar * pos), sn, cs;
            sincosf(ai * pos, &sn, &cs);
            acc += mg * (cr * cs - ci * sn);
        }
        g_K[d * SEQ + l] = 2.f * acc;
    }
}
__global__ void naive_conv(const bf16* u, const bf16* Dsk, bf16* out) {
    __shared__ float us[SEQ], ks[SEQ];
    const int d = blockIdx.x;
    for (int l = threadIdx.x; l < SEQ; l += blockDim.x) { us[l] = __bfloat162float(u[l * DM + d]); ks[l] = g_K[d * SEQ + l]; }
    __syncthreads();
    for (int l = threadIdx.x; l < SEQ; l += blockDim.x) {
        float acc = 0;
        for (int i = 0; i <= l; i++) acc += ks[l - i] * us[i];
        float y = __bfloat162float(__float2bfloat16(acc));
        float sk = __bfloat162float(__float2bfloat16(us[l] * __bfloat162float(Dsk[d])));
        out[l * OUTW + DM + d] = __float2bfloat16(y + sk);
    }
}

typedef CUresult (*EncodeFn)(CUtensorMap*, CUtensorMapDataType, cuuint32_t, void*, const cuuint64_t*, const cuuint64_t*, const cuuint32_t*,
                             const cuuint32_t*, CUtensorMapInterleave, CUtensorMapSwizzle, CUtensorMapL2promotion, CUtensorMapFloatOOBfill);

void make_map(EncodeFn fn, CUtensorMap* m, const void* p, int rank, const cuuint64_t* dims, const cuuint64_t* strides, const cuuint32_t* box) {
    const cuuint32_t es[3] = {1, 1, 1};
    fn(m, CU_TENSOR_MAP_DATA_TYPE_BFLOAT16, rank, const_cast<void*>(p), dims, strides, box, es, CU_TENSOR_MAP_INTERLEAVE_NONE,
       CU_TENSOR_MAP_SWIZZLE_128B, CU_TENSOR_MAP_L2_PROMOTION_L2_128B, CU_TENSOR_MAP_FLOAT_OOB_FILL_NONE);
}

}

extern "C" void kernel_launch(void* const* d_in, const int* in_sizes, int n_in, void* d_out, int out_size) {
    const bf16* x = (const bf16*)d_in[0];
    const bf16* mem0 = (const bf16*)d_in[1];
    const bf16* Wo = (const bf16*)d_in[5];
    bf16* out = (bf16*)d_out;

    static EncodeFn enc = nullptr;
    if (!enc) {
        void* fn = nullptr;
        cudaDriverEntryPointQueryResult st;
        cudaGetDriverEntryPoint("cuTensorMapEncodeTiled", &fn, cudaEnableDefault, &st);
        enc = (EncodeFn)fn;
        cudaFuncSetAttribute(chain_kernel, cudaFuncAttributeMaxDynamicSharedMemorySize, A_SMEM);
    }
    CUtensorMap tmW[3], tmWo, tmX;
    {
        const cuuint64_t dims[2] = {4096, 576}, str[1] = {8192};
        const cuuint32_t box[2] = {64, 192};
        for (int i = 0; i < 3; i++) make_map(enc, &tmW[i], d_in[2 + i], 2, dims, str, box);
    }
    {
        const cuuint64_t dims[2] = {576, 4096}, str[1] = {1152};
        const cuuint32_t box[2] = {64, 128};
        make_map(enc, &tmWo, Wo, 2, dims, str, box);
    }
    {
        const cuuint64_t dims[3] = {64, 2048, 9}, str[2] = {1152, 128};
        const cuuint32_t box[3] = {64, 32, 9};
        make_map(enc, &tmX, x, 3, dims, str, box);
    }
    cudaStream_t st = cudaStreamPerThread;
    {
        cudaLaunchConfig_t cfg = {};
        cfg.gridDim = dim3(96); cfg.blockDim = dim3(256); cfg.dynamicSmemBytes = A_SMEM; cfg.stream = st;
        cudaLaunchAttribute at[1];
        at[0].id = cudaLaunchAttributeClusterDimension;
        at[0].val.clusterDim.x = 3; at[0].val.clusterDim.y = 1; at[0].val.clusterDim.z = 1;
        cfg.attrs = at; cfg.numAttrs = 1;
        cudaLaunchKernelEx(&cfg, chain_kernel, tmW[0], tmW[1], tmW[2], tmWo, tmX, mem0);
    }
    naive_outproj<<<SEQ, DM, 0, st>>>(Wo, out);
    naive_kgen<<<DM, 256, 0, st>>>((const bf16*)d_in[8], (const bf16*)d_in[9], (const bf16*)d_in[10], (const bf16*)d_in[11], (const bf16*)d_in[12]);
    naive_conv<<<DM, 256, 0, st>>>((const bf16*)d_in[7], (const bf16*)d_in[13], out);
}
```

```cpp
#include <cuda_runtime.h>
#include <cuda_bf16.h>
#include <cuda_fp16.h>
#include <cuda.h>
#include <stdint.h>

typedef __nv_bfloat16 bf16;

namespace {

constexpr int DM = 576, NH = 32, DH = 128, SEG = 32, NSEG = 64, SEQ = 2048, NST = 128;
constexpr int OUTW = 2 * DM;
constexpr unsigned SPIN_LIM = 1u << 15;

constexpr int SLOT_BYTES = 768 * 32;
__device__ __align__(1024) uint4 g_acc[NSEG * SLOT_BYTES / 16];
__device__ __align__(1024) uint4 g_ox[NSEG * NH * 512];
__device__ __align__(1024) uint4 g_vx[NH * 2 * 512];
__device__ unsigned g_flag[NSEG * 4];
__device__ unsigned g_zero_cnt;

__device__ __forceinline__ uint32_t smem_u32(const void* p) { return (uint32_t)__cvta_generic_to_shared(p); }
__device__ __forceinline__ unsigned clk() { unsigned c; asm volatile("mov.u32 %0, %%clock;" : "=r"(c)::"memory"); return c; }
__device__ __forceinline__ unsigned gtime() { unsigned t; asm volatile("mov.u32 %0, %%globaltimer_lo;" : "=r"(t)::"memory"); return t; }
__device__ __forceinline__ uint32_t mapa(uint32_t a, uint32_t r) { uint32_t o; asm("mapa.shared::cluster.u32 %0, %1, %2;" : "=r"(o) : "r"(a), "r"(r)); return o; }
__device__ __forceinline__ void mbar_init(uint32_t b, uint32_t n) { asm volatile("mbarrier.init.shared::cta.b64 [%0], %1;" ::"r"(b), "r"(n) : "memory"); }
__device__ __forceinline__ void mbar_arrive(uint32_t b) { asm volatile("mbarrier.arrive.shared::cta.b64 _, [%0];" ::"r"(b) : "memory"); }
__device__ __forceinline__ void mbar_expect(uint32_t b, uint32_t tx) { asm volatile("mbarrier.arrive.expect_tx.shared::cta.b64 _, [%0], %1;" ::"r"(b), "r"(tx) : "memory"); }
__device__ __forceinline__ bool mbar_try(uint32_t b, uint32_t par) {
    uint32_t ok;
    asm volatile("{.reg .pred p; mbarrier.try_wait.parity.shared::cta.b64 p, [%1], %2; selp.u32 %0, 1, 0, p;}" : "=r"(ok) : "r"(b), "r"(par) : "memory");
    return ok;
}
__device__ __forceinline__ bool mbar_test(uint32_t b, uint32_t par) {
    uint32_t ok;
    asm volatile("{.reg .pred p; mbarrier.test_wait.parity.shared::cta.b64 p, [%1], %2; selp.u32 %0, 1, 0, p;}" : "=r"(ok) : "r"(b), "r"(par) : "memory");
    return ok;
}
__device__ __forceinline__ void mbar_wait(uint32_t b, uint32_t par) {
    asm volatile("{.reg .pred p, q; .reg .u32 c; mov.u32 c, 0;\n"
                 "W: mbarrier.try_wait.parity.shared::cta.b64 p, [%0], %1;\n"
                 "@p bra D;\n add.u32 c, c, 1; setp.lt.u32 q, c, %2;\n @q bra W;\n D:\n}" ::"r"(b), "r"(par), "n"(SPIN_LIM) : "memory");
}
__device__ __forceinline__ void cluster_sync() { asm volatile("barrier.cluster.arrive.aligned; barrier.cluster.wait.aligned;" ::: "memory"); }
__device__ __forceinline__ void fence_async_smem() { asm volatile("fence.proxy.async.shared::cta;" ::: "memory"); }
__device__ __forceinline__ void ldsm4(uint32_t* r, uint32_t a) { asm volatile("ldmatrix.sync.aligned.m8n8.x4.shared.b16 {%0,%1,%2,%3},[%4];" : "=r"(r[0]), "=r"(r[1]), "=r"(r[2]), "=r"(r[3]) : "r"(a) : "memory"); }
__device__ __forceinline__ void ldsm4t(uint32_t* r, uint32_t a) { asm volatile("ldmatrix.sync.aligned.m8n8.x4.trans.shared.b16 {%0,%1,%2,%3},[%4];" : "=r"(r[0]), "=r"(r[1]), "=r"(r[2]), "=r"(r[3]) : "r"(a) : "memory"); }
__device__ __forceinline__ void stsm1(uint32_t a, uint32_t r0) { asm volatile("stmatrix.sync.aligned.m8n8.x1.shared.b16 [%0],{%1};" ::"r"(a), "r"(r0) : "memory"); }
__device__ __forceinline__ void stsm2t(uint32_t a, uint32_t r0, uint32_t r1) { asm volatile("stmatrix.sync.aligned.m8n8.x2.trans.shared.b16 [%0],{%1,%2};" ::"r"(a), "r"(r0), "r"(r1) : "memory"); }
__device__ __forceinline__ void stsm4t(uint32_t a, uint32_t r0, uint32_t r1, uint32_t r2, uint32_t r3) { asm volatile("stmatrix.sync.aligned.m8n8.x4.trans.shared.b16 [%0],{%1,%2,%3,%4};" ::"r"(a), "r"(r0), "r"(r1), "r"(r2), "r"(r3) : "memory"); }
__device__ __forceinline__ void sts32(uint32_t a, uint32_t v) { asm volatile("st.shared.b32 [%0], %1;" ::"r"(a), "r"(v) : "memory"); }
__device__ __forceinline__ void sts64(uint32_t a, uint32_t x, uint32_t y) { asm volatile("st.shared.v2.b32 [%0], {%1,%2};" ::"r"(a), "r"(x), "r"(y) : "memory"); }
__device__ __forceinline__ void sts128(uint32_t a, uint32_t x, uint32_t y, uint32_t z, uint32_t w) { asm volatile("st.shared.v4.b32 [%0], {%1,%2,%3,%4};" ::"r"(a), "r"(x), "r"(y), "r"(z), "r"(w) : "memory"); }
__device__ __forceinline__ void lds64(uint32_t* r, uint32_t a) { asm volatile("ld.shared.v2.b32 {%0,%1},[%2];" : "=r"(r[0]), "=r"(r[1]) : "r"(a) : "memory"); }
__device__ __forceinline__ float2 lds64f(uint32_t a) { float2 v; asm volatile("ld.shared.v2.f32 {%0,%1},[%2];" : "=f"(v.x), "=f"(v.y) : "r"(a) : "memory"); return v; }
__device__ __forceinline__ void lds128(uint32_t* r, uint32_t a) { asm volatile("ld.shared.v4.b32 {%0,%1,%2,%3},[%4];" : "=r"(r[0]), "=r"(r[1]), "=r"(r[2]), "=r"(r[3]) : "r"(a) : "memory"); }
__device__ __forceinline__ void st_async64(uint32_t a, uint32_t x, uint32_t y, uint32_t bar) {
    asm volatile("st.async.weak.shared::cluster.mbarrier::complete_tx::bytes.v2.b32 [%0], {%1,%2}, [%3];" ::"r"(a), "r"(x), "r"(y), "r"(bar) : "memory");
}
__device__ __forceinline__ void st_async32(uint32_t a, uint32_t x, uint32_t bar) {
    asm volatile("st.async.weak.shared::cluster.mbarrier::complete_tx::bytes.b32 [%0], %1, [%2];" ::"r"(a), "r"(x), "r"(bar) : "memory");
}
__device__ __forceinline__ void ldsm2(uint32_t* r, uint32_t a) { asm volatile("ldmatrix.sync.aligned.m8n8.x2.shared.b16 {%0,%1},[%2];" : "=r"(r[0]), "=r"(r[1]) : "r"(a) : "memory"); }
__device__ __forceinline__ uint32_t pack_f16_sat(float lo, float hi) { uint32_t r; asm("cvt.rn.satfinite.f16x2.f32 %0, %1, %2;" : "=r"(r) : "f"(hi), "f"(lo)); return r; }
__device__ __forceinline__ __half2 as_h2(uint32_t x) { return *reinterpret_cast<__half2*>(&x); }
__device__ __forceinline__ uint32_t as_u32(__half2 x) { return *reinterpret_cast<uint32_t*>(&x); }
__device__ __forceinline__ uint32_t pack_bf16(float lo, float hi) { uint32_t r; asm("cvt.rn.bf16x2.f32 %0, %1, %2;" : "=r"(r) : "f"(hi), "f"(lo)); return r; }
__device__ __forceinline__ float ex2(float x) { float r; asm("ex2.approx.ftz.f32 %0, %1;" : "=f"(r) : "f"(x)); return r; }
__device__ __forceinline__ float rcp(float x) { float r; asm("rcp.approx.ftz.f32 %0, %1;" : "=f"(r) : "f"(x)); return r; }
__device__ __forceinline__ void mma16(float* d, const uint32_t* a, uint32_t b0, uint32_t b1) {
    asm volatile("mma.sync.aligned.m16n8k16.row.col.f32.bf16.bf16.f32 {%0,%1,%2,%3},{%4,%5,%6,%7},{%8,%9},{%0,%1,%2,%3};"
                 : "+f"(d[0]), "+f"(d[1]), "+f"(d[2]), "+f"(d[3]) : "r"(a[0]), "r"(a[1]), "r"(a[2]), "r"(a[3]), "r"(b0), "r"(b1));
}
__device__ __forceinline__ void mma16z(float* d, const uint32_t* a, uint32_t b0, uint32_t b1) {
    asm volatile("mma.sync.aligned.m16n8k16.row.col.f32.bf16.bf16.f32 {%0,%1,%2,%3},{%4,%5,%6,%7},{%8,%9},{%10,%10,%10,%10};"
                 : "=f"(d[0]), "=f"(d[1]), "=f"(d[2]), "=f"(d[3]) : "r"(a[0]), "r"(a[1]), "r"(a[2]), "r"(a[3]), "r"(b0), "r"(b1), "f"(0.f));
}
__device__ __forceinline__ void mma8(float* d, uint32_t a0, uint32_t a1, uint32_t b0) {
    asm volatile("mma.sync.aligned.m16n8k8.row.col.f32.bf16.bf16.f32 {%0,%1,%2,%3},{%4,%5},{%6},{%0,%1,%2,%3};"
                 : "+f"(d[0]), "+f"(d[1]), "+f"(d[2]), "+f"(d[3]) : "r"(a0), "r"(a1), "r"(b0));
}
template <int ACC>
__device__ __forceinline__ void mma_sp(float* d, const uint32_t* a, const uint32_t* b) {
    if (ACC)
        asm volatile("mma.sp::ordered_metadata.sync.aligned.m16n8k32.row.col.f32.bf16.bf16.f32 {%0,%1,%2,%3},{%4,%5,%6,%7},{%8,%9,%10,%11},{%0,%1,%2,%3},%12,0x0;"
                     : "+f"(d[0]), "+f"(d[1]), "+f"(d[2]), "+f"(d[3])
                     : "r"(a[0]), "r"(a[1]), "r"(a[2]), "r"(a[3]), "r"(b[0]), "r"(b[1]), "r"(b[2]), "r"(b[3]), "r"(0xEEEE4444u));
    else
        asm volatile("mma.sp::ordered_metadata.sync.aligned.m16n8k32.row.col.f32.bf16.bf16.f32 {%0,%1,%2,%3},{%4,%5,%6,%7},{%8,%9,%10,%11},{%13,%13,%13,%13},%12,0x0;"
                     : "=f"(d[0]), "=f"(d[1]), "=f"(d[2]), "=f"(d[3])
                     : "r"(a[0]), "r"(a[1]), "r"(a[2]), "r"(a[3]), "r"(b[0]), "r"(b[1]), "r"(b[2]), "r"(b[3]), "r"(0xEEEE4444u), "f"(0.f));
}
__device__ __forceinline__ void mbar_arrive_if0(uint32_t b, uint32_t z) { asm volatile("{.reg .pred p; setp.eq.u32 p, %1, 0; @p mbarrier.arrive.shared::cta.b64 _, [%0];}" ::"r"(b), "r"(z) : "memory"); }
__device__ __forceinline__ void mbar_expect_if0(uint32_t b, uint32_t tx, uint32_t z) { asm volatile("{.reg .pred p; setp.eq.u32 p, %2, 0; @p mbarrier.arrive.expect_tx.shared::cta.b64 _, [%0], %1;}" ::"r"(b), "r"(tx), "r"(z) : "memory"); }
__device__ __forceinline__ float lds32f(uint32_t a) { float v; asm volatile("ld.shared.f32 %0,[%1];" : "=f"(v) : "r"(a) : "memory"); return v; }
__device__ __forceinline__ void wg_fence() { asm volatile("wgmma.fence.sync.aligned;" ::: "memory"); }
__device__ __forceinline__ void wg_commit() { asm volatile("wgmma.commit_group.sync.aligned;" ::: "memory"); }
template <int N> __device__ __forceinline__ void wg_wait() { asm volatile("wgmma.wait_group.sync.aligned %0;" ::"n"(N) : "memory"); }
__device__ __forceinline__ void delay(unsigned n) { if (n) { const unsigned t0 = clk(); while (clk() - t0 < n) {} } }
template <int ACC, uint32_t DHI = 0x40000040u>
__device__ __forceinline__ void wg_rs_n32(float* d, const uint32_t* a, uint32_t dlo) {
    if (ACC)
        asm volatile("{.reg .b64 db; mov.b64 db, {%20, %21};\n"
                     "wgmma.mma_async.sync.aligned.m64n32k16.f32.bf16.bf16 {%0,%1,%2,%3,%4,%5,%6,%7,%8,%9,%10,%11,%12,%13,%14,%15},{%16,%17,%18,%19},db,1,1,1,0;}"
                     : "+f"(d[0]), "+f"(d[1]), "+f"(d[2]), "+f"(d[3]), "+f"(d[4]), "+f"(d[5]), "+f"(d[6]), "+f"(d[7]),
                       "+f"(d[8]), "+f"(d[9]), "+f"(d[10]), "+f"(d[11]), "+f"(d[12]), "+f"(d[13]), "+f"(d[14]), "+f"(d[15])
                     : "r"(a[0]), "r"(a[1]), "r"(a[2]), "r"(a[3]), "r"(dlo), "r"(DHI));
    else
        asm volatile("{.reg .b64 db; mov.b64 db, {%20, %21};\n"
                     "wgmma.mma_async.sync.aligned.m64n32k16.f32.bf16.bf16 {%0,%1,%2,%3,%4,%5,%6,%7,%8,%9,%10,%11,%12,%13,%14,%15},{%16,%17,%18,%19},db,0,1,1,0;}"
                     : "=f"(d[0]), "=f"(d[1]), "=f"(d[2]), "=f"(d[3]), "=f"(d[4]), "=f"(d[5]), "=f"(d[6]), "=f"(d[7]),
                       "=f"(d[8]), "=f"(d[9]), "=f"(d[10]), "=f"(d[11]), "=f"(d[12]), "=f"(d[13]), "=f"(d[14]), "=f"(d[15])
                     : "r"(a[0]), "r"(a[1]), "r"(a[2]), "r"(a[3]), "r"(dlo), "r"(DHI));
}
__device__ __forceinline__ uint32_t desc_lo(uint32_t addr) { return ((addr & 0x3FFFF) >> 4) | (1u << 16); }
__device__ __forceinline__ void tma2d(uint32_t dst, const CUtensorMap* m, int c0, int c1, uint32_t bar) {
    asm volatile("cp.async.bulk.tensor.2d.shared::cluster.global.mbarrier::complete_tx::bytes [%0], [%1, {%2,%3}], [%4];"
                 ::"r"(dst), "l"(m), "r"(c0), "r"(c1), "r"(bar) : "memory");
}
__device__ __forceinline__ void tma3d(uint32_t dst, const CUtensorMap* m, int c0, int c1, int c2, uint32_t bar) {
    asm volatile("cp.async.bulk.tensor.3d.shared::cluster.global.mbarrier::complete_tx::bytes [%0], [%1, {%2,%3,%4}], [%5];"
                 ::"r"(dst), "l"(m), "r"(c0), "r"(c1), "r"(c2), "r"(bar) : "memory");
}
__device__ __forceinline__ void tma3d_mc(uint32_t dst, const CUtensorMap* m, int c0, int c1, int c2, uint32_t bar, uint16_t mask) {
    asm volatile("cp.async.bulk.tensor.3d.shared::cluster.global.mbarrier::complete_tx::bytes.multicast::cluster [%0], [%1, {%2,%3,%4}], [%5], %6;"
                 ::"r"(dst), "l"(m), "r"(c0), "r"(c1), "r"(c2), "r"(bar), "h"(mask) : "memory");
}
__device__ __forceinline__ void bulk_g2s_mc(uint32_t dst, const void* src, uint32_t bytes, uint32_t bar, uint16_t mask) {
    asm volatile("cp.async.bulk.shared::cluster.global.mbarrier::complete_tx::bytes.multicast::cluster [%0], [%1], %2, [%3], %4;"
                 ::"r"(dst), "l"(src), "r"(bytes), "r"(bar), "h"(mask) : "memory");
}
__device__ __forceinline__ void tma2d_prefetch(const CUtensorMap* m, int c0, int c1) {
    asm volatile("cp.async.bulk.prefetch.tensor.2d.L2.global [%0, {%1,%2}];" ::"l"(m), "r"(c0), "r"(c1) : "memory");
}
__device__ __forceinline__ void bulk_s2c(uint32_t dst, uint32_t src, uint32_t bytes, uint32_t bar) {
    asm volatile("cp.async.bulk.shared::cluster.shared::cta.mbarrier::complete_tx::bytes [%0], [%1], %2, [%3];" ::"r"(dst), "r"(src), "r"(bytes), "r"(bar) : "memory");
}
__device__ __forceinline__ void bulk_s2g(void* dst, uint32_t src, uint32_t bytes) {
    asm volatile("cp.async.bulk.global.shared::cta.bulk_group [%0], [%1], %2;" ::"l"(dst), "r"(src), "r"(bytes) : "memory");
}
__device__ __forceinline__ void bulk_commit() { asm volatile("cp.async.bulk.commit_group;" ::: "memory"); }
__device__ __forceinline__ void bulk_wait0() { asm volatile("cp.async.bulk.wait_group 0;" ::: "memory"); }
__device__ __forceinline__ uint4 ld_poll(const void* p) {
    uint4 v;
    asm volatile("ld.relaxed.gpu.global.v4.u32 {%0,%1,%2,%3},[%4];" : "=r"(v.x), "=r"(v.y), "=r"(v.z), "=r"(v.w) : "l"(p) : "memory");
    return v;
}
__device__ __forceinline__ unsigned ld_acquire(const unsigned* p) { unsigned v; asm volatile("ld.acquire.gpu.global.u32 %0,[%1];" : "=r"(v) : "l"(p) : "memory"); return v; }
__device__ __forceinline__ void red_release(unsigned* p, unsigned v) { asm volatile("red.release.gpu.global.add.u32 [%0], %1;" ::"l"(p), "r"(v) : "memory"); }

__device__ __forceinline__ void publish(unsigned* p) {
    asm volatile("fence.proxy.async.global;" ::: "memory");
    asm volatile("red.relaxed.gpu.global.add.u32 [%0], 1;" ::"l"(p) : "memory");
}
template <int ID, int N> __device__ __forceinline__ void bar_sync() { asm volatile("bar.sync %0, %1;" ::"n"(ID), "n"(N) : "memory"); }
template <int ID, int N> __device__ __forceinline__ void bar_arrive() { asm volatile("bar.arrive %0, %1;" ::"n"(ID), "n"(N) : "memory"); }
__device__ __forceinline__ void cluster_arrive() { asm volatile("barrier.cluster.arrive.relaxed.aligned;" ::: "memory"); }
__device__ __forceinline__ void cluster_wait() { asm volatile("barrier.cluster.wait.aligned;" ::: "memory"); }

constexpr uint32_t XB_BYTES = 36864;
constexpr uint32_t S_XB = 0;
constexpr uint32_t S_QM = 73728;
constexpr uint32_t S_KM = 74752;
constexpr uint32_t S_OM = 75776;
constexpr uint32_t S_SP = 77824;
constexpr uint32_t S_SUM = 80384;
constexpr uint32_t S_TGT = 81408;
constexpr uint32_t S_VM = 147456;
constexpr uint32_t S_QX = 86016;
constexpr uint32_t S_PX = S_QX;
constexpr uint32_t S_KX = 94208;
constexpr uint32_t S_VX = 102400;
constexpr uint32_t S_SX = 135168;
constexpr uint32_t S_OX = 155648;
constexpr uint32_t S_MEM = 172032;
constexpr uint32_t S_WO = 181248;
constexpr uint32_t S_BAR = 230400;
constexpr uint32_t A_SMEM = S_BAR + 128;
__host__ __device__ constexpr uint32_t s_w(int c) { return c == 0 ? S_WO : 73728 + (c - 1) * 49152; }
constexpr uint32_t B_W = S_BAR, B_WO = S_BAR + 24, B_X = S_BAR + 32, B_S = S_BAR + 48, B_VX = S_BAR + 56, B_SX = S_BAR + 72, B_M = S_BAR + 88, B_T = S_BAR + 112;
constexpr int NB_QK = 1, NB_O = 2, NB_RED = 3, NB_P = 4, NB_AUX = 5, NB_PRO = 6, NB_X = 7, NB_GO = 8;

constexpr float SM_SCALE = 0.08838834764831845f * 1.4426950408889634f;
constexpr uint32_t ONES = 0x3F803F80u;
constexpr uint32_t FULL_COUNT = 0x4200u;
#define XLIM NSEG
#define XTMA_DELAY 0
#define SX_DELAY 0
#define TGT_NS 1072
#define LOOK_NS 100
#define RCP_AT 2
#define NCH 2
#define POLL_AT 1
#define OX_DELAY 0
#define XTMA_NS 50
#define REG_MAIN0 232
#define REG_MAIN1 232
#define REG_AUX 40

#define PV_MODE 1
#define OX_AT 1
#define OFF 0
static_assert(REG_MAIN0 + REG_MAIN1 + REG_AUX <= 504, "the three warpgroups share 3 x 168 registers");
#define TSTAMP(i, e) do {} while (0)

__device__ __forceinline__ void load_scores(uint32_t a, __half2 (&hs)[5]) {
    uint32_t r[10];
    ldsm4(r, a);
    ldsm4(r + 4, a + 512);
    ldsm2(r + 8, a + 1024);
    const __half2 hf = as_h2(0x38003800u);
#pragma unroll
    for (int T = 0; T < 5; T++) hs[T] = __hfma2(as_h2(r[2 * T]), hf, __hmul2(as_h2(r[2 * T + 1]), hf));
}
__device__ __forceinline__ void softmax_exp(const __half2 (&hs)[5], float (&ev)[10]) {
    __half2 m = __hmax2(__hmax2(__hmax2(hs[0], hs[1]), __hmax2(hs[2], hs[3])), hs[4]);
    const uint32_t mu = as_u32(m);
    const uint32_t m1 = __shfl_xor_sync(0xffffffffu, mu, 1), m2 = __shfl_xor_sync(0xffffffffu, mu, 2), m3 = __shfl_xor_sync(0xffffffffu, mu, 3);
    m = __hmax2(__hmax2(m, as_h2(m1)), __hmax2(as_h2(m2), as_h2(m3)));
    const float mc = -fmaxf(__low2float(m), __high2float(m)) * (2.f * SM_SCALE);
#pragma unroll
    for (int T = 0; T < 5; T++) {
        ev[2 * T] = ex2(fmaf(__low2float(hs[T]), 2.f * SM_SCALE, mc));
        ev[2 * T + 1] = ex2(fmaf(__high2float(hs[T]), 2.f * SM_SCALE, mc));
    }
}

__device__ __forceinline__ void x_scores(uint32_t sb, int seg, int wq, uint32_t L16, float (&ev)[10]) {
    __half2 hs[5];
    load_scores(sb + S_SX + (seg & 1) * 5120 + wq * 1280 + L16, hs);
    const int dg = (int)(L16 >> 6) - (int)((L16 >> 3) & 6) + 8 * wq;
#pragma unroll
    for (int T = 0; T < 4; T++) {
        uint32_t u = as_u32(hs[T]);
        if (dg < 8 * T + 1) u = (u & 0xFFFFu) | 0xFC000000u;
        if (dg < 8 * T) u = 0xFC00FC00u;
        hs[T] = as_h2(u);
    }
    softmax_exp(hs, ev);
}
__device__ __forceinline__ void x_probs(uint32_t sb, int seg, int wq, uint32_t L16, const float (&ev)[10]) {
    float l = ((ev[0] + ev[1]) + (ev[2] + ev[3])) + ((ev[4] + ev[5]) + (ev[6] + ev[7])) + (ev[8] + ev[9]);
    const float l1 = __shfl_xor_sync(0xffffffffu, l, 1), l2 = __shfl_xor_sync(0xffffffffu, l, 2), l3 = __shfl_xor_sync(0xffffffffu, l, 3);
    const float r = rcp((l + l1) + (l2 + l3));
    const uint32_t a = sb + S_PX + (seg & 1) * 4096 + wq * 640 + (L16 >> 2);
#pragma unroll
    for (int i = 0; i < 5; i++) sts32(a + i * 128, pack_bf16(ev[2 * i] * r, ev[2 * i + 1] * r));
    fence_async_smem();
}
__device__ __forceinline__ void x_pv_load(uint32_t sb, int seg, int w, uint32_t L16, uint32_t (&a)[3][4]) {
    lds128(a[0], sb + S_VX + (seg & 3) * 8192 + w * 1024 + L16);
    lds128(a[1], sb + S_VX + (seg & 3) * 8192 + w * 1024 + 512 + L16);
    lds64(a[2], sb + S_VM + (seg & 3) * 2048 + w * 256 + (L16 >> 1));
    a[2][2] = 0; a[2][3] = 0;
}
__device__ __forceinline__ void x_pv_run(uint32_t sb, int seg, int w, uint32_t L16, const uint32_t (&a)[3][4]) {
    const uint32_t d = ((sb + S_PX + (seg & 1) * 4096) & 0x3FFFF) >> 4;
    float o[16];
    wg_fence();
    wg_rs_n32<0, 40>(o, a[0], d | (8u << 16));
    wg_rs_n32<1, 40>(o, a[1], (d + 16) | (8u << 16));
    wg_rs_n32<1, 40>(o, a[2], d + 32);
    wg_commit();
    wg_wait<0>();
    const uint32_t ox = sb + S_OX + (seg & 1) * 8192 + (w >> 2) * 4096 + (L16 & 0x100) * 4 + (L16 & 0x70) * 8 +
                        ((((w & 3) * 32) | ((L16 >> 3) & 0x10)) ^ (L16 & 0x70));
    stsm4t(ox, pack_bf16(o[0], o[1]), pack_bf16(o[2], o[3]), pack_bf16(o[4], o[5]), pack_bf16(o[6], o[7]));
    stsm4t(ox + 2048, pack_bf16(o[8], o[9]), pack_bf16(o[10], o[11]), pack_bf16(o[12], o[13]), pack_bf16(o[14], o[15]));
}
__device__ __forceinline__ void ox_publish(int seg, uint32_t h) { bulk_wait0(); publish(&g_flag[seg * 4 + (h >> 3)]); }
__device__ __forceinline__ void ox_store(uint32_t sb, int seg, uint32_t h) {
    fence_async_smem();
    bulk_s2g(g_ox + (seg * NH + h) * 512, sb + S_OX + (seg & 1) * 8192, 8192);
    bulk_commit();
}

__device__ __forceinline__ void x_epilogue(uint32_t sb, const float (&d)[16], int seg, bool isv, int w, uint32_t L16) {
    uint32_t pk[8];
#pragma unroll
    for (int i = 0; i < 8; i++) pk[i] = pack_bf16(d[2 * i], d[2 * i + 1]);
    if (!isv) {
        const uint32_t a = sb + S_QX + (w >> 2) * 8192 + (seg & 1) * 4096 + (w & 3) * 256 + (L16 & 0xF0) + (L16 & 0x100) * 4;
        stsm4t(a, pk[0], pk[1], pk[2], pk[3]);
        stsm4t(a + 2048, pk[4], pk[5], pk[6], pk[7]);
    } else {
        const uint32_t a = sb + S_VX + (seg & 3) * 8192 + w * 1024 + L16;
        sts128(a, pk[0], pk[1], pk[2], pk[3]);
        sts128(a + 512, pk[4], pk[5], pk[6], pk[7]);
    }
}

template <int K0, int K1>
__device__ __forceinline__ void x_project(float (&d)[16], const uint32_t (&wA)[36][4], uint32_t desc) {
#pragma unroll
    for (int i = K0; i < K1; i++) {
        const uint32_t db = desc + (((i >> 2) * 4096 + (i & 3) * 32) >> 4);
        if (i == 0) wg_rs_n32<0>(d, wA[i], db); else wg_rs_n32<1>(d, wA[i], db);
    }
}

__device__ __forceinline__ void mem_scores(uint32_t sb, uint32_t peerA, uint32_t peerB, uint32_t off, const uint32_t (&q0)[4], const uint32_t (&q1)[4],
                                           const uint32_t (&k0)[4], const uint32_t (&k1)[4]) {
    float e0[4], o0[4], e1[4], o1[4];
    mma16z(e0, q0, k0[0], k0[1]);
    mma16z(o0, q0, k0[2], k0[3]);
    mma16z(e1, q1, k1[0], k1[1]);
    mma16z(o1, q1, k1[2], k1[3]);
    const uint32_t sc = pack_f16_sat((e0[0] + o0[2]) + (e1[0] + o1[2]), (e0[1] + o0[3]) + (e1[1] + o1[3]));
    st_async32(peerB + off, sc, peerB + B_S);
    st_async32(peerA + off, sc, peerA + B_S);
    sts32(sb + off, sc);
    __syncwarp();
}

__device__ __forceinline__ unsigned post_time(int s, uint32_t L16) {
    delay(1);
    const unsigned t = gtime() | 1;
    if (L16 == 0) asm volatile("st.relaxed.gpu.global.u32 [%0], %1;" ::"l"(reinterpret_cast<unsigned*>(g_acc) + s * 96 + blockIdx.x), "r"(t) : "memory");
    return t;
}
__device__ __forceinline__ void plan_look(uint32_t sb, int s, uint32_t L16, unsigned t) {
    const char* p = reinterpret_cast<const char*>(g_acc) + s * 384 + (L16 < 384 ? L16 : 0);
    uint4 v;
    unsigned c = 0;
    do { v = ld_poll(p); } while (__any_sync(0xffffffffu, (v.x & v.y & v.z & v.w & 1) == 0) && ++c < SPIN_LIM);
    const int d = max(max((int)(v.x - t), (int)(v.y - t)), max((int)(v.z - t), (int)(v.w - t)));
    const unsigned tgt = t + min(__reduce_max_sync(0xffffffffu, d), 20000) + TGT_NS;
    if (L16 < 48) { const uint32_t r = mapa(sb, L16 >> 4); st_async32(r + S_TGT, tgt, r + B_T); }
}

template <int ROLE>
__device__ __forceinline__ void chain_main(const uint32_t sb, const uint32_t lane16, const int wq, const uint32_t j, const uint32_t h,
                                           const uint32_t peerA, const uint32_t peerB) {
    uint32_t L16 = lane16;
    constexpr bool isv = ROLE >= 2;
    constexpr int wg = ROLE & 1;
    const int w = wg * 4 + wq;
    const uint32_t xdesc = desc_lo(sb + S_XB);
    const uint32_t zero = h >> 20;
    uint32_t wA[36][4], woA[8][4], woB[4][4];
    float xd[16];
    {
        const int m = L16 >> 7, r = (L16 >> 4) & 7;
        const int blk = (ROLE == 1) ? ((wq & 2) * 2 + (wq & 1) + (m & 1) * 2) : (2 * wq + (m & 1));
        const uint32_t a = sb + wg * 24576 + ((m >> 1) * 8 + r) * 128 + ((blk ^ r) << 4);
        mbar_wait(sb + B_X, 0);
#pragma unroll
        for (int c = 0; c < 3; c++) {
            mbar_wait(sb + B_W + 8 * c, 0);
#pragma unroll
            for (int i = 0; i < 12; i++) ldsm4t(wA[12 * c + i], a + s_w(c) + i * 2048);
            if (c == 0) bar_arrive<NB_PRO, 384>();
            if (c == 2) { bar_sync<NB_O, 256>(); cluster_arrive(); }
            wg_fence();
            if (c == 0) x_project<0, 12>(xd, wA, xdesc);
            if (c == 1) x_project<12, 24>(xd, wA, xdesc);
            if (c == 2) x_project<24, 36>(xd, wA, xdesc);
            wg_commit();
            wg_wait<0>();
        }
        x_epilogue(sb, xd, 0, isv, w, L16);
        bar_arrive<NB_RED, 384>();
        mbar_wait(sb + B_WO, 0);
        const int ca = 3 * w + (m & 1), cb = 3 * w + 2;
        const uint32_t aA = sb + S_WO + (ca >> 3) * 16384 + ((m >> 1) * 8 + r) * 128 + (((ca & 7) ^ r) << 4);
        const int eB = ((m & 2) + ((r >> 1) & 1)) * 8 + 4 * (m & 1) + 2 * (r >> 2) + (r & 1);
        const uint32_t aB = sb + S_WO + (cb >> 3) * 16384 + eB * 128 + (((cb & 7) ^ (eB & 7)) << 4);
#pragma unroll
        for (int i = 0; i < 8; i++) ldsm4t(woA[i], aA + i * 2048);
#pragma unroll
        for (int i = 0; i < 4; i++) ldsm4t(woB[i], aB + i * 4096);
        mbar_wait(sb + B_X + 8, 0);
        cluster_wait();
        bar_sync<NB_O, 256>();
        wg_fence();
        x_project<0, 36>(xd, wA, xdesc + (XB_BYTES >> 4));
        wg_commit();
    }
    int s = 0;
#pragma unroll 1
    while (true) {
        const uint32_t par = s & 1;
        const uint32_t kx = sb + S_KX + par * 4096;
        asm volatile("" : "+r"(L16));
        wg_wait<0>();
        x_epilogue(sb, xd, s + 1, isv, w, L16);
        float c0[4], c1[4];
        uint32_t k0[4], k1[4], pva[3][4];
        {
            const uint32_t a = sb + S_MEM + L16;
            constexpr int CH = 18 / NCH;
            uint32_t b[3][4];
            bool ready = true;
            mbar_wait(sb + B_M, par);
            ldsm4(b[0], a);
            ldsm4(b[1], a + 512);
            bar_arrive<NB_GO, 288>();
#pragma unroll
            for (int i = 0; i < 18; i++) {
                if ((i + 4) % CH == 0 && i + 4 < 18) ready = mbar_test(sb + B_M + ((i + 4) / CH) * 8, par);
                if ((i + 2) % CH == 0 && i + 2 < 18) { if (__builtin_expect(!ready, 0)) mbar_wait(sb + B_M + ((i + 2) / CH) * 8, par); }
                if (i + 2 < 18) ldsm4(b[(i + 2) % 3], a + (i + 2) * 512);
                if (ROLE == 0 && i == 16) ldsm4(k0, kx + wq * 1024 + L16);
                if (ROLE == 0 && i == 17) ldsm4(k1, kx + wq * 1024 + 512 + L16);
                if (PV_MODE == 0 && !(OFF & 8) && isv && i == 17) x_pv_load(sb, s + 2, w, L16, pva);
                if (i == 0) { mma16z(c0, wA[0], b[0][0], b[0][1]); mma16z(c1, wA[1], b[0][2], b[0][3]); }
                else { mma16(c0, wA[2 * i], b[i % 3][0], b[i % 3][1]); mma16(c1, wA[2 * i + 1], b[i % 3][2], b[i % 3][3]); }
            }
        }
        const uint32_t p0 = pack_bf16(c0[0] + c1[0], c0[1] + c1[1]), p1 = pack_bf16(c0[2] + c1[2], c0[3] + c1[3]);
        if (!isv) {
            stsm2t(sb + S_QM + w * 256 + L16, p0, p1);
            bar_sync<NB_QK, 384>();
            if (ROLE == 0) {
                uint32_t q0[4], q1[4];
                ldsm4(q0, sb + S_QM + L16);
                ldsm4(q1, sb + S_QM + 512 + L16);
                mem_scores(sb, peerA, peerB, S_SP + j * 128 + wq * 256 + (L16 >> 2), q0, q1, k0, k1);
                mbar_arrive_if0(sb + B_S, L16);
            } else {
                if (s + 2 < XLIM) mbar_wait(sb + B_X + par * 8, ((s + 2) >> 1) & 1);
                if (wq != 0 && !(OFF & 16)) {
                    const int rt = (wq == 3) ? 0 : 1;
                    const uint32_t qa = sb + S_QX + par * 4096 + rt * 2048 + (L16 & 0x80) * 8 + (L16 & 0x170);
                    const uint32_t kb0 = (wq == 2 ? kx + 2048 : sb + S_KM) + L16;
                    const uint32_t kb1 = (wq == 2 ? kx + 3072 : kx) + L16;
                    const uint32_t kb2 = kx + 1024 + L16;
                    float a0[4], a1[4], a2[4];
#pragma unroll
                    for (int hf = 0; hf < 2; hf++) {
                        uint32_t qa0[4], qa1[4], b[4];
                        ldsm4(qa0, qa + hf * 512);
                        ldsm4(qa1, qa + hf * 512 + 128);
                        ldsm4(b, kb0 + hf * 512);
                        if (hf == 0) mma16z(a0, qa0, b[0], b[1]); else mma16(a0, qa0, b[0], b[1]);
                        mma16(a0, qa1, b[2], b[3]);
                        ldsm4(b, kb1 + hf * 512);
                        if (hf == 0) mma16z(a1, qa0, b[0], b[1]); else mma16(a1, qa0, b[0], b[1]);
                        mma16(a1, qa1, b[2], b[3]);
                        ldsm4(b, kb2 + hf * 512);
                        if (hf == 0) mma16z(a2, qa0, b[0], b[1]); else mma16(a2, qa0, b[0], b[1]);
                        mma16(a2, qa1, b[2], b[3]);
                    }
                    mbar_wait(sb + B_S, par);
                    delay(SX_DELAY);
                    const uint32_t dst = peerB + S_SX + par * 5120 + j * 128 + rt * 2560 + (L16 >> 2);
                    const uint32_t bar = peerB + B_SX + par * 8;
                    const uint32_t T0 = (wq == 2 ? 2 : 4) * 256, T1 = (wq == 2 ? 3 : 0) * 256;
                    st_async32(dst + T0, pack_f16_sat(a0[0], a0[1]), bar);
                    st_async32(dst + 1280 + T0, pack_f16_sat(a0[2], a0[3]), bar);
                    if (wq != 2) st_async32(dst + T1, pack_f16_sat(a1[0], a1[1]), bar);
                    st_async32(dst + 1280 + T1, pack_f16_sat(a1[2], a1[3]), bar);
                    if (wq == 1) st_async32(dst + 256, pack_f16_sat(a2[0], a2[1]), bar);
                    if (wq != 2) st_async32(dst + 1280 + 256, pack_f16_sat(a2[2], a2[3]), bar);
                }
            }
        } else {
            const uint32_t off = S_VM + (s & 3) * 2048 + w * 256 + (L16 >> 1);
            st_async64(peerA + off, p0, p1, peerA + B_S);
            st_async64(peerB + off, p0, p1, peerB + B_S);
            sts64(sb + off, p0, p1);
            __syncwarp();
            mbar_expect_if0(sb + B_S, 160, L16);
            if (PV_MODE == 1 || (PV_MODE == 2 && ROLE == 3)) x_pv_load(sb, s + 2, w, L16, pva);
            if (PV_MODE == 2 && ROLE == 2) bar_arrive<NB_P, 384>(); else bar_sync<NB_P, 384>();
            if (PV_MODE == 2) {
                if (ROLE == 3) { x_pv_run(sb, s + 2, w, L16, pva); x_pv_load(sb, s + 2, wq, L16, pva); x_pv_run(sb, s + 2, wq, L16, pva); }
            } else
            if (!(OFF & 8)) x_pv_run(sb, s + 2, w, L16, pva);
            if (ROLE == 3 && s + 2 < XLIM) mbar_wait(sb + B_X + par * 8, ((s + 2) >> 1) & 1);
        }
        if (s == NSEG - 1) break;
        if (wg == 0) {
            if (!isv) mbar_wait(sb + B_VX + par * 8, (s >> 1) & 1);
            uint32_t va[4][4];
            const uint32_t vx = sb + S_VX + (s & 3) * 8192 + wq * 2048 + L16;
            const uint32_t vm = sb + S_VM + (s & 3) * 2048 + wq * 512 + (L16 >> 1);
            lds128(va[0], vx);
            lds128(va[2], vx + 1024);
            mbar_wait(sb + B_S, par);
            __half2 hs[5];
            load_scores(sb + S_SP + L16, hs);
            float ev[10];
            softmax_exp(hs, ev);
            lds128(va[1], vx + 512);
            lds128(va[3], vx + 1536);
            uint32_t p[5];
#pragma unroll
            for (int i = 0; i < 5; i++) p[i] = pack_bf16(ev[2 * i], ev[2 * i + 1]);
            uint32_t vm0[2], vm1[2];
            const uint32_t ones[4] = {ONES, ONES, ONES, ONES};
            float sum[4], o0[4], o1[4];
            mma16z(o0, va[0], p[0], p[1]);
            mma16z(o1, va[2], p[0], p[1]);
            mma16z(sum, ones, p[0], p[1]);
            lds64(vm0, vm);
            lds64(vm1, vm + 256);
            mma16(o0, va[1], p[2], p[3]);
            mma16(o1, va[3], p[2], p[3]);
            mma16(sum, ones, p[2], p[3]);
            mma8(o0, vm0[0], vm0[1], p[4]);
            mma8(o1, vm1[0], vm1[1], p[4]);
            mma8(sum, ONES, ONES, p[4]);
            stsm4t(sb + S_OM + wq * 512 + L16, pack_bf16(o0[0], o0[1]), pack_bf16(o0[2], o0[3]), pack_bf16(o1[0], o1[1]), pack_bf16(o1[2], o1[3]));
            sts64(sb + S_SUM + wq * 256 + (L16 >> 1), __float_as_uint(sum[0]), __float_as_uint(sum[1]));
        }
        bar_sync<NB_O, 256>();
        {
            float a0[4], a1[4], e[4];
            float2 sc;
            float sr, r0, r1, rr;
#pragma unroll
            for (int i = 0; i < 4; i++) {
                uint32_t b[4];
                ldsm4(b, sb + S_OM + i * 512 + L16);
                if (i == 0) {
                    mma16z(a0, woA[0], b[0], b[1]); mma16z(a1, woA[1], b[2], b[3]);
                    mma_sp<0>(e, b, woB[0]);
                } else {
                    if (i == 1) { sc = lds64f(sb + S_SUM + (L16 >> 1)); sr = lds32f(sb + S_SUM + ((L16 >> 4) & 0x1C)); }
                    const uint32_t z = __float_as_uint(a0[0]) & zero;
                    mma16(a0, woA[2 * i], b[0], b[1]); mma16(a1, woA[2 * i + 1], b[2], b[3]);
                    mma_sp<1>(e, b, woB[i]);
                    if (i == RCP_AT) {
                        r0 = rcp(__uint_as_float(__float_as_uint(sc.x) | z));
                        r1 = rcp(__uint_as_float(__float_as_uint(sc.y) | z));
                        rr = rcp(__uint_as_float(__float_as_uint(sr) | z));
                    }
                }
            }
            asm volatile("" : "+r"(L16));
            char* const rslot = reinterpret_cast<char*>(g_acc) + ((s + 1) * SLOT_BYTES + j * 8192 + w * 1024) + (L16 + (L16 & 0x1C0));
            asm volatile("red.relaxed.gpu.global.add.noftz.v4.bf16x2 [%0], {%1,%2,%3,%4};"
                         ::"l"(rslot), "r"(pack_bf16((a0[0] + a1[0]) * r0, (a0[1] + a1[1]) * r1)), "r"(pack_bf16((a0[2] + a1[2]) * r0, (a0[3] + a1[3]) * r1)),
                           "r"(pack_bf16((e[0] + e[2]) * rr, (e[1] + e[3]) * rr)), "r"(0x3F80u) : "memory");
        }
        bar_sync<NB_X, 256>();
        wg_fence();
        x_project<0, POLL_AT>(xd, wA, xdesc + par * (XB_BYTES >> 4));
        bar_arrive<NB_RED, 384>();
        x_project<POLL_AT, 36>(xd, wA, xdesc + par * (XB_BYTES >> 4));
        wg_commit();
        s++;
    }
    if (isv) {
        uint32_t pva[3][4];
        x_pv_load(sb, NSEG - 2, w, L16, pva);
        bar_sync<NB_RED, 384>();
        x_pv_run(sb, NSEG - 2, w, L16, pva);
        bar_arrive<NB_QK, 384>();
        x_pv_load(sb, NSEG - 1, w, L16, pva);
        bar_sync<NB_P, 384>();
        x_pv_run(sb, NSEG - 1, w, L16, pva);
        bar_arrive<NB_PRO, 384>();
    }
}

template <bool isv>
__device__ __forceinline__ void chain_aux(const uint32_t sb, const uint32_t lane16, const int wq, const uint32_t j, const uint32_t h,
                                          const uint32_t peerA, const uint32_t peerB, const CUtensorMap* tmWo, const CUtensorMap* tmX,
                                          const bf16* __restrict__ mem0) {
    const int t = wq * 32 + (lane16 >> 4);
    TSTAMP(64, 0);
    cluster_arrive();
    {
        uint4* z = g_acc + blockIdx.x * 1024 + t;
#pragma unroll
        for (int i = 0; i < 8; i++) z[i * 128] = make_uint4(0, 0, 0, 0);
        if (blockIdx.x == 0) { g_flag[t] = 0; g_flag[128 + t] = 0; }
        for (int i = t; i < 576; i += 128) {
            const uint4 v = *reinterpret_cast<const uint4*>(mem0 + (i & 7) * DM + (i >> 3) * 8);
            sts128(sb + S_MEM + i * 16, v.x, v.y, v.z, v.w);
        }
        __threadfence();
        bar_sync<NB_AUX, 128>();
        if (t == 0) red_release(&g_zero_cnt, 1);
        asm volatile("griddepcontrol.launch_dependents;" ::: "memory");
        bar_sync<NB_PRO, 384>();
        if (t == 0) {
            fence_async_smem();
            mbar_expect(sb + B_WO, 49152);
            for (int b = 0; b < 3; b++) tma2d(sb + S_WO + b * 16384, tmWo, 192 * j + 64 * b, h * 128, sb + B_WO);
        }
        unsigned c = 0;
        while (ld_acquire(&g_zero_cnt) < 96 && ++c < SPIN_LIM) {}
        __syncwarp();
        for (int c2 = 0; c2 < 3; c2++) mbar_arrive_if0(sb + B_M + c2 * 8, lane16);
        cluster_wait();
        bar_sync<NB_RED, 384>();
        if (t == 0) {
            fence_async_smem();
            if (!isv) mbar_expect(sb + B_VX, 8192);
            else {
                bulk_s2c(peerA + S_VX, sb + S_VX, 8192, peerA + B_VX);
                bulk_s2c(peerB + S_VX, sb + S_VX, 8192, peerB + B_VX);
            }
            mbar_expect(sb + B_X, XB_BYTES);
            tma3d(sb + S_XB, tmX, 0, 64, 0, sb + B_X);
        }
        __syncwarp();
    }
    TSTAMP(0, 0);
    uint32_t L16 = lane16;
    const char* slot = reinterpret_cast<const char*>(g_acc) + wq * 1024 + (L16 + (L16 & 0x1C0));
    float ev[10];
    int s = 0;
#pragma unroll 1
    while (true) {
        const uint32_t par = s & 1;
        asm volatile("" : "+r"(L16));
        if (!isv) {
            if (wq == 0) {
                bar_sync<NB_QK, 384>();
                uint32_t q0[4], q1[4], k0[4], k1[4];
                ldsm4(q0, sb + S_QM + L16);
                ldsm4(k0, sb + S_KM + L16);
                ldsm4(q1, sb + S_QM + 512 + L16);
                ldsm4(k1, sb + S_KM + 512 + L16);
                mem_scores(sb, peerA, peerB, S_SP + j * 128 + 1024 + (L16 >> 2), q0, q1, k0, k1);
                mbar_expect_if0(sb + B_S, 640 + 2048, L16);
            } else if (wq == 3) {
                bar_sync<NB_GO, 288>();
                const unsigned t = post_time(s, L16);
                bar_sync<NB_QK, 384>();
                if (j == 0 && s < NSEG - 1) {
                    if (LOOK_NS) __nanosleep(LOOK_NS);
                    plan_look(sb, s, L16, t);
                }
            } else {
                bar_arrive<NB_QK, 384>();
                if (wq == 2) {
                    if (L16 == 0) {
                        if (s + 3 < XLIM) mbar_expect(sb + B_X + (par ^ 1) * 8, XB_BYTES);
                        mbar_expect(sb + B_VX + (par ^ 1) * 8, (OFF & 2) ? 0 : 8192);
                        mbar_expect(sb + B_T, 4);
                        if (s == 2 && h == 0 && j == 0) g_zero_cnt = 0;
                    }
                } else if (s + 3 < XLIM && j == 1) {
                    mbar_wait(sb + B_S, par);
                    delay(XTMA_DELAY);
                    if (XTMA_NS) __nanosleep(XTMA_NS);
                    if (L16 == 0) tma3d_mc(sb + S_XB + (par ^ 1) * XB_BYTES, tmX, 0, (s + 3) * SEG, 0, sb + B_X + (par ^ 1) * 8, 7);
                }
                __syncwarp();
            }
        } else {
            if (wq == 3) {
                bar_sync<NB_GO, 288>();
                post_time(s, L16);
            } else if (L16 == 0) {
                if (wq == 0) {
                    if (!(OFF & 2) && s >= 1) {
                        bulk_wait0();
                        bulk_g2s_mc(sb + S_VX + (s & 3) * 8192, g_vx + (h * 2 + par) * 512, 8192, sb + B_VX + par * 8, 3);
                    }
                } else if (wq == 1) {
                    if (OX_AT == 0 && s >= 3) ox_publish(s - 3, h);
                    if (OX_AT != 0 && s >= 4) ox_publish(s - 4, h);
                } else {
                    mbar_expect(sb + B_SX + par * 8, (OFF & 16) ? 0 : 3584);
                    mbar_expect(sb + B_T, 4);
                    if (s + 3 < XLIM) mbar_expect(sb + B_X + (par ^ 1) * 8, XB_BYTES);
                }
            }
            __syncwarp();
            if (s >= 1) mbar_wait(sb + B_SX + (par ^ 1) * 8, ((s - 1) >> 1) & 1);
            bar_sync<NB_P, 384>();
            if (OX_AT == 1 && wq == 1) { if (L16 == 0 && s >= 3) ox_store(sb, s - 3, h); __syncwarp(); }
            if (!(OFF & 4) || s == NSEG - 1) x_scores(sb, s + 1, wq, L16, ev);
            if (OX_AT == 2 && wq == 1) { if (L16 == 0 && s >= 3) ox_store(sb, s - 3, h); __syncwarp(); }
            if (wq == 0) {
                if (!(OFF & 2) && L16 == 0 && s + 1 < NSEG) {
                    fence_async_smem();
                    bulk_s2g(g_vx + (h * 2 + (par ^ 1)) * 512, sb + S_VX + ((s + 1) & 3) * 8192, 8192);
                    bulk_commit();
                }
                __syncwarp();
            }
        }
        if (s == NSEG - 1) break;
        bar_sync<NB_RED, 384>();
        if (isv && !(OFF & 4)) x_probs(sb, s + 1, wq, L16, ev);
        asm volatile("" : "+r"(L16));
        slot += SLOT_BYTES;
        mbar_wait(sb + B_T, par);
        {
            const unsigned tgt = __float_as_uint(lds32f(sb + S_TGT));
            while ((int)(gtime() - tgt) < 0) {}
        }
        uint4 v[6];
#pragma unroll
        for (int i = 0; i < 6; i++) v[i] = ld_poll(slot + i * 4096);
        if (OX_AT == 0 && !(OFF & 1) && isv && wq == 1 && s >= 2) { delay(OX_DELAY); if (L16 == 0) ox_store(sb, s - 2, h); __syncwarp(); }
        s++;
        const uint32_t ma = sb + S_MEM + wq * 384 + L16;
        unsigned c = 0;
        constexpr int CW = 6 / NCH;
        int done = NCH;
#pragma unroll
        for (int k = 0; k < NCH; k++) {
            uint32_t bad = 0;
#pragma unroll
            for (int i = CW * k; i < CW * k + CW; i++) { stsm2t(ma + i * 1536, v[i].x, v[i].y); stsm1(ma + i * 1536 + 256, v[i].z); bad |= v[i].w ^ FULL_COUNT; }
            const bool again = __any_sync(0xffffffffu, bad != 0);
            mbar_arrive_if0(sb + B_M + k * 8, L16 | (uint32_t)again);
            if (again) { done = k; break; }
        }
        if (done < NCH) {
            uint32_t bad;
            do {
#pragma unroll
                for (int i = 0; i < 6; i++) if (i >= CW * done) v[i] = ld_poll(slot + i * 4096);
                bad = 0;
#pragma unroll
                for (int i = 0; i < 6; i++) if (i >= CW * done) { stsm2t(ma + i * 1536, v[i].x, v[i].y); stsm1(ma + i * 1536 + 256, v[i].z); bad |= v[i].w ^ FULL_COUNT; }
            } while (++c < SPIN_LIM && __any_sync(0xffffffffu, bad != 0));
            __syncwarp();
#pragma unroll
            for (int k = 0; k < NCH; k++) if (k >= done) mbar_arrive_if0(sb + B_M + k * 8, L16);
        }
        TSTAMP(s, c | t_pack);
    }
    if (!isv) {
        mbar_wait(sb + B_VX + 8, ((NSEG - 1) >> 1) & 1);
        mbar_wait(sb + B_S, 1);
    } else {
        x_probs(sb, NSEG - 2, wq, L16, ev);
        if (OX_AT != 0 && wq == 1) { if (L16 == 0) ox_publish(NSEG - 4, h); __syncwarp(); }
        bar_sync<NB_RED, 384>();
        if (wq == 1 && L16 == 0) ox_store(sb, NSEG - 3, h);
        __syncwarp();
        bar_sync<NB_QK, 384>();
        if (wq == 2 && L16 == 0) ox_store(sb, NSEG - 2, h);
        __syncwarp();
        mbar_wait(sb + B_S, 1);
        mbar_wait(sb + B_SX + 8, ((NSEG - 1) >> 1) & 1);
        x_scores(sb, NSEG - 1, wq, L16, ev);
        x_probs(sb, NSEG - 1, wq, L16, ev);
        if (wq == 1 && L16 == 0) ox_publish(NSEG - 3, h);
        __syncwarp();
        bar_arrive<NB_P, 384>();
        if (wq == 2) { if (L16 == 0) ox_publish(NSEG - 2, h); __syncwarp(); bar_arrive<NB_PRO, 384>(); }
        else bar_sync<NB_PRO, 384>();
        if (wq == 3 && L16 == 0) { ox_store(sb, NSEG - 1, h); ox_publish(NSEG - 1, h); }
    }
}

__global__ void __launch_bounds__(384, 1)
chain_kernel(const __grid_constant__ CUtensorMap tmWq, const __grid_constant__ CUtensorMap tmWk, const __grid_constant__ CUtensorMap tmWv,
             const __grid_constant__ CUtensorMap tmWo, const __grid_constant__ CUtensorMap tmX, const bf16* __restrict__ mem0) {
    extern __shared__ __align__(1024) uint8_t smem[];
    const uint32_t sb = smem_u32(smem);
    const int tid = threadIdx.x;
    const uint32_t L16 = __shfl_sync(0xffffffffu, (tid & 31) * 16, tid & 31);
    const int w = __shfl_sync(0xffffffffu, tid >> 5, 0), wg = w >> 2, wq = w & 3;
    uint32_t j, h;
    asm("mov.u32 %0, %%cluster_ctarank;" : "=r"(j));
    asm("mov.u32 %0, %%clusterid.x;" : "=r"(h));
    const bool isv = (j == 2);
    const uint32_t peerA = mapa(sb, isv ? 0 : (j ^ 1)), peerB = mapa(sb, isv ? 1 : 2);
    if (tid == 256) {
        for (int c = 0; c < 3; c++) { mbar_init(sb + B_W + 8 * c, 1); mbar_init(sb + B_M + 8 * c, 4); }
        mbar_init(sb + B_WO, 1); mbar_init(sb + B_T, 1);
        mbar_init(sb + B_X, 1); mbar_init(sb + B_X + 8, 1);
        mbar_init(sb + B_S, isv ? 8 : 5);
        mbar_init(sb + B_VX, 1); mbar_init(sb + B_VX + 8, 1);
        mbar_init(sb + B_SX, 1); mbar_init(sb + B_SX + 8, 1);
        asm volatile("fence.mbarrier_init.release.cluster;" ::: "memory");
        const CUtensorMap* m0 = isv ? &tmWv : &tmWq;
        const CUtensorMap* m1 = isv ? &tmWv : &tmWk;
        const int c0 = h * 128 + (isv ? 0 : 64 * j), c1 = h * 128 + (isv ? 64 : 64 * j);
        mbar_expect(sb + B_X, XB_BYTES);
        tma3d(sb + S_XB, &tmX, 0, 0, 0, sb + B_X);
#pragma unroll
        for (int c = 0; c < 3; c++) {
            mbar_expect(sb + B_W + 8 * c, 49152);
            tma2d(sb + s_w(c), m0, c0, c * 192, sb + B_W + 8 * c);
            tma2d(sb + s_w(c) + 24576, m1, c1, c * 192, sb + B_W + 8 * c);
        }
        mbar_expect(sb + B_X + 8, XB_BYTES);
        tma3d(sb + S_XB + XB_BYTES, &tmX, 0, 32, 0, sb + B_X + 8);
    }
    __syncthreads();
    if (wg == 2) {
        asm volatile("setmaxnreg.dec.sync.aligned.u32 %0;" ::"n"(REG_AUX));
        if (!isv) chain_aux<false>(sb, L16, wq, j, h, peerA, peerB, &tmWo, &tmX, mem0);
        else chain_aux<true>(sb, L16, wq, j, h, peerA, peerB, &tmWo, &tmX, mem0);
        __syncwarp();
        cluster_arrive(); cluster_wait();
        TSTAMP(65, 0);
    } else if (wg == 0) {
        asm volatile("setmaxnreg.inc.sync.aligned.u32 %0;" ::"n"(REG_MAIN0));
        if (!isv) chain_main<0>(sb, L16, wq, j, h, peerA, peerB);
        else chain_main<2>(sb, L16, wq, j, h, peerA, peerB);
        cluster_arrive(); cluster_wait();
    } else {
        asm volatile("setmaxnreg.inc.sync.aligned.u32 %0;" ::"n"(REG_MAIN1));
        if (!isv) chain_main<1>(sb, L16, wq, j, h, peerA, peerB);
        else chain_main<3>(sb, L16, wq, j, h, peerA, peerB);
        cluster_arrive(); cluster_wait();
    }
}

__device__ float g_K[DM * SEQ];

__global__ void naive_outproj(const bf16* __restrict__ Wo, bf16* __restrict__ out) {
    __shared__ float o[4096];
    const int t = blockIdx.x, seg = t >> 5, r = t & 31;
    const bf16* ox = reinterpret_cast<const bf16*>(g_ox);
    for (int i = threadIdx.x; i < 4096; i += blockDim.x) {
        int h = i >> 7, e = i & 127;
        o[i] = __bfloat162float(ox[(seg * 32 + h) * 4096 + (e >> 6) * 2048 + r * 64 + ((((e & 63) >> 3) ^ (r & 7)) << 3) + (e & 7)]);
    }
    __syncthreads();
    float acc = 0;
    for (int i = 0; i < 4096; i++) acc += o[i] * __bfloat162float(Wo[i * DM + threadIdx.x]);
    out[t * OUTW + threadIdx.x] = __float2bfloat16(acc);
}
__global__ void naive_kgen(const bf16* logA, const bf16* Aim, const bf16* Cr, const bf16* Ci, const bf16* logdt) {
    const int d = blockIdx.x;
    const float dt = __bfloat162float(__float2bfloat16(expf(__bfloat162float(logdt[d]))));
    for (int l = threadIdx.x; l < SEQ; l += blockDim.x) {
        const float pos = __bfloat162float(__float2bfloat16((float)l));
        float acc = 0;
        for (int n = 0; n < NST; n++) {
            float ar = -__bfloat162float(__float2bfloat16(expf(__bfloat162float(logA[d * NST + n])))) * dt;
            float ai = __bfloat162float(Aim[d * NST + n]) * dt;
            float cr = __bfloat162float(Cr[d * NST + n]) * dt, ci = __bfloat162float(Ci[d * NST + n]) * dt;
            float mg = expf(ar * pos), sn, cs;
            sincosf(ai * pos, &sn, &cs);
            acc += mg * (cr * cs - ci * sn);
        }
        g_K[d * SEQ + l] = 2.f * acc;
    }
}
__global__ void naive_conv(const bf16* u, const bf16* Dsk, bf16* out) {
    __shared__ float us[SEQ], ks[SEQ];
    const int d = blockIdx.x;
    for (int l = threadIdx.x; l < SEQ; l += blockDim.x) { us[l] = __bfloat162float(u[l * DM + d]); ks[l] = g_K[d * SEQ + l]; }
    __syncthreads();
    for (int l = threadIdx.x; l < SEQ; l += blockDim.x) {
        float acc = 0;
        for (int i = 0; i <= l; i++) acc += ks[l - i] * us[i];
        float y = __bfloat162float(__float2bfloat16(acc));
        float sk = __bfloat162float(__float2bfloat16(us[l] * __bfloat162float(Dsk[d])));
        out[l * OUTW + DM + d] = __float2bfloat16(y + sk);
    }
}

typedef CUresult (*EncodeFn)(CUtensorMap*, CUtensorMapDataType, cuuint32_t, void*, const cuuint64_t*, const cuuint64_t*, const cuuint32_t*,
                             const cuuint32_t*, CUtensorMapInterleave, CUtensorMapSwizzle, CUtensorMapL2promotion, CUtensorMapFloatOOBfill);

void make_map(EncodeFn fn, CUtensorMap* m, const void* p, int rank, const cuuint64_t* dims, const cuuint64_t* strides, const cuuint32_t* box) {
    const cuuint32_t es[3] = {1, 1, 1};
    fn(m, CU_TENSOR_MAP_DATA_TYPE_BFLOAT16, rank, const_cast<void*>(p), dims, strides, box, es, CU_TENSOR_MAP_INTERLEAVE_NONE,
       CU_TENSOR_MAP_SWIZZLE_128B, CU_TENSOR_MAP_L2_PROMOTION_L2_128B, CU_TENSOR_MAP_FLOAT_OOB_FILL_NONE);
}

}

extern "C" void kernel_launch(void* const* d_in, const int* in_sizes, int n_in, void* d_out, int out_size) {
    const bf16* x = (const bf16*)d_in[0];
    const bf16* mem0 = (const bf16*)d_in[1];
    const bf16* Wo = (const bf16*)d_in[5];
    bf16* out = (bf16*)d_out;

    static EncodeFn enc = nullptr;
    if (!enc) {
        void* fn = nullptr;
        cudaDriverEntryPointQueryResult st;
        cudaGetDriverEntryPoint("cuTensorMapEncodeTiled", &fn, cudaEnableDefault, &st);
        enc = (EncodeFn)fn;
        cudaFuncSetAttribute(chain_kernel, cudaFuncAttributeMaxDynamicSharedMemorySize, A_SMEM);
    }
    CUtensorMap tmW[3], tmWo, tmX;
    {
        const cuuint64_t dims[2] = {4096, 576}, str[1] = {8192};
        const cuuint32_t box[2] = {64, 192};
        for (int i = 0; i < 3; i++) make_map(enc, &tmW[i], d_in[2 + i], 2, dims, str, box);
    }
    {
        const cuuint64_t dims[2] = {576, 4096}, str[1] = {1152};
        const cuuint32_t box[2] = {64, 128};
        make_map(enc, &tmWo, Wo, 2, dims, str, box);
    }
    {
        const cuuint64_t dims[3] = {64, 2048, 9}, str[2] = {1152, 128};
        const cuuint32_t box[3] = {64, 32, 9};
        make_map(enc, &tmX, x, 3, dims, str, box);
    }
    cudaStream_t st = cudaStreamPerThread;
    {
        cudaLaunchConfig_t cfg = {};
        cfg.gridDim = dim3(96); cfg.blockDim = dim3(384); cfg.dynamicSmemBytes = A_SMEM; cfg.stream = st;
        cudaLaunchAttribute at[1];
        at[0].id = cudaLaunchAttributeClusterDimension;
        at[0].val.clusterDim.x = 3; at[0].val.clusterDim.y = 1; at[0].val.clusterDim.z = 1;
        cfg.attrs = at; cfg.numAttrs = 1;
        cudaLaunchKernelEx(&cfg, chain_kernel, tmW[0], tmW[1], tmW[2], tmWo, tmX, mem0);
    }
    naive_outproj<<<SEQ, DM, 0, st>>>(Wo, out);
    naive_kgen<<<DM, 256, 0, st>>>((const bf16*)d_in[8], (const bf16*)d_in[9], (const bf16*)d_in[10], (const bf16*)d_in[11], (const bf16*)d_in[12]);
    naive_conv<<<DM, 256, 0, st>>>((const bf16*)d_in[7], (const bf16*)d_in[13], out);
}
```

```cpp
#include <cuda_runtime.h>
#include <cuda_bf16.h>
#include <cuda_fp16.h>
#include <cuda.h>
#include <stdint.h>

typedef __nv_bfloat16 bf16;

namespace {

constexpr int DM = 576, NH = 32, DH = 128, SEG = 32, NSEG = 64, SEQ = 2048, NST = 128;
constexpr int OUTW = 2 * DM;
constexpr unsigned SPIN_LIM = 1u << 15;

constexpr int SLOT_BYTES = 768 * 32;
__device__ __align__(1024) uint4 g_acc[NSEG * SLOT_BYTES / 16];
__device__ __align__(1024) uint4 g_ox[NSEG * NH * 512];
__device__ __align__(1024) uint4 g_vx[NH * 2 * 512];
__device__ unsigned g_flag[NSEG * 4];
__device__ unsigned g_zero_cnt;

__device__ __forceinline__ uint32_t smem_u32(const void* p) { return (uint32_t)__cvta_generic_to_shared(p); }
__device__ __forceinline__ unsigned clk() { unsigned c; asm volatile("mov.u32 %0, %%clock;" : "=r"(c)::"memory"); return c; }
__device__ __forceinline__ unsigned gtime() { unsigned t; asm volatile("mov.u32 %0, %%globaltimer_lo;" : "=r"(t)::"memory"); return t; }
__device__ __forceinline__ uint32_t mapa(uint32_t a, uint32_t r) { uint32_t o; asm("mapa.shared::cluster.u32 %0, %1, %2;" : "=r"(o) : "r"(a), "r"(r)); return o; }
__device__ __forceinline__ void mbar_init(uint32_t b, uint32_t n) { asm volatile("mbarrier.init.shared::cta.b64 [%0], %1;" ::"r"(b), "r"(n) : "memory"); }
__device__ __forceinline__ void mbar_arrive(uint32_t b) { asm volatile("mbarrier.arrive.shared::cta.b64 _, [%0];" ::"r"(b) : "memory"); }
__device__ __forceinline__ void mbar_expect(uint32_t b, uint32_t tx) { asm volatile("mbarrier.arrive.expect_tx.shared::cta.b64 _, [%0], %1;" ::"r"(b), "r"(tx) : "memory"); }
__device__ __forceinline__ bool mbar_try(uint32_t b, uint32_t par) {
    uint32_t ok;
    asm volatile("{.reg .pred p; mbarrier.try_wait.parity.shared::cta.b64 p, [%1], %2; selp.u32 %0, 1, 0, p;}" : "=r"(ok) : "r"(b), "r"(par) : "memory");
    return ok;
}
__device__ __forceinline__ bool mbar_test(uint32_t b, uint32_t par) {
    uint32_t ok;
    asm volatile("{.reg .pred p; mbarrier.test_wait.parity.shared::cta.b64 p, [%1], %2; selp.u32 %0, 1, 0, p;}" : "=r"(ok) : "r"(b), "r"(par) : "memory");
    return ok;
}
__device__ __forceinline__ void mbar_wait(uint32_t b, uint32_t par) {
    asm volatile("{.reg .pred p, q; .reg .u32 c; mov.u32 c, 0;\n"
                 "W: mbarrier.try_wait.parity.shared::cta.b64 p, [%0], %1;\n"
                 "@p bra D;\n add.u32 c, c, 1; setp.lt.u32 q, c, %2;\n @q bra W;\n D:\n}" ::"r"(b), "r"(par), "n"(SPIN_LIM) : "memory");
}
constexpr unsigned LONG_LIM = 1u << 17;
__device__ __forceinline__ void mbar_wait_long(uint32_t b, uint32_t par) {
    asm volatile("{.reg .pred p, q; .reg .u32 c; mov.u32 c, 0;\n"
                 "W: mbarrier.try_wait.parity.shared::cta.b64 p, [%0], %1;\n"
                 "@p bra D;\n add.u32 c, c, 1; setp.lt.u32 q, c, %2;\n @q bra W;\n D:\n}" ::"r"(b), "r"(par), "n"(LONG_LIM) : "memory");
}
__device__ __forceinline__ void cluster_sync() { asm volatile("barrier.cluster.arrive.aligned; barrier.cluster.wait.aligned;" ::: "memory"); }
__device__ __forceinline__ void fence_async_smem() { asm volatile("fence.proxy.async.shared::cta;" ::: "memory"); }
__device__ __forceinline__ void ldsm4(uint32_t* r, uint32_t a) { asm volatile("ldmatrix.sync.aligned.m8n8.x4.shared.b16 {%0,%1,%2,%3},[%4];" : "=r"(r[0]), "=r"(r[1]), "=r"(r[2]), "=r"(r[3]) : "r"(a) : "memory"); }
__device__ __forceinline__ void ldsm4t(uint32_t* r, uint32_t a) { asm volatile("ldmatrix.sync.aligned.m8n8.x4.trans.shared.b16 {%0,%1,%2,%3},[%4];" : "=r"(r[0]), "=r"(r[1]), "=r"(r[2]), "=r"(r[3]) : "r"(a) : "memory"); }
__device__ __forceinline__ void stsm1(uint32_t a, uint32_t r0) { asm volatile("stmatrix.sync.aligned.m8n8.x1.shared.b16 [%0],{%1};" ::"r"(a), "r"(r0) : "memory"); }
__device__ __forceinline__ void stsm2t(uint32_t a, uint32_t r0, uint32_t r1) { asm volatile("stmatrix.sync.aligned.m8n8.x2.trans.shared.b16 [%0],{%1,%2};" ::"r"(a), "r"(r0), "r"(r1) : "memory"); }
__device__ __forceinline__ void stsm4t(uint32_t a, uint32_t r0, uint32_t r1, uint32_t r2, uint32_t r3) { asm volatile("stmatrix.sync.aligned.m8n8.x4.trans.shared.b16 [%0],{%1,%2,%3,%4};" ::"r"(a), "r"(r0), "r"(r1), "r"(r2), "r"(r3) : "memory"); }
__device__ __forceinline__ void sts32(uint32_t a, uint32_t v) { asm volatile("st.shared.b32 [%0], %1;" ::"r"(a), "r"(v) : "memory"); }
__device__ __forceinline__ void sts64(uint32_t a, uint32_t x, uint32_t y) { asm volatile("st.shared.v2.b32 [%0], {%1,%2};" ::"r"(a), "r"(x), "r"(y) : "memory"); }
__device__ __forceinline__ void sts128(uint32_t a, uint32_t x, uint32_t y, uint32_t z, uint32_t w) { asm volatile("st.shared.v4.b32 [%0], {%1,%2,%3,%4};" ::"r"(a), "r"(x), "r"(y), "r"(z), "r"(w) : "memory"); }
__device__ __forceinline__ void lds64(uint32_t* r, uint32_t a) { asm volatile("ld.shared.v2.b32 {%0,%1},[%2];" : "=r"(r[0]), "=r"(r[1]) : "r"(a) : "memory"); }
__device__ __forceinline__ float2 lds64f(uint32_t a) { float2 v; asm volatile("ld.shared.v2.f32 {%0,%1},[%2];" : "=f"(v.x), "=f"(v.y) : "r"(a) : "memory"); return v; }
__device__ __forceinline__ void lds128(uint32_t* r, uint32_t a) { asm volatile("ld.shared.v4.b32 {%0,%1,%2,%3},[%4];" : "=r"(r[0]), "=r"(r[1]), "=r"(r[2]), "=r"(r[3]) : "r"(a) : "memory"); }
__device__ __forceinline__ void st_async64(uint32_t a, uint32_t x, uint32_t y, uint32_t bar) {
    asm volatile("st.async.weak.shared::cluster.mbarrier::complete_tx::bytes.v2.b32 [%0], {%1,%2}, [%3];" ::"r"(a), "r"(x), "r"(y), "r"(bar) : "memory");
}
__device__ __forceinline__ void st_async32(uint32_t a, uint32_t x, uint32_t bar) {
    asm volatile("st.async.weak.shared::cluster.mbarrier::complete_tx::bytes.b32 [%0], %1, [%2];" ::"r"(a), "r"(x), "r"(bar) : "memory");
}
__device__ __forceinline__ void ldsm2(uint32_t* r, uint32_t a) { asm volatile("ldmatrix.sync.aligned.m8n8.x2.shared.b16 {%0,%1},[%2];" : "=r"(r[0]), "=r"(r[1]) : "r"(a) : "memory"); }
__device__ __forceinline__ uint32_t pack_f16_sat(float lo, float hi) { uint32_t r; asm("cvt.rn.satfinite.f16x2.f32 %0, %1, %2;" : "=r"(r) : "f"(hi), "f"(lo)); return r; }
__device__ __forceinline__ __half2 as_h2(uint32_t x) { return *reinterpret_cast<__half2*>(&x); }
__device__ __forceinline__ uint32_t as_u32(__half2 x) { return *reinterpret_cast<uint32_t*>(&x); }
__device__ __forceinline__ uint32_t pack_bf16(float lo, float hi) { uint32_t r; asm("cvt.rn.bf16x2.f32 %0, %1, %2;" : "=r"(r) : "f"(hi), "f"(lo)); return r; }
__device__ __forceinline__ float ex2(float x) { float r; asm("ex2.approx.ftz.f32 %0, %1;" : "=f"(r) : "f"(x)); return r; }
__device__ __forceinline__ float rcp(float x) { float r; asm("rcp.approx.ftz.f32 %0, %1;" : "=f"(r) : "f"(x)); return r; }
__device__ __forceinline__ void mma16(float* d, const uint32_t* a, uint32_t b0, uint32_t b1) {
    asm volatile("mma.sync.aligned.m16n8k16.row.col.f32.bf16.bf16.f32 {%0,%1,%2,%3},{%4,%5,%6,%7},{%8,%9},{%0,%1,%2,%3};"
                 : "+f"(d[0]), "+f"(d[1]), "+f"(d[2]), "+f"(d[3]) : "r"(a[0]), "r"(a[1]), "r"(a[2]), "r"(a[3]), "r"(b0), "r"(b1));
}
__device__ __forceinline__ void mma16z(float* d, const uint32_t* a, uint32_t b0, uint32_t b1) {
    asm volatile("mma.sync.aligned.m16n8k16.row.col.f32.bf16.bf16.f32 {%0,%1,%2,%3},{%4,%5,%6,%7},{%8,%9},{%10,%10,%10,%10};"
                 : "=f"(d[0]), "=f"(d[1]), "=f"(d[2]), "=f"(d[3]) : "r"(a[0]), "r"(a[1]), "r"(a[2]), "r"(a[3]), "r"(b0), "r"(b1), "f"(0.f));
}
__device__ __forceinline__ void mma8(float* d, uint32_t a0, uint32_t a1, uint32_t b0) {
    asm volatile("mma.sync.aligned.m16n8k8.row.col.f32.bf16.bf16.f32 {%0,%1,%2,%3},{%4,%5},{%6},{%0,%1,%2,%3};"
                 : "+f"(d[0]), "+f"(d[1]), "+f"(d[2]), "+f"(d[3]) : "r"(a0), "r"(a1), "r"(b0));
}
template <int ACC>
__device__ __forceinline__ void mma_sp(float* d, const uint32_t* a, const uint32_t* b) {
    if (ACC)
        asm volatile("mma.sp::ordered_metadata.sync.aligned.m16n8k32.row.col.f32.bf16.bf16.f32 {%0,%1,%2,%3},{%4,%5,%6,%7},{%8,%9,%10,%11},{%0,%1,%2,%3},%12,0x0;"
                     : "+f"(d[0]), "+f"(d[1]), "+f"(d[2]), "+f"(d[3])
                     : "r"(a[0]), "r"(a[1]), "r"(a[2]), "r"(a[3]), "r"(b[0]), "r"(b[1]), "r"(b[2]), "r"(b[3]), "r"(0xEEEE4444u));
    else
        asm volatile("mma.sp::ordered_metadata.sync.aligned.m16n8k32.row.col.f32.bf16.bf16.f32 {%0,%1,%2,%3},{%4,%5,%6,%7},{%8,%9,%10,%11},{%13,%13,%13,%13},%12,0x0;"
                     : "=f"(d[0]), "=f"(d[1]), "=f"(d[2]), "=f"(d[3])
                     : "r"(a[0]), "r"(a[1]), "r"(a[2]), "r"(a[3]), "r"(b[0]), "r"(b[1]), "r"(b[2]), "r"(b[3]), "r"(0xEEEE4444u), "f"(0.f));
}
__device__ __forceinline__ void mbar_arrive_if0(uint32_t b, uint32_t z) { asm volatile("{.reg .pred p; setp.eq.u32 p, %1, 0; @p mbarrier.arrive.shared::cta.b64 _, [%0];}" ::"r"(b), "r"(z) : "memory"); }
__device__ __forceinline__ void mbar_expect_if0(uint32_t b, uint32_t tx, uint32_t z) { asm volatile("{.reg .pred p; setp.eq.u32 p, %2, 0; @p mbarrier.arrive.expect_tx.shared::cta.b64 _, [%0], %1;}" ::"r"(b), "r"(tx), "r"(z) : "memory"); }
__device__ __forceinline__ float lds32f(uint32_t a) { float v; asm volatile("ld.shared.f32 %0,[%1];" : "=f"(v) : "r"(a) : "memory"); return v; }
__device__ __forceinline__ void wg_fence() { asm volatile("wgmma.fence.sync.aligned;" ::: "memory"); }
__device__ __forceinline__ void wg_commit() { asm volatile("wgmma.commit_group.sync.aligned;" ::: "memory"); }
template <int N> __device__ __forceinline__ void wg_wait() { asm volatile("wgmma.wait_group.sync.aligned %0;" ::"n"(N) : "memory"); }
__device__ __forceinline__ void delay(unsigned n) { if (n) { const unsigned t0 = clk(); while (clk() - t0 < n) {} } }
template <int ACC, uint32_t DHI = 0x40000040u>
__device__ __forceinline__ void wg_rs_n32(float* d, const uint32_t* a, uint32_t dlo) {
    if (ACC)
        asm volatile("{.reg .b64 db; mov.b64 db, {%20, %21};\n"
                     "wgmma.mma_async.sync.aligned.m64n32k16.f32.bf16.bf16 {%0,%1,%2,%3,%4,%5,%6,%7,%8,%9,%10,%11,%12,%13,%14,%15},{%16,%17,%18,%19},db,1,1,1,0;}"
                     : "+f"(d[0]), "+f"(d[1]), "+f"(d[2]), "+f"(d[3]), "+f"(d[4]), "+f"(d[5]), "+f"(d[6]), "+f"(d[7]),
                       "+f"(d[8]), "+f"(d[9]), "+f"(d[10]), "+f"(d[11]), "+f"(d[12]), "+f"(d[13]), "+f"(d[14]), "+f"(d[15])
                     : "r"(a[0]), "r"(a[1]), "r"(a[2]), "r"(a[3]), "r"(dlo), "r"(DHI));
    else
        asm volatile("{.reg .b64 db; mov.b64 db, {%20, %21};\n"
                     "wgmma.mma_async.sync.aligned.m64n32k16.f32.bf16.bf16 {%0,%1,%2,%3,%4,%5,%6,%7,%8,%9,%10,%11,%12,%13,%14,%15},{%16,%17,%18,%19},db,0,1,1,0;}"
                     : "=f"(d[0]), "=f"(d[1]), "=f"(d[2]), "=f"(d[3]), "=f"(d[4]), "=f"(d[5]), "=f"(d[6]), "=f"(d[7]),
                       "=f"(d[8]), "=f"(d[9]), "=f"(d[10]), "=f"(d[11]), "=f"(d[12]), "=f"(d[13]), "=f"(d[14]), "=f"(d[15])
                     : "r"(a[0]), "r"(a[1]), "r"(a[2]), "r"(a[3]), "r"(dlo), "r"(DHI));
}
__device__ __forceinline__ uint32_t desc_lo(uint32_t addr) { return ((addr & 0x3FFFF) >> 4) | (1u << 16); }
__device__ __forceinline__ void tma2d(uint32_t dst, const CUtensorMap* m, int c0, int c1, uint32_t bar) {
    asm volatile("cp.async.bulk.tensor.2d.shared::cluster.global.mbarrier::complete_tx::bytes [%0], [%1, {%2,%3}], [%4];"
                 ::"r"(dst), "l"(m), "r"(c0), "r"(c1), "r"(bar) : "memory");
}
__device__ __forceinline__ void tma3d(uint32_t dst, const CUtensorMap* m, int c0, int c1, int c2, uint32_t bar) {
    asm volatile("cp.async.bulk.tensor.3d.shared::cluster.global.mbarrier::complete_tx::bytes [%0], [%1, {%2,%3,%4}], [%5];"
                 ::"r"(dst), "l"(m), "r"(c0), "r"(c1), "r"(c2), "r"(bar) : "memory");
}
__device__ __forceinline__ void tma3d_mc(uint32_t dst, const CUtensorMap* m, int c0, int c1, int c2, uint32_t bar, uint16_t mask) {
    asm volatile("cp.async.bulk.tensor.3d.shared::cluster.global.mbarrier::complete_tx::bytes.multicast::cluster [%0], [%1, {%2,%3,%4}], [%5], %6;"
                 ::"r"(dst), "l"(m), "r"(c0), "r"(c1), "r"(c2), "r"(bar), "h"(mask) : "memory");
}
__device__ __forceinline__ void bulk_g2s_mc(uint32_t dst, const void* src, uint32_t bytes, uint32_t bar, uint16_t mask) {
    asm volatile("cp.async.bulk.shared::cluster.global.mbarrier::complete_tx::bytes.multicast::cluster [%0], [%1], %2, [%3], %4;"
                 ::"r"(dst), "l"(src), "r"(bytes), "r"(bar), "h"(mask) : "memory");
}
__device__ __forceinline__ void tma2d_prefetch(const CUtensorMap* m, int c0, int c1) {
    asm volatile("cp.async.bulk.prefetch.tensor.2d.L2.global [%0, {%1,%2}];" ::"l"(m), "r"(c0), "r"(c1) : "memory");
}
__device__ __forceinline__ void bulk_s2c(uint32_t dst, uint32_t src, uint32_t bytes, uint32_t bar) {
    asm volatile("cp.async.bulk.shared::cluster.shared::cta.mbarrier::complete_tx::bytes [%0], [%1], %2, [%3];" ::"r"(dst), "r"(src), "r"(bytes), "r"(bar) : "memory");
}
__device__ __forceinline__ void bulk_s2g(void* dst, uint32_t src, uint32_t bytes) {
    asm volatile("cp.async.bulk.global.shared::cta.bulk_group [%0], [%1], %2;" ::"l"(dst), "r"(src), "r"(bytes) : "memory");
}
__device__ __forceinline__ void bulk_commit() { asm volatile("cp.async.bulk.commit_group;" ::: "memory"); }
__device__ __forceinline__ void bulk_wait0() { asm volatile("cp.async.bulk.wait_group 0;" ::: "memory"); }
__device__ __forceinline__ uint4 ld_poll(const void* p) {
    uint4 v;
    asm volatile("ld.relaxed.gpu.global.v4.u32 {%0,%1,%2,%3},[%4];" : "=r"(v.x), "=r"(v.y), "=r"(v.z), "=r"(v.w) : "l"(p) : "memory");
    return v;
}
__device__ __forceinline__ unsigned ld_acquire(const unsigned* p) { unsigned v; asm volatile("ld.acquire.gpu.global.u32 %0,[%1];" : "=r"(v) : "l"(p) : "memory"); return v; }
__device__ __forceinline__ void red_release(unsigned* p, unsigned v) { asm volatile("red.release.gpu.global.add.u32 [%0], %1;" ::"l"(p), "r"(v) : "memory"); }

__device__ __forceinline__ void publish(unsigned* p) {
    asm volatile("fence.proxy.async.global;" ::: "memory");
    asm volatile("red.relaxed.gpu.global.add.u32 [%0], 1;" ::"l"(p) : "memory");
}
template <int ID, int N> __device__ __forceinline__ void bar_sync() { asm volatile("bar.sync %0, %1;" ::"n"(ID), "n"(N) : "memory"); }
template <int ID, int N> __device__ __forceinline__ void bar_arrive() { asm volatile("bar.arrive %0, %1;" ::"n"(ID), "n"(N) : "memory"); }
__device__ __forceinline__ void cluster_arrive() { asm volatile("barrier.cluster.arrive.relaxed.aligned;" ::: "memory"); }
__device__ __forceinline__ void cluster_wait() { asm volatile("barrier.cluster.wait.aligned;" ::: "memory"); }

constexpr uint32_t XB_BYTES = 36864;
constexpr uint32_t S_XB = 0;
constexpr uint32_t S_QM = 73728;
constexpr uint32_t S_KM = 74752;
constexpr uint32_t S_OM = 75776;
constexpr uint32_t S_SP = 77824;
constexpr uint32_t S_SUM = 80384;
constexpr uint32_t S_TGT = 81408;
constexpr uint32_t S_VM = 147456;
constexpr uint32_t S_QX = 86016;
constexpr uint32_t S_PX = S_QX;
constexpr uint32_t S_KX = 94208;
constexpr uint32_t S_VX = 102400;
constexpr uint32_t S_SX = 135168;
constexpr uint32_t S_OX = 155648;
constexpr uint32_t S_MEM = 172032;
constexpr uint32_t S_WO = 181248;
constexpr uint32_t S_BAR = 230400;
constexpr uint32_t A_SMEM = S_BAR + 128;
__host__ __device__ constexpr uint32_t s_w(int c) { return c == 0 ? S_WO : 73728 + (c - 1) * 49152; }
constexpr uint32_t B_W = S_BAR, B_WO = S_BAR + 24, B_X = S_BAR + 32, B_S = S_BAR + 48, B_VX = S_BAR + 56, B_SX = S_BAR + 72, B_M = S_BAR + 88, B_T = S_BAR + 112;
constexpr int NB_QK = 1, NB_O = 2, NB_RED = 3, NB_P = 4, NB_AUX = 5, NB_PRO = 6, NB_X = 7, NB_GO = 8;

constexpr float SM_SCALE = 0.08838834764831845f * 1.4426950408889634f;
constexpr uint32_t ONES = 0x3F803F80u;
constexpr uint32_t FULL_COUNT = 0x4200u;
#define XLIM NSEG
#define XTMA_DELAY 0
#define SX_DELAY 0
#define TGT_NS 1072
#define LOOK_NS 100
#define RCP_AT 2
#define NCH 2
#define POLL_AT 1
#define OX_DELAY 0
#define XTMA_NS 50
#define REG_MAIN0 232
#define REG_MAIN1 232
#define REG_AUX 40

#define PV_MODE 1
#define OX_AT 1
#define FLAG_NS 100
#define OFF 0
static_assert(REG_MAIN0 + REG_MAIN1 + REG_AUX <= 504, "the three warpgroups share 3 x 168 registers");
#define HSTAMP(i) do {} while (0)
#define HSTAMP2(i) do {} while (0)
#define TSTAMP(i, e) do {} while (0)

__device__ __forceinline__ void load_scores(uint32_t a, __half2 (&hs)[5]) {
    uint32_t r[10];
    ldsm4(r, a);
    ldsm4(r + 4, a + 512);
    ldsm2(r + 8, a + 1024);
    const __half2 hf = as_h2(0x38003800u);
#pragma unroll
    for (int T = 0; T < 5; T++) hs[T] = __hfma2(as_h2(r[2 * T]), hf, __hmul2(as_h2(r[2 * T + 1]), hf));
}
__device__ __forceinline__ void softmax_exp(const __half2 (&hs)[5], float (&ev)[10]) {
    __half2 m = __hmax2(__hmax2(__hmax2(hs[0], hs[1]), __hmax2(hs[2], hs[3])), hs[4]);
    const uint32_t mu = as_u32(m);
    const uint32_t m1 = __shfl_xor_sync(0xffffffffu, mu, 1), m2 = __shfl_xor_sync(0xffffffffu, mu, 2), m3 = __shfl_xor_sync(0xffffffffu, mu, 3);
    m = __hmax2(__hmax2(m, as_h2(m1)), __hmax2(as_h2(m2), as_h2(m3)));
    const float mc = -fmaxf(__low2float(m), __high2float(m)) * (2.f * SM_SCALE);
#pragma unroll
    for (int T = 0; T < 5; T++) {
        ev[2 * T] = ex2(fmaf(__low2float(hs[T]), 2.f * SM_SCALE, mc));
        ev[2 * T + 1] = ex2(fmaf(__high2float(hs[T]), 2.f * SM_SCALE, mc));
    }
}

__device__ __forceinline__ void x_scores(uint32_t sb, int seg, int wq, uint32_t L16, float (&ev)[10]) {
    __half2 hs[5];
    load_scores(sb + S_SX + (seg & 1) * 5120 + wq * 1280 + L16, hs);
    const int dg = (int)(L16 >> 6) - (int)((L16 >> 3) & 6) + 8 * wq;
#pragma unroll
    for (int T = 0; T < 4; T++) {
        uint32_t u = as_u32(hs[T]);
        if (dg < 8 * T + 1) u = (u & 0xFFFFu) | 0xFC000000u;
        if (dg < 8 * T) u = 0xFC00FC00u;
        hs[T] = as_h2(u);
    }
    softmax_exp(hs, ev);
}
__device__ __forceinline__ void x_probs(uint32_t sb, int seg, int wq, uint32_t L16, const float (&ev)[10]) {
    float l = ((ev[0] + ev[1]) + (ev[2] + ev[3])) + ((ev[4] + ev[5]) + (ev[6] + ev[7])) + (ev[8] + ev[9]);
    const float l1 = __shfl_xor_sync(0xffffffffu, l, 1), l2 = __shfl_xor_sync(0xffffffffu, l, 2), l3 = __shfl_xor_sync(0xffffffffu, l, 3);
    const float r = rcp((l + l1) + (l2 + l3));
    const uint32_t a = sb + S_PX + (seg & 1) * 4096 + wq * 640 + (L16 >> 2);
#pragma unroll
    for (int i = 0; i < 5; i++) sts32(a + i * 128, pack_bf16(ev[2 * i] * r, ev[2 * i + 1] * r));
    fence_async_smem();
}
__device__ __forceinline__ void x_pv_load(uint32_t sb, int seg, int w, uint32_t L16, uint32_t (&a)[3][4]) {
    lds128(a[0], sb + S_VX + (seg & 3) * 8192 + w * 1024 + L16);
    lds128(a[1], sb + S_VX + (seg & 3) * 8192 + w * 1024 + 512 + L16);
    lds64(a[2], sb + S_VM + (seg & 3) * 2048 + w * 256 + (L16 >> 1));
    a[2][2] = 0; a[2][3] = 0;
}
__device__ __forceinline__ void x_pv_run(uint32_t sb, int seg, int w, uint32_t L16, const uint32_t (&a)[3][4]) {
    const uint32_t d = ((sb + S_PX + (seg & 1) * 4096) & 0x3FFFF) >> 4;
    float o[16];
    wg_fence();
    wg_rs_n32<0, 40>(o, a[0], d | (8u << 16));
    wg_rs_n32<1, 40>(o, a[1], (d + 16) | (8u << 16));
    wg_rs_n32<1, 40>(o, a[2], d + 32);
    wg_commit();
    wg_wait<0>();
    const uint32_t ox = sb + S_OX + (seg & 1) * 8192 + (w >> 2) * 4096 + (L16 & 0x100) * 4 + (L16 & 0x70) * 8 +
                        ((((w & 3) * 32) | ((L16 >> 3) & 0x10)) ^ (L16 & 0x70));
    stsm4t(ox, pack_bf16(o[0], o[1]), pack_bf16(o[2], o[3]), pack_bf16(o[4], o[5]), pack_bf16(o[6], o[7]));
    stsm4t(ox + 2048, pack_bf16(o[8], o[9]), pack_bf16(o[10], o[11]), pack_bf16(o[12], o[13]), pack_bf16(o[14], o[15]));
}
__device__ __forceinline__ void ox_publish(int seg, uint32_t h) { bulk_wait0(); publish(&g_flag[seg * 4 + (h >> 3)]); }
__device__ __forceinline__ void ox_store(uint32_t sb, int seg, uint32_t h) {
    fence_async_smem();
    bulk_s2g(g_ox + (seg * NH + h) * 512, sb + S_OX + (seg & 1) * 8192, 8192);
    bulk_commit();
}

__device__ __forceinline__ void x_epilogue(uint32_t sb, const float (&d)[16], int seg, bool isv, int w, uint32_t L16) {
    uint32_t pk[8];
#pragma unroll
    for (int i = 0; i < 8; i++) pk[i] = pack_bf16(d[2 * i], d[2 * i + 1]);
    if (!isv) {
        const uint32_t a = sb + S_QX + (w >> 2) * 8192 + (seg & 1) * 4096 + (w & 3) * 256 + (L16 & 0xF0) + (L16 & 0x100) * 4;
        stsm4t(a, pk[0], pk[1], pk[2], pk[3]);
        stsm4t(a + 2048, pk[4], pk[5], pk[6], pk[7]);
    } else {
        const uint32_t a = sb + S_VX + (seg & 3) * 8192 + w * 1024 + L16;
        sts128(a, pk[0], pk[1], pk[2], pk[3]);
        sts128(a + 512, pk[4], pk[5], pk[6], pk[7]);
    }
}

template <int K0, int K1>
__device__ __forceinline__ void x_project(float (&d)[16], const uint32_t (&wA)[36][4], uint32_t desc) {
#pragma unroll
    for (int i = K0; i < K1; i++) {
        const uint32_t db = desc + (((i >> 2) * 4096 + (i & 3) * 32) >> 4);
        if (i == 0) wg_rs_n32<0>(d, wA[i], db); else wg_rs_n32<1>(d, wA[i], db);
    }
}

__device__ __forceinline__ void mem_scores(uint32_t sb, uint32_t peerA, uint32_t peerB, uint32_t off, const uint32_t (&q0)[4], const uint32_t (&q1)[4],
                                           const uint32_t (&k0)[4], const uint32_t (&k1)[4]) {
    float e0[4], o0[4], e1[4], o1[4];
    mma16z(e0, q0, k0[0], k0[1]);
    mma16z(o0, q0, k0[2], k0[3]);
    mma16z(e1, q1, k1[0], k1[1]);
    mma16z(o1, q1, k1[2], k1[3]);
    const uint32_t sc = pack_f16_sat((e0[0] + o0[2]) + (e1[0] + o1[2]), (e0[1] + o0[3]) + (e1[1] + o1[3]));
    st_async32(peerB + off, sc, peerB + B_S);
    st_async32(peerA + off, sc, peerA + B_S);
    sts32(sb + off, sc);
    __syncwarp();
}

__device__ __forceinline__ unsigned post_time(int s, uint32_t L16) {
    delay(1);
    const unsigned t = gtime() | 1;
    if (L16 == 0) asm volatile("st.relaxed.gpu.global.u32 [%0], %1;" ::"l"(reinterpret_cast<unsigned*>(g_acc) + s * 96 + blockIdx.x), "r"(t) : "memory");
    return t;
}
__device__ __forceinline__ void plan_look(uint32_t sb, int s, uint32_t L16, unsigned t) {
    const char* p = reinterpret_cast<const char*>(g_acc) + s * 384 + (L16 < 384 ? L16 : 0);
    uint4 v;
    unsigned c = 0;
    do { v = ld_poll(p); } while (__any_sync(0xffffffffu, (v.x & v.y & v.z & v.w & 1) == 0) && ++c < SPIN_LIM);
    const int d = max(max((int)(v.x - t), (int)(v.y - t)), max((int)(v.z - t), (int)(v.w - t)));
    const unsigned tgt = t + min(__reduce_max_sync(0xffffffffu, d), 20000) + TGT_NS;
    if (L16 < 48) { const uint32_t r = mapa(sb, L16 >> 4); st_async32(r + S_TGT, tgt, r + B_T); }
}

template <int ROLE>
__device__ __forceinline__ void chain_main(const uint32_t sb, const uint32_t lane16, const int wq, const uint32_t j, const uint32_t h,
                                           const uint32_t peerA, const uint32_t peerB) {
    uint32_t L16 = lane16;
    constexpr bool isv = ROLE >= 2;
    constexpr int wg = ROLE & 1;
    const int w = wg * 4 + wq;
    const uint32_t xdesc = desc_lo(sb + S_XB);
    const uint32_t zero = h >> 20;
    uint32_t wA[36][4], woA[8][4], woB[4][4];
    float xd[16];
    {
        const int m = L16 >> 7, r = (L16 >> 4) & 7;
        const int blk = (ROLE == 1) ? ((wq & 2) * 2 + (wq & 1) + (m & 1) * 2) : (2 * wq + (m & 1));
        const uint32_t a = sb + wg * 24576 + ((m >> 1) * 8 + r) * 128 + ((blk ^ r) << 4);
        mbar_wait(sb + B_X, 0);
#pragma unroll
        for (int c = 0; c < 3; c++) {
            mbar_wait(sb + B_W + 8 * c, 0);
#pragma unroll
            for (int i = 0; i < 12; i++) ldsm4t(wA[12 * c + i], a + s_w(c) + i * 2048);
            if (c == 0) bar_arrive<NB_PRO, 384>();
            if (c == 2) { bar_sync<NB_O, 256>(); cluster_arrive(); }
            wg_fence();
            if (c == 0) x_project<0, 12>(xd, wA, xdesc);
            if (c == 1) x_project<12, 24>(xd, wA, xdesc);
            if (c == 2) x_project<24, 36>(xd, wA, xdesc);
            wg_commit();
            wg_wait<0>();
        }
        x_epilogue(sb, xd, 0, isv, w, L16);
        bar_arrive<NB_RED, 384>();
        mbar_wait(sb + B_WO, 0);
        const int ca = 3 * w + (m & 1), cb = 3 * w + 2;
        const uint32_t aA = sb + S_WO + (ca >> 3) * 16384 + ((m >> 1) * 8 + r) * 128 + (((ca & 7) ^ r) << 4);
        const int eB = ((m & 2) + ((r >> 1) & 1)) * 8 + 4 * (m & 1) + 2 * (r >> 2) + (r & 1);
        const uint32_t aB = sb + S_WO + (cb >> 3) * 16384 + eB * 128 + (((cb & 7) ^ (eB & 7)) << 4);
#pragma unroll
        for (int i = 0; i < 8; i++) ldsm4t(woA[i], aA + i * 2048);
#pragma unroll
        for (int i = 0; i < 4; i++) ldsm4t(woB[i], aB + i * 4096);
        mbar_wait(sb + B_X + 8, 0);
        cluster_wait();
        bar_sync<NB_O, 256>();
        wg_fence();
        x_project<0, 36>(xd, wA, xdesc + (XB_BYTES >> 4));
        wg_commit();
    }
    int s = 0;
#pragma unroll 1
    while (true) {
        const uint32_t par = s & 1;
        const uint32_t kx = sb + S_KX + par * 4096;
        asm volatile("" : "+r"(L16));
        wg_wait<0>();
        x_epilogue(sb, xd, s + 1, isv, w, L16);
        float c0[4], c1[4];
        uint32_t k0[4], k1[4], pva[3][4];
        {
            const uint32_t a = sb + S_MEM + L16;
            constexpr int CH = 18 / NCH;
            uint32_t b[3][4];
            bool ready = true;
            mbar_wait(sb + B_M, par);
            ldsm4(b[0], a);
            ldsm4(b[1], a + 512);
            bar_arrive<NB_GO, 288>();
#pragma unroll
            for (int i = 0; i < 18; i++) {
                if ((i + 4) % CH == 0 && i + 4 < 18) ready = mbar_test(sb + B_M + ((i + 4) / CH) * 8, par);
                if ((i + 2) % CH == 0 && i + 2 < 18) { if (__builtin_expect(!ready, 0)) mbar_wait(sb + B_M + ((i + 2) / CH) * 8, par); }
                if (i + 2 < 18) ldsm4(b[(i + 2) % 3], a + (i + 2) * 512);
                if (ROLE == 0 && i == 16) ldsm4(k0, kx + wq * 1024 + L16);
                if (ROLE == 0 && i == 17) ldsm4(k1, kx + wq * 1024 + 512 + L16);
                if (PV_MODE == 0 && !(OFF & 8) && isv && i == 17) x_pv_load(sb, s + 2, w, L16, pva);
                if (i == 0) { mma16z(c0, wA[0], b[0][0], b[0][1]); mma16z(c1, wA[1], b[0][2], b[0][3]); }
                else { mma16(c0, wA[2 * i], b[i % 3][0], b[i % 3][1]); mma16(c1, wA[2 * i + 1], b[i % 3][2], b[i % 3][3]); }
            }
        }
        const uint32_t p0 = pack_bf16(c0[0] + c1[0], c0[1] + c1[1]), p1 = pack_bf16(c0[2] + c1[2], c0[3] + c1[3]);
        if (!isv) {
            stsm2t(sb + S_QM + w * 256 + L16, p0, p1);
            bar_sync<NB_QK, 384>();
            if (ROLE == 0) {
                uint32_t q0[4], q1[4];
                ldsm4(q0, sb + S_QM + L16);
                ldsm4(q1, sb + S_QM + 512 + L16);
                mem_scores(sb, peerA, peerB, S_SP + j * 128 + wq * 256 + (L16 >> 2), q0, q1, k0, k1);
                mbar_arrive_if0(sb + B_S, L16);
            } else {
                if (s + 2 < XLIM) mbar_wait(sb + B_X + par * 8, ((s + 2) >> 1) & 1);
                if (wq != 0 && !(OFF & 16)) {
                    const int rt = (wq == 3) ? 0 : 1;
                    const uint32_t qa = sb + S_QX + par * 4096 + rt * 2048 + (L16 & 0x80) * 8 + (L16 & 0x170);
                    const uint32_t kb0 = (wq == 2 ? kx + 2048 : sb + S_KM) + L16;
                    const uint32_t kb1 = (wq == 2 ? kx + 3072 : kx) + L16;
                    const uint32_t kb2 = kx + 1024 + L16;
                    float a0[4], a1[4], a2[4];
#pragma unroll
                    for (int hf = 0; hf < 2; hf++) {
                        uint32_t qa0[4], qa1[4], b[4];
                        ldsm4(qa0, qa + hf * 512);
                        ldsm4(qa1, qa + hf * 512 + 128);
                        ldsm4(b, kb0 + hf * 512);
                        if (hf == 0) mma16z(a0, qa0, b[0], b[1]); else mma16(a0, qa0, b[0], b[1]);
                        mma16(a0, qa1, b[2], b[3]);
                        ldsm4(b, kb1 + hf * 512);
                        if (hf == 0) mma16z(a1, qa0, b[0], b[1]); else mma16(a1, qa0, b[0], b[1]);
                        mma16(a1, qa1, b[2], b[3]);
                        ldsm4(b, kb2 + hf * 512);
                        if (hf == 0) mma16z(a2, qa0, b[0], b[1]); else mma16(a2, qa0, b[0], b[1]);
                        mma16(a2, qa1, b[2], b[3]);
                    }
                    mbar_wait(sb + B_S, par);
                    delay(SX_DELAY);
                    const uint32_t dst = peerB + S_SX + par * 5120 + j * 128 + rt * 2560 + (L16 >> 2);
                    const uint32_t bar = peerB + B_SX + par * 8;
                    const uint32_t T0 = (wq == 2 ? 2 : 4) * 256, T1 = (wq == 2 ? 3 : 0) * 256;
                    st_async32(dst + T0, pack_f16_sat(a0[0], a0[1]), bar);
                    st_async32(dst + 1280 + T0, pack_f16_sat(a0[2], a0[3]), bar);
                    if (wq != 2) st_async32(dst + T1, pack_f16_sat(a1[0], a1[1]), bar);
                    st_async32(dst + 1280 + T1, pack_f16_sat(a1[2], a1[3]), bar);
                    if (wq == 1) st_async32(dst + 256, pack_f16_sat(a2[0], a2[1]), bar);
                    if (wq != 2) st_async32(dst + 1280 + 256, pack_f16_sat(a2[2], a2[3]), bar);
                }
            }
        } else {
            const uint32_t off = S_VM + (s & 3) * 2048 + w * 256 + (L16 >> 1);
            st_async64(peerA + off, p0, p1, peerA + B_S);
            st_async64(peerB + off, p0, p1, peerB + B_S);
            sts64(sb + off, p0, p1);
            __syncwarp();
            mbar_expect_if0(sb + B_S, 160, L16);
            if (PV_MODE == 1 || (PV_MODE == 2 && ROLE == 3)) x_pv_load(sb, s + 2, w, L16, pva);
            if (PV_MODE == 2 && ROLE == 2) bar_arrive<NB_P, 384>(); else bar_sync<NB_P, 384>();
            if (PV_MODE == 2) {
                if (ROLE == 3) { x_pv_run(sb, s + 2, w, L16, pva); x_pv_load(sb, s + 2, wq, L16, pva); x_pv_run(sb, s + 2, wq, L16, pva); }
            } else
            if (!(OFF & 8)) x_pv_run(sb, s + 2, w, L16, pva);
            if (ROLE == 3 && s + 2 < XLIM) mbar_wait(sb + B_X + par * 8, ((s + 2) >> 1) & 1);
        }
        if (s == NSEG - 1) break;
        if (wg == 0) {
            if (!isv) mbar_wait(sb + B_VX + par * 8, (s >> 1) & 1);
            uint32_t va[4][4];
            const uint32_t vx = sb + S_VX + (s & 3) * 8192 + wq * 2048 + L16;
            const uint32_t vm = sb + S_VM + (s & 3) * 2048 + wq * 512 + (L16 >> 1);
            lds128(va[0], vx);
            lds128(va[2], vx + 1024);
            mbar_wait(sb + B_S, par);
            __half2 hs[5];
            load_scores(sb + S_SP + L16, hs);
            float ev[10];
            softmax_exp(hs, ev);
            lds128(va[1], vx + 512);
            lds128(va[3], vx + 1536);
            uint32_t p[5];
#pragma unroll
            for (int i = 0; i < 5; i++) p[i] = pack_bf16(ev[2 * i], ev[2 * i + 1]);
            uint32_t vm0[2], vm1[2];
            const uint32_t ones[4] = {ONES, ONES, ONES, ONES};
            float sum[4], o0[4], o1[4];
            mma16z(o0, va[0], p[0], p[1]);
            mma16z(o1, va[2], p[0], p[1]);
            mma16z(sum, ones, p[0], p[1]);
            lds64(vm0, vm);
            lds64(vm1, vm + 256);
            mma16(o0, va[1], p[2], p[3]);
            mma16(o1, va[3], p[2], p[3]);
            mma16(sum, ones, p[2], p[3]);
            mma8(o0, vm0[0], vm0[1], p[4]);
            mma8(o1, vm1[0], vm1[1], p[4]);
            mma8(sum, ONES, ONES, p[4]);
            stsm4t(sb + S_OM + wq * 512 + L16, pack_bf16(o0[0], o0[1]), pack_bf16(o0[2], o0[3]), pack_bf16(o1[0], o1[1]), pack_bf16(o1[2], o1[3]));
            sts64(sb + S_SUM + wq * 256 + (L16 >> 1), __float_as_uint(sum[0]), __float_as_uint(sum[1]));
        }
        bar_sync<NB_O, 256>();
        {
            float a0[4], a1[4], e[4];
            float2 sc;
            float sr, r0, r1, rr;
#pragma unroll
            for (int i = 0; i < 4; i++) {
                uint32_t b[4];
                ldsm4(b, sb + S_OM + i * 512 + L16);
                if (i == 0) {
                    mma16z(a0, woA[0], b[0], b[1]); mma16z(a1, woA[1], b[2], b[3]);
                    mma_sp<0>(e, b, woB[0]);
                } else {
                    if (i == 1) { sc = lds64f(sb + S_SUM + (L16 >> 1)); sr = lds32f(sb + S_SUM + ((L16 >> 4) & 0x1C)); }
                    const uint32_t z = __float_as_uint(a0[0]) & zero;
                    mma16(a0, woA[2 * i], b[0], b[1]); mma16(a1, woA[2 * i + 1], b[2], b[3]);
                    mma_sp<1>(e, b, woB[i]);
                    if (i == RCP_AT) {
                        r0 = rcp(__uint_as_float(__float_as_uint(sc.x) | z));
                        r1 = rcp(__uint_as_float(__float_as_uint(sc.y) | z));
                        rr = rcp(__uint_as_float(__float_as_uint(sr) | z));
                    }
                }
            }
            asm volatile("" : "+r"(L16));
            char* const rslot = reinterpret_cast<char*>(g_acc) + ((s + 1) * SLOT_BYTES + j * 8192 + w * 1024) + (L16 + (L16 & 0x1C0));
            asm volatile("red.relaxed.gpu.global.add.noftz.v4.bf16x2 [%0], {%1,%2,%3,%4};"
                         ::"l"(rslot), "r"(pack_bf16((a0[0] + a1[0]) * r0, (a0[1] + a1[1]) * r1)), "r"(pack_bf16((a0[2] + a1[2]) * r0, (a0[3] + a1[3]) * r1)),
                           "r"(pack_bf16((e[0] + e[2]) * rr, (e[1] + e[3]) * rr)), "r"(0x3F80u) : "memory");
        }
        bar_sync<NB_X, 256>();
        wg_fence();
        x_project<0, POLL_AT>(xd, wA, xdesc + par * (XB_BYTES >> 4));
        bar_arrive<NB_RED, 384>();
        x_project<POLL_AT, 36>(xd, wA, xdesc + par * (XB_BYTES >> 4));
        wg_commit();
        s++;
    }
    if (isv) {
        uint32_t pva[3][4];
        x_pv_load(sb, NSEG - 2, w, L16, pva);
        bar_sync<NB_RED, 384>();
        x_pv_run(sb, NSEG - 2, w, L16, pva);
        bar_arrive<NB_QK, 384>();
        x_pv_load(sb, NSEG - 1, w, L16, pva);
        bar_sync<NB_P, 384>();
        x_pv_run(sb, NSEG - 1, w, L16, pva);
        bar_arrive<NB_PRO, 384>();
    }
}

template <bool isv>
__device__ __forceinline__ void chain_aux(const uint32_t sb, const uint32_t lane16, const int wq, const uint32_t j, const uint32_t h,
                                          const uint32_t peerA, const uint32_t peerB, const CUtensorMap* tmWo, const CUtensorMap* tmX,
                                          const bf16* __restrict__ mem0) {
    const int t = wq * 32 + (lane16 >> 4);
    TSTAMP(64, 0);
    cluster_arrive();
    {
        uint4* z = g_acc + blockIdx.x * 1024 + t;
#pragma unroll
        for (int i = 0; i < 8; i++) z[i * 128] = make_uint4(0, 0, 0, 0);
        if (blockIdx.x == 0) { g_flag[t] = 0; g_flag[128 + t] = 0; }
        for (int i = t; i < 576; i += 128) {
            const uint4 v = *reinterpret_cast<const uint4*>(mem0 + (i & 7) * DM + (i >> 3) * 8);
            sts128(sb + S_MEM + i * 16, v.x, v.y, v.z, v.w);
        }
        __threadfence();
        bar_sync<NB_AUX, 128>();
        if (t == 0) red_release(&g_zero_cnt, 1);
        asm volatile("griddepcontrol.launch_dependents;" ::: "memory");
        bar_sync<NB_PRO, 384>();
        if (t == 0) {
            fence_async_smem();
            mbar_expect(sb + B_WO, 49152);
            for (int b = 0; b < 3; b++) tma2d(sb + S_WO + b * 16384, tmWo, 192 * j + 64 * b, h * 128, sb + B_WO);
        }
        unsigned c = 0;
        while (ld_acquire(&g_zero_cnt) < 96 && ++c < SPIN_LIM) {}
        __syncwarp();
        for (int c2 = 0; c2 < 3; c2++) mbar_arrive_if0(sb + B_M + c2 * 8, lane16);
        cluster_wait();
        bar_sync<NB_RED, 384>();
        if (t == 0) {
            fence_async_smem();
            if (!isv) mbar_expect(sb + B_VX, 8192);
            else {
                bulk_s2c(peerA + S_VX, sb + S_VX, 8192, peerA + B_VX);
                bulk_s2c(peerB + S_VX, sb + S_VX, 8192, peerB + B_VX);
            }
            mbar_expect(sb + B_X, XB_BYTES);
            tma3d(sb + S_XB, tmX, 0, 64, 0, sb + B_X);
        }
        __syncwarp();
    }
    TSTAMP(0, 0);
    uint32_t L16 = lane16;
    const char* slot = reinterpret_cast<const char*>(g_acc) + wq * 1024 + (L16 + (L16 & 0x1C0));
    float ev[10];
    int s = 0;
#pragma unroll 1
    while (true) {
        const uint32_t par = s & 1;
        asm volatile("" : "+r"(L16));
        if (!isv) {
            if (wq == 0) {
                bar_sync<NB_QK, 384>();
                uint32_t q0[4], q1[4], k0[4], k1[4];
                ldsm4(q0, sb + S_QM + L16);
                ldsm4(k0, sb + S_KM + L16);
                ldsm4(q1, sb + S_QM + 512 + L16);
                ldsm4(k1, sb + S_KM + 512 + L16);
                mem_scores(sb, peerA, peerB, S_SP + j * 128 + 1024 + (L16 >> 2), q0, q1, k0, k1);
                mbar_expect_if0(sb + B_S, 640 + 2048, L16);
            } else if (wq == 3) {
                bar_sync<NB_GO, 288>();
                const unsigned t = post_time(s, L16);
                bar_sync<NB_QK, 384>();
                if (j == 0 && s < NSEG - 1) {
                    if (LOOK_NS) __nanosleep(LOOK_NS);
                    plan_look(sb, s, L16, t);
                }
            } else {
                bar_arrive<NB_QK, 384>();
                if (wq == 2) {
                    if (L16 == 0) {
                        if (s + 3 < XLIM) mbar_expect(sb + B_X + (par ^ 1) * 8, XB_BYTES);
                        mbar_expect(sb + B_VX + (par ^ 1) * 8, (OFF & 2) ? 0 : 8192);
                        mbar_expect(sb + B_T, 4);
                        if (s == 2 && h == 0 && j == 0) g_zero_cnt = 0;
                    }
                } else if (s + 3 < XLIM && j == 1) {
                    mbar_wait(sb + B_S, par);
                    delay(XTMA_DELAY);
                    if (XTMA_NS) __nanosleep(XTMA_NS);
                    if (L16 == 0) tma3d_mc(sb + S_XB + (par ^ 1) * XB_BYTES, tmX, 0, (s + 3) * SEG, 0, sb + B_X + (par ^ 1) * 8, 7);
                }
                __syncwarp();
            }
        } else {
            if (wq == 3) {
                bar_sync<NB_GO, 288>();
                post_time(s, L16);
            } else if (L16 == 0) {
                if (wq == 0) {
                    if (!(OFF & 2) && s >= 1) {
                        bulk_wait0();
                        bulk_g2s_mc(sb + S_VX + (s & 3) * 8192, g_vx + (h * 2 + par) * 512, 8192, sb + B_VX + par * 8, 3);
                    }
                } else if (wq == 1) {
                    if (OX_AT == 0 && s >= 3) ox_publish(s - 3, h);
                    if (OX_AT != 0 && s >= 4) ox_publish(s - 4, h);
                } else {
                    mbar_expect(sb + B_SX + par * 8, (OFF & 16) ? 0 : 3584);
                    mbar_expect(sb + B_T, 4);
                    if (s + 3 < XLIM) mbar_expect(sb + B_X + (par ^ 1) * 8, XB_BYTES);
                }
            }
            __syncwarp();
            if (s >= 1) mbar_wait(sb + B_SX + (par ^ 1) * 8, ((s - 1) >> 1) & 1);
            bar_sync<NB_P, 384>();
            if (OX_AT == 1 && wq == 1) { if (L16 == 0 && s >= 3) ox_store(sb, s - 3, h); __syncwarp(); }
            if (!(OFF & 4) || s == NSEG - 1) x_scores(sb, s + 1, wq, L16, ev);
            if (OX_AT == 2 && wq == 1) { if (L16 == 0 && s >= 3) ox_store(sb, s - 3, h); __syncwarp(); }
            if (wq == 0) {
                if (!(OFF & 2) && L16 == 0 && s + 1 < NSEG) {
                    fence_async_smem();
                    bulk_s2g(g_vx + (h * 2 + (par ^ 1)) * 512, sb + S_VX + ((s + 1) & 3) * 8192, 8192);
                    bulk_commit();
                }
                __syncwarp();
            }
        }
        if (s == NSEG - 1) break;
        bar_sync<NB_RED, 384>();
        if (isv && !(OFF & 4)) x_probs(sb, s + 1, wq, L16, ev);
        asm volatile("" : "+r"(L16));
        slot += SLOT_BYTES;
        mbar_wait(sb + B_T, par);
        {
            const unsigned tgt = __float_as_uint(lds32f(sb + S_TGT));
            while ((int)(gtime() - tgt) < 0) {}
        }
        uint4 v[6];
#pragma unroll
        for (int i = 0; i < 6; i++) v[i] = ld_poll(slot + i * 4096);
        if (OX_AT == 0 && !(OFF & 1) && isv && wq == 1 && s >= 2) { delay(OX_DELAY); if (L16 == 0) ox_store(sb, s - 2, h); __syncwarp(); }
        s++;
        const uint32_t ma = sb + S_MEM + wq * 384 + L16;
        unsigned c = 0;
        constexpr int CW = 6 / NCH;
        int done = NCH;
#pragma unroll
        for (int k = 0; k < NCH; k++) {
            uint32_t bad = 0;
#pragma unroll
            for (int i = CW * k; i < CW * k + CW; i++) { stsm2t(ma + i * 1536, v[i].x, v[i].y); stsm1(ma + i * 1536 + 256, v[i].z); bad |= v[i].w ^ FULL_COUNT; }
            const bool again = __any_sync(0xffffffffu, bad != 0);
            mbar_arrive_if0(sb + B_M + k * 8, L16 | (uint32_t)again);
            if (again) { done = k; break; }
        }
        if (done < NCH) {
            uint32_t bad;
            do {
#pragma unroll
                for (int i = 0; i < 6; i++) if (i >= CW * done) v[i] = ld_poll(slot + i * 4096);
                bad = 0;
#pragma unroll
                for (int i = 0; i < 6; i++) if (i >= CW * done) { stsm2t(ma + i * 1536, v[i].x, v[i].y); stsm1(ma + i * 1536 + 256, v[i].z); bad |= v[i].w ^ FULL_COUNT; }
            } while (++c < SPIN_LIM && __any_sync(0xffffffffu, bad != 0));
            __syncwarp();
#pragma unroll
            for (int k = 0; k < NCH; k++) if (k >= done) mbar_arrive_if0(sb + B_M + k * 8, L16);
        }
        TSTAMP(s, c | t_pack);
    }
    if (!isv) {
        mbar_wait(sb + B_VX + 8, ((NSEG - 1) >> 1) & 1);
        mbar_wait(sb + B_S, 1);
    } else {
        x_probs(sb, NSEG - 2, wq, L16, ev);
        if (OX_AT != 0 && wq == 1) { if (L16 == 0) ox_publish(NSEG - 4, h); __syncwarp(); }
        bar_sync<NB_RED, 384>();
        if (wq == 1 && L16 == 0) ox_store(sb, NSEG - 3, h);
        __syncwarp();
        bar_sync<NB_QK, 384>();
        if (wq == 2 && L16 == 0) ox_store(sb, NSEG - 2, h);
        __syncwarp();
        mbar_wait(sb + B_S, 1);
        mbar_wait(sb + B_SX + 8, ((NSEG - 1) >> 1) & 1);
        x_scores(sb, NSEG - 1, wq, L16, ev);
        x_probs(sb, NSEG - 1, wq, L16, ev);
        if (wq == 1 && L16 == 0) ox_publish(NSEG - 3, h);
        __syncwarp();
        bar_arrive<NB_P, 384>();
        if (wq == 2) { if (L16 == 0) ox_publish(NSEG - 2, h); __syncwarp(); bar_arrive<NB_PRO, 384>(); }
        else bar_sync<NB_PRO, 384>();
        if (wq == 3 && L16 == 0) { ox_store(sb, NSEG - 1, h); ox_publish(NSEG - 1, h); }
    }
}

__global__ void __launch_bounds__(384, 1)
chain_kernel(const __grid_constant__ CUtensorMap tmWq, const __grid_constant__ CUtensorMap tmWk, const __grid_constant__ CUtensorMap tmWv,
             const __grid_constant__ CUtensorMap tmWo, const __grid_constant__ CUtensorMap tmX, const bf16* __restrict__ mem0) {
    extern __shared__ __align__(1024) uint8_t smem[];
    const uint32_t sb = smem_u32(smem);
    const int tid = threadIdx.x;
    const uint32_t L16 = __shfl_sync(0xffffffffu, (tid & 31) * 16, tid & 31);
    const int w = __shfl_sync(0xffffffffu, tid >> 5, 0), wg = w >> 2, wq = w & 3;
    uint32_t j, h;
    asm("mov.u32 %0, %%cluster_ctarank;" : "=r"(j));
    asm("mov.u32 %0, %%clusterid.x;" : "=r"(h));
    const bool isv = (j == 2);
    const uint32_t peerA = mapa(sb, isv ? 0 : (j ^ 1)), peerB = mapa(sb, isv ? 1 : 2);
    if (tid == 256) {
        for (int c = 0; c < 3; c++) { mbar_init(sb + B_W + 8 * c, 1); mbar_init(sb + B_M + 8 * c, 4); }
        mbar_init(sb + B_WO, 1); mbar_init(sb + B_T, 1);
        mbar_init(sb + B_X, 1); mbar_init(sb + B_X + 8, 1);
        mbar_init(sb + B_S, isv ? 8 : 5);
        mbar_init(sb + B_VX, 1); mbar_init(sb + B_VX + 8, 1);
        mbar_init(sb + B_SX, 1); mbar_init(sb + B_SX + 8, 1);
        asm volatile("fence.mbarrier_init.release.cluster;" ::: "memory");
        const CUtensorMap* m0 = isv ? &tmWv : &tmWq;
        const CUtensorMap* m1 = isv ? &tmWv : &tmWk;
        const int c0 = h * 128 + (isv ? 0 : 64 * j), c1 = h * 128 + (isv ? 64 : 64 * j);
        mbar_expect(sb + B_X, XB_BYTES);
        tma3d(sb + S_XB, &tmX, 0, 0, 0, sb + B_X);
#pragma unroll
        for (int c = 0; c < 3; c++) {
            mbar_expect(sb + B_W + 8 * c, 49152);
            tma2d(sb + s_w(c), m0, c0, c * 192, sb + B_W + 8 * c);
            tma2d(sb + s_w(c) + 24576, m1, c1, c * 192, sb + B_W + 8 * c);
        }
        mbar_expect(sb + B_X + 8, XB_BYTES);
        tma3d(sb + S_XB + XB_BYTES, &tmX, 0, 32, 0, sb + B_X + 8);
    }
    __syncthreads();
    if (wg == 2) {
        asm volatile("setmaxnreg.dec.sync.aligned.u32 %0;" ::"n"(REG_AUX));
        if (!isv) chain_aux<false>(sb, L16, wq, j, h, peerA, peerB, &tmWo, &tmX, mem0);
        else chain_aux<true>(sb, L16, wq, j, h, peerA, peerB, &tmWo, &tmX, mem0);
        __syncwarp();
        cluster_arrive(); cluster_wait();
        TSTAMP(65, 0);
    } else if (wg == 0) {
        asm volatile("setmaxnreg.inc.sync.aligned.u32 %0;" ::"n"(REG_MAIN0));
        if (!isv) chain_main<0>(sb, L16, wq, j, h, peerA, peerB);
        else chain_main<2>(sb, L16, wq, j, h, peerA, peerB);
        cluster_arrive(); cluster_wait();
    } else {
        asm volatile("setmaxnreg.inc.sync.aligned.u32 %0;" ::"n"(REG_MAIN1));
        if (!isv) chain_main<1>(sb, L16, wq, j, h, peerA, peerB);
        else chain_main<3>(sb, L16, wq, j, h, peerA, peerB);
        cluster_arrive(); cluster_wait();
    }
}

constexpr int NHELP = 36;
constexpr uint32_t H_U = 0;
constexpr uint32_t UT_PITCH = 4368;
constexpr uint32_t H_UT = 65536;
constexpr uint32_t KW_BYTES = 8320;
constexpr uint32_t H_KW = 135424;
constexpr uint32_t H_PAR = 201984;
constexpr uint32_t H_KD = 218368;
constexpr uint32_t H_STAGE = 0;
constexpr uint32_t H_RED = 196608;
constexpr uint32_t H_FIN = 212992;
constexpr uint32_t H_BAR = 229376;
constexpr uint32_t B_SMEM = H_BAR + 256;
constexpr uint32_t HB_U = H_BAR, HB_WO = H_BAR + 8, HB_FULL = H_BAR + 16, HB_EMPTY = H_BAR + 64, HB_RFULL = H_BAR + 112, HB_REMPTY = H_BAR + 128, HB_FIN = H_BAR + 144;
__device__ __align__(1024) uint4 g_part[4 * 9 * 4 * 4 * 128];

__device__ __forceinline__ float2 cmul(float2 a, float2 b) { return make_float2(fmaf(a.x, b.x, -a.y * b.y), fmaf(a.x, b.y, a.y * b.x)); }
__device__ __forceinline__ float2 csqr(float2 a) { return make_float2(fmaf(a.x, a.x, -a.y * a.y), (a.x + a.x) * a.y); }
__device__ __forceinline__ float2 cexp(float zr, float zi, float p) {
    const float m = ex2(zr * p);
    const float r = zi * p;
    const float a = (r - rintf(r)) * 6.283185307179586f;
    return make_float2(m * __cosf(a), m * __sinf(a));
}
__device__ __forceinline__ uint32_t pack_f16(float lo, float hi) { uint32_t r; asm("cvt.rn.f16x2.f32 %0, %1, %2;" : "=r"(r) : "f"(hi), "f"(lo)); return r; }
__device__ __forceinline__ void mma16h(float* d, const uint32_t* a, uint32_t b0, uint32_t b1) {
    asm volatile("mma.sync.aligned.m16n8k16.row.col.f32.f16.f16.f32 {%0,%1,%2,%3},{%4,%5,%6,%7},{%8,%9},{%0,%1,%2,%3};"
                 : "+f"(d[0]), "+f"(d[1]), "+f"(d[2]), "+f"(d[3]) : "r"(a[0]), "r"(a[1]), "r"(a[2]), "r"(a[3]), "r"(b0), "r"(b1));
}
__device__ __forceinline__ float bf_round(float x) { return __bfloat162float(__float2bfloat16_rn(x)); }
__device__ __forceinline__ uint32_t lds32(uint32_t a) { uint32_t v; asm volatile("ld.shared.b32 %0,[%1];" : "=r"(v) : "r"(a) : "memory"); return v; }
__device__ __forceinline__ uint32_t lds16(uint32_t a) { uint16_t v; asm volatile("ld.shared.u16 %0,[%1];" : "=h"(v) : "r"(a) : "memory"); return v; }
__device__ __forceinline__ void stsm4(uint32_t a, uint32_t r0, uint32_t r1, uint32_t r2, uint32_t r3) { asm volatile("stmatrix.sync.aligned.m8n8.x4.shared.b16 [%0],{%1,%2,%3,%4};" ::"r"(a), "r"(r0), "r"(r1), "r"(r2), "r"(r3) : "memory"); }

__device__ __forceinline__ void s4d_kernel(uint32_t par, uint32_t kd, uint32_t kw, int d, int lane, const bf16* __restrict__ logA, const bf16* __restrict__ Aim,
                                           const bf16* __restrict__ Cre, const bf16* __restrict__ Cim, const bf16* __restrict__ logdt) {
    const float dt = bf_round(expf(__bfloat162float(logdt[d])));
    float4 q[4];
    float cmax = 0.f, last = 0.f;
#pragma unroll
    for (int i = 0; i < 4; i++) {
        const int n = d * NST + i * 32 + lane;
        q[i].x = -bf_round(expf(__bfloat162float(logA[n]))) * dt * 1.4426950408889634f;
        q[i].y = __bfloat162float(Aim[n]) * dt * 0.15915494309189535f;
        q[i].z = 2.f * (__bfloat162float(Cre[n]) * dt);
        q[i].w = 2.f * (__bfloat162float(Cim[n]) * dt);
        cmax = fmaxf(cmax, fmaxf(fabsf(q[i].z), fabsf(q[i].w)));
        const float2 e = cexp(q[i].x, q[i].y, 2048.f);
        last += q[i].z * e.x - q[i].w * e.y;
    }
#pragma unroll
    for (int o = 16; o; o >>= 1) { cmax = fmaxf(cmax, __shfl_xor_sync(0xffffffffu, cmax, o)); last += __shfl_xor_sync(0xffffffffu, last, o); }
    const float cs = __uint_as_float(max(__float_as_uint(cmax) & 0x7F800000u, 0x00800000u));
    const float ci = 1.f / cs;
#pragma unroll
    for (int i = 0; i < 4; i++) sts128(par + (i * 32 + lane) * 16, __float_as_uint(q[i].x), __float_as_uint(q[i].y), __float_as_uint(q[i].z * ci), __float_as_uint(q[i].w * ci));
    __syncwarp();
    float acc[5][4];
#pragma unroll
    for (int i = 0; i < 5; i++) acc[i][0] = acc[i][1] = acc[i][2] = acc[i][3] = 0.f;
    const float g = (float)(lane >> 2);
#pragma unroll 1
    for (int ks = 0; ks < 16; ks++) {
        uint32_t A[5][4], B[4][2];
#pragma unroll
        for (int hf = 0; hf < 2; hf++) {
            uint32_t r[4];
            lds128(r, par + (ks * 8 + hf * 4 + (lane & 3)) * 16);
            const float zr = __uint_as_float(r[0]), zi = __uint_as_float(r[1]);
            const float2 c = make_float2(__uint_as_float(r[2]), __uint_as_float(r[3]));
            float2 y = cexp(zr, zi, g), x0 = cexp(zr, zi, 8.f * g + 128.f), x1 = cexp(zr, zi, 8.f * g + 192.f);
            const float2 xl = cexp(zr, zi, 8.f * g + 64.f);
#pragma unroll
            for (int k = 0; k < 4; k++) {
                const float2 cy = cmul(c, y);
                B[k][hf] = pack_f16(cy.x, -cy.y);
                A[k + 1][2 * hf] = pack_f16(x0.x, x0.y);
                A[k + 1][2 * hf + 1] = pack_f16(x1.x, x1.y);
                if (k < 3) { y = csqr(y); x0 = csqr(x0); x1 = csqr(x1); }
            }
            A[0][2 * hf] = pack_f16(y.x, y.y);
            A[0][2 * hf + 1] = pack_f16(xl.x, xl.y);
        }
        mma16h(acc[0], A[0], B[0][0], B[0][1]);
#pragma unroll
        for (int k = 0; k < 4; k++) mma16h(acc[k + 1], A[k + 1], B[k][0], B[k][1]);
    }
#pragma unroll
    for (int i = 0; i < 5; i++) {
        sts32(kd + i * 256 + lane * 4, pack_bf16(acc[i][0] * cs, acc[i][1] * cs));
        sts32(kd + i * 256 + 128 + lane * 4, pack_bf16(acc[i][2] * cs, acc[i][3] * cs));
    }
    if (lane == 0) sts32(kd + 1280, pack_bf16(last, 0.f));
    if (lane < 16) sts32(kw + lane * 4, 0);
    __syncwarp();
    uint32_t carry = 0;
#pragma unroll 4
    for (int it = 0; it < 64; it++) {
        const int l = it * 32 + lane;
        const int jx = l < 128 ? l : (int)__bfloat16_as_ushort(__float2bfloat16_rn((float)l)) - (133 << 7);
        const uint32_t v = lds16(kd + jx * 2);
        uint32_t pv = __shfl_up_sync(0xffffffffu, v, 1);
        if (lane == 0) pv = carry;
        carry = __shfl_sync(0xffffffffu, v, 31);
        sts32(kw + 64 + l * 4, v | (pv << 16));
    }
    __syncwarp();
}

__device__ __forceinline__ void s4d_conv(uint32_t ut, uint32_t kw, int lane) {
    float acc[16][4];
#pragma unroll
    for (int i = 0; i < 16; i++) acc[i][0] = acc[i][1] = acc[i][2] = acc[i][3] = 0.f;
    const uint32_t ka = kw + 64 + ((lane >> 2) - 2 * (lane & 3)) * 4;
    const uint32_t ua = ut + 256 + lane * 8;
#pragma unroll 1
    for (int rho = 0; rho < 8; rho++) {
        uint32_t B[16][2];
#pragma unroll
        for (int q = 0; q < 16; q++) lds64(B[q], ua + q * 256 - rho * 32);
#pragma unroll
        for (int m = 0; m < 16; m++) {
            uint32_t A[4];
            const uint32_t x = ka + m * 512 + rho * 64;
            A[0] = lds32(x); A[1] = lds32(x + 32); A[2] = lds32(x - 32); A[3] = A[0];
#pragma unroll
            for (int i = m; i < 16; i++) mma16(acc[i], A, B[i - m][0], B[i - m][1]);
        }
    }
    __syncwarp();
    const uint32_t ya = ut + 256 + (lane & 7) * 32 + ((lane >> 3) & 1) * 16 + (lane >> 4) * 256;
#pragma unroll
    for (int i = 0; i < 16; i += 2)
        stsm4t(ya + i * 256, pack_bf16(acc[i][0], acc[i][1]), pack_bf16(acc[i][2], acc[i][3]),
               pack_bf16(acc[i + 1][0], acc[i + 1][1]), pack_bf16(acc[i + 1][2], acc[i + 1][3]));
}

__global__ void __launch_bounds__(384, 1)
helper_kernel(const __grid_constant__ CUtensorMap tmU, const __grid_constant__ CUtensorMap tmY, const __grid_constant__ CUtensorMap tmWo,
              const bf16* __restrict__ logA, const bf16* __restrict__ Aim, const bf16* __restrict__ Cre, const bf16* __restrict__ Cim,
              const bf16* __restrict__ logdt, const bf16* __restrict__ Dskip, bf16* __restrict__ out) {
    extern __shared__ __align__(1024) uint8_t smem[];
    const uint32_t sb = smem_u32(smem);
    const int tid = threadIdx.x, lane = tid & 31;
    const int w = __shfl_sync(0xffffffffu, tid >> 5, 0);
    const int d0 = blockIdx.x * 16;
    HSTAMP(0);
    if (tid == 0) {
        mbar_init(sb + HB_U, 1); mbar_init(sb + HB_WO, 1);
        for (int i = 0; i < 6; i++) { mbar_init(sb + HB_FULL + 8 * i, 1); mbar_init(sb + HB_EMPTY + 8 * i, 4); }
        for (int i = 0; i < 2; i++) { mbar_init(sb + HB_RFULL + 8 * i, 4); mbar_init(sb + HB_REMPTY + 8 * i, 4); mbar_init(sb + HB_FIN + 8 * i, 2); }
        fence_async_smem();
        mbar_expect(sb + HB_U, 65536);
        for (int i = 0; i < 8; i++) tma2d(sb + H_U + i * 8192, &tmU, d0, i * 256, sb + HB_U);
    }
    __syncthreads();
    const int m = lane >> 3, r = lane & 7;
    if (w < 8) {
        s4d_kernel(sb + H_PAR + w * 2048, sb + H_KD + w * 1296, sb + H_KW + w * KW_BYTES, d0 + w, lane, logA, Aim, Cre, Cim, logdt);
    } else {
        for (int i = tid - 256; i < 256; i += 128) sts128(sb + H_UT + (i >> 4) * UT_PITCH + (i & 15) * 16, 0, 0, 0, 0);
        mbar_wait(sb + HB_U, 0);
        const uint32_t src = sb + H_U + ((m & 1) * 8 + r) * 32 + (((m >> 1) ^ (r >> 2)) << 4);
        const uint32_t dst = sb + H_UT + 256 + (lane >> 2) * UT_PITCH + (lane & 3) * 8;
#pragma unroll 4
        for (int grp = w - 8; grp < 128; grp += 4) {
            uint32_t v[4];
            ldsm4t(v, src + grp * 512);
            sts64(dst + grp * 32, v[0], v[1]);
            sts64(dst + 8 * UT_PITCH + grp * 32, v[2], v[3]);
        }
    }
    __syncthreads();
    HSTAMP(1);
    if (w < 8) {
        s4d_conv(sb + H_UT + w * UT_PITCH, sb + H_KW + w * KW_BYTES, lane);
        s4d_kernel(sb + H_PAR + w * 2048, sb + H_KD + w * 1296, sb + H_KW + w * KW_BYTES, d0 + 8 + w, lane, logA, Aim, Cre, Cim, logdt);
        s4d_conv(sb + H_UT + (8 + w) * UT_PITCH, sb + H_KW + w * KW_BYTES, lane);
    }
    __syncthreads();
    HSTAMP(2);
    const int cc = blockIdx.x % 9, kq = blockIdx.x / 9;
    {
        const __nv_bfloat162 D0 = *reinterpret_cast<const __nv_bfloat162*>(Dskip + d0 + (lane & 3) * 2);
        const __nv_bfloat162 D1 = *reinterpret_cast<const __nv_bfloat162*>(Dskip + d0 + 8 + (lane & 3) * 2);
        const uint32_t ua = sb + H_U + ((m & 1) * 8 + r) * 32 + (((m >> 1) ^ (r >> 2)) << 4);
        const uint32_t ya = sb + H_UT + 256 + ((m >> 1) * 8 + r) * UT_PITCH + (m & 1) * 16;
        for (int grp = w; grp < 128; grp += 12) {
            uint32_t u[4], y[4];
            ldsm4(u, ua + grp * 512);
            ldsm4t(y, ya + grp * 32);
#pragma unroll
            for (int i = 0; i < 4; i++) {
                const __nv_bfloat162 o = __hadd2_rn(*reinterpret_cast<__nv_bfloat162*>(&y[i]), __hmul2_rn(*reinterpret_cast<__nv_bfloat162*>(&u[i]), i < 2 ? D0 : D1));
                y[i] = *reinterpret_cast<const uint32_t*>(&o);
            }
            stsm4(ua + grp * 512, y[0], y[1], y[2], y[3]);
        }
        fence_async_smem();
        __syncthreads();
        if (tid == 0) {
            for (int i = 0; i < 8; i++)
                asm volatile("cp.async.bulk.tensor.2d.global.shared::cta.bulk_group [%0, {%1,%2}], [%3];" ::"l"(&tmY), "r"(DM + d0), "r"(i * 256), "r"(sb + H_U + i * 8192) : "memory");
            bulk_commit();
            mbar_expect(sb + HB_WO, 131072);
            for (int i = 0; i < 8; i++) tma2d(sb + 65536 + i * 16384, &tmWo, cc * 64, (kq * 8 + i) * 128, sb + HB_WO);
            asm volatile("cp.async.bulk.wait_group.read 0;" ::: "memory");
        }
    }
    if (w < 8) {
        const int wg = w >> 2;
        uint32_t wo[32][4];
        mbar_wait(sb + HB_WO, 0);
        const uint32_t a = sb + 65536 + wg * 65536 + ((m >> 1) * 8 + r) * 128 + (((2 * (w & 3) + (m & 1)) ^ r) << 4);
#pragma unroll
        for (int i = 0; i < 32; i++) ldsm4t(wo[i], a + i * 2048);
        __syncthreads();
        HSTAMP(3);
        const int t = tid & 127;
        int st = 0, ph = 0;
#pragma unroll 1
        for (int s = 0; s < NSEG; s++) {
            mbar_wait_long(sb + HB_FULL + (st * 2 + wg) * 8, ph);
            const uint32_t desc = desc_lo(sb + H_STAGE + st * 65536 + wg * 32768);
            float d[16];
            wg_fence();
#pragma unroll
            for (int i = 0; i < 32; i++) {
                const uint32_t db = desc + (((i >> 2) * 4096 + (i & 3) * 32) >> 4);
                if (i == 0) wg_rs_n32<0>(d, wo[i], db); else wg_rs_n32<1>(d, wo[i], db);
            }
            wg_commit();
            wg_wait<0>();
            mbar_arrive_if0(sb + HB_EMPTY + (st * 2 + wg) * 8, lane);
            if (++st == 3) { st = 0; ph ^= 1; }
            const uint32_t ra = sb + H_RED + (s & 1) * 8192 + t * 16;
            if (wg == 0) {
                if (s >= 2) mbar_wait_long(sb + HB_REMPTY + (s & 1) * 8, ((s - 2) >> 1) & 1);
#pragma unroll
                for (int i = 0; i < 4; i++) sts128(ra + i * 2048, __float_as_uint(d[4 * i]), __float_as_uint(d[4 * i + 1]), __float_as_uint(d[4 * i + 2]), __float_as_uint(d[4 * i + 3]));
                __syncwarp();
                mbar_arrive_if0(sb + HB_RFULL + (s & 1) * 8, lane);
            } else {
                mbar_wait_long(sb + HB_RFULL + (s & 1) * 8, (s >> 1) & 1);
                if (s >= 2) mbar_wait_long(sb + HB_FIN + (s & 1) * 8, ((s - 2) >> 1) & 1);
                uint4* dst = g_part + (((s & 3) * 9 + cc) * 16 + kq) * 128 + t;
#pragma unroll
                for (int i = 0; i < 4; i++) {
                    uint32_t p[4];
                    lds128(p, ra + i * 2048);
#pragma unroll
                    for (int k = 0; k < 4; k++) p[k] = ((__float_as_uint(__uint_as_float(p[k]) + d[4 * i + k]) + 64) & ~127u) | (s + 1);
                    asm volatile("st.relaxed.gpu.global.v4.u32 [%0], {%1,%2,%3,%4};" ::"l"(dst + i * 512), "r"(p[0]), "r"(p[1]), "r"(p[2]), "r"(p[3]) : "memory");
                }
                __syncwarp();
                mbar_arrive_if0(sb + HB_REMPTY + (s & 1) * 8, lane);
            }
        }
    } else {
        __syncthreads();
        if (w == 8) {
            if (lane == 0) {
                int st = 0, ph = 1;
                for (int s = 0; s < NSEG; s++) {
                    unsigned c = 0;
                    while (ld_acquire(&g_flag[s * 4 + kq]) < 8 && ++c < LONG_LIM) __nanosleep(FLAG_NS);
                    asm volatile("fence.proxy.async;" ::: "memory");
                    for (int g = 0; g < 2; g++) {
                        const uint32_t bar = sb + HB_FULL + (st * 2 + g) * 8;
                        mbar_wait_long(sb + HB_EMPTY + (st * 2 + g) * 8, ph);
                        mbar_expect(bar, 32768);
                        asm volatile("cp.async.bulk.shared::cluster.global.mbarrier::complete_tx::bytes [%0], [%1], %2, [%3];"
                                     ::"r"(sb + H_STAGE + st * 65536 + g * 32768), "l"(g_ox + (s * NH + kq * 8 + g * 4) * 512), "r"(32768), "r"(bar) : "memory");
                    }
                    if (++st == 3) { st = 0; ph ^= 1; }
                }
            }
        } else if (w < 11) {
            const int f = w - 9;
            const uint32_t fa = sb + H_FIN + f * 512;
            for (int s = 0; s < NSEG; s++) {
                mbar_wait_long(sb + HB_REMPTY + (s & 1) * 8, (s >> 1) & 1);
                const uint4* src = g_part + (((s & 3) * 9 + cc) * 16 + kq * 4) * 128 + f * 64 + lane;
                uint4 v[8];
                unsigned c = 0;
                while (true) {
                    uint32_t bad = 0;
#pragma unroll
                    for (int i = 0; i < 8; i++) v[i] = ld_poll(src + (i >> 1) * 128 + (i & 1) * 32);
#pragma unroll
                    for (int i = 0; i < 8; i++) bad |= (v[i].x ^ (s + 1)) | (v[i].y ^ (s + 1)) | (v[i].z ^ (s + 1)) | (v[i].w ^ (s + 1));
                    if (!__any_sync(0xffffffffu, (bad & 127) != 0) || ++c >= LONG_LIM) break;
                    __nanosleep(FLAG_NS);
                }
                mbar_arrive_if0(sb + HB_FIN + (s & 1) * 8, lane);
                uint32_t pk[4];
#pragma unroll
                for (int u = 0; u < 2; u++) {
                    float o[4] = {0.f, 0.f, 0.f, 0.f};
#pragma unroll
                    for (int k = 0; k < 4; k++) {
                        o[0] += __uint_as_float(v[2 * k + u].x & ~127u); o[1] += __uint_as_float(v[2 * k + u].y & ~127u);
                        o[2] += __uint_as_float(v[2 * k + u].z & ~127u); o[3] += __uint_as_float(v[2 * k + u].w & ~127u);
                    }
                    pk[2 * u] = pack_bf16(o[0], o[1]); pk[2 * u + 1] = pack_bf16(o[2], o[3]);
                }
                stsm4t(fa + r * 64 + ((m ^ (r >> 1)) << 4), pk[0], pk[1], pk[2], pk[3]);
                __syncwarp();
                uint32_t o4[4];
                lds128(o4, fa + (lane >> 2) * 64 + (((lane & 3) ^ (lane >> 3)) << 4));
                *reinterpret_cast<uint4*>(out + (s * SEG + kq * 8 + (lane >> 2)) * OUTW + cc * 64 + f * 32 + (lane & 3) * 8) = make_uint4(o4[0], o4[1], o4[2], o4[3]);
                __syncwarp();
                HSTAMP2(s);
            }
        }
    }
    if (tid == 0) bulk_wait0();
    asm volatile("griddepcontrol.wait;" ::: "memory");
}

typedef CUresult (*EncodeFn)(CUtensorMap*, CUtensorMapDataType, cuuint32_t, void*, const cuuint64_t*, const cuuint64_t*, const cuuint32_t*,
                             const cuuint32_t*, CUtensorMapInterleave, CUtensorMapSwizzle, CUtensorMapL2promotion, CUtensorMapFloatOOBfill);

void make_map(EncodeFn fn, CUtensorMap* m, const void* p, int rank, const cuuint64_t* dims, const cuuint64_t* strides, const cuuint32_t* box,
              CUtensorMapSwizzle sw = CU_TENSOR_MAP_SWIZZLE_128B, CUtensorMapL2promotion pr = CU_TENSOR_MAP_L2_PROMOTION_L2_128B) {
    const cuuint32_t es[3] = {1, 1, 1};
    fn(m, CU_TENSOR_MAP_DATA_TYPE_BFLOAT16, rank, const_cast<void*>(p), dims, strides, box, es, CU_TENSOR_MAP_INTERLEAVE_NONE,
       sw, pr, CU_TENSOR_MAP_FLOAT_OOB_FILL_NONE);
}

}

extern "C" void kernel_launch(void* const* d_in, const int* in_sizes, int n_in, void* d_out, int out_size) {
    const bf16* x = (const bf16*)d_in[0];
    const bf16* mem0 = (const bf16*)d_in[1];
    const bf16* Wo = (const bf16*)d_in[5];
    bf16* out = (bf16*)d_out;

    static EncodeFn enc = nullptr;
    if (!enc) {
        void* fn = nullptr;
        cudaDriverEntryPointQueryResult st;
        cudaGetDriverEntryPoint("cuTensorMapEncodeTiled", &fn, cudaEnableDefault, &st);
        enc = (EncodeFn)fn;
        cudaFuncSetAttribute(chain_kernel, cudaFuncAttributeMaxDynamicSharedMemorySize, A_SMEM);
        cudaFuncSetAttribute(helper_kernel, cudaFuncAttributeMaxDynamicSharedMemorySize, B_SMEM);
    }
    CUtensorMap tmW[3], tmWo, tmX;
    {
        const cuuint64_t dims[2] = {4096, 576}, str[1] = {8192};
        const cuuint32_t box[2] = {64, 192};
        for (int i = 0; i < 3; i++) make_map(enc, &tmW[i], d_in[2 + i], 2, dims, str, box);
    }
    {
        const cuuint64_t dims[2] = {576, 4096}, str[1] = {1152};
        const cuuint32_t box[2] = {64, 128};
        make_map(enc, &tmWo, Wo, 2, dims, str, box);
    }
    {
        const cuuint64_t dims[3] = {64, 2048, 9}, str[2] = {1152, 128};
        const cuuint32_t box[3] = {64, 32, 9};
        make_map(enc, &tmX, x, 3, dims, str, box);
    }
    CUtensorMap tmU, tmY;
    {
        const cuuint64_t dimsU[2] = {576, 2048}, strU[1] = {1152}, dimsY[2] = {1152, 2048}, strY[1] = {2304};
        const cuuint32_t box[2] = {16, 256};
        make_map(enc, &tmU, d_in[7], 2, dimsU, strU, box, CU_TENSOR_MAP_SWIZZLE_32B);
        make_map(enc, &tmY, out, 2, dimsY, strY, box, CU_TENSOR_MAP_SWIZZLE_32B, CU_TENSOR_MAP_L2_PROMOTION_NONE);
    }
    cudaStream_t st = cudaStreamPerThread;
    {
        cudaLaunchConfig_t cfg = {};
        cfg.gridDim = dim3(96); cfg.blockDim = dim3(384); cfg.dynamicSmemBytes = A_SMEM; cfg.stream = st;
        cudaLaunchAttribute at[1];
        at[0].id = cudaLaunchAttributeClusterDimension;
        at[0].val.clusterDim.x = 3; at[0].val.clusterDim.y = 1; at[0].val.clusterDim.z = 1;
        cfg.attrs = at; cfg.numAttrs = 1;
        cudaLaunchKernelEx(&cfg, chain_kernel, tmW[0], tmW[1], tmW[2], tmWo, tmX, mem0);
    }
    {
        cudaLaunchConfig_t cfg = {};
        cfg.gridDim = dim3(NHELP); cfg.blockDim = dim3(384); cfg.dynamicSmemBytes = B_SMEM; cfg.stream = st;
        cudaLaunchAttribute at[1];
        at[0].id = cudaLaunchAttributeProgrammaticStreamSerialization;
        at[0].val.programmaticStreamSerializationAllowed = 1;
        cfg.attrs = at; cfg.numAttrs = 1;
        cudaLaunchKernelEx(&cfg, helper_kernel, tmU, tmY, tmWo, (const bf16*)d_in[8], (const bf16*)d_in[9], (const bf16*)d_in[10],
                           (const bf16*)d_in[11], (const bf16*)d_in[12], (const bf16*)d_in[13], out);
    }
}
```

```cpp
#include <cuda_runtime.h>
#include <cuda_bf16.h>
#include <cuda_fp16.h>
#include <cuda.h>
#include <stdint.h>

typedef __nv_bfloat16 bf16;

namespace {

constexpr int DM = 576, NH = 32, DH = 128, SEG = 32, NSEG = 64, SEQ = 2048, NST = 128;
constexpr int OUTW = 2 * DM;
constexpr unsigned SPIN_LIM = 1u << 15;

constexpr int SLOT_BYTES = 768 * 32;
__device__ __align__(1024) uint4 g_acc[NSEG * SLOT_BYTES / 16];
__device__ __align__(1024) uint4 g_ox[NSEG * NH * 512];
__device__ __align__(1024) uint4 g_vx[NH * 2 * 512];
__device__ unsigned g_flag[NSEG * 4];
__device__ unsigned g_zero_cnt;

__device__ __forceinline__ uint32_t smem_u32(const void* p) { return (uint32_t)__cvta_generic_to_shared(p); }
__device__ __forceinline__ unsigned clk() { unsigned c; asm volatile("mov.u32 %0, %%clock;" : "=r"(c)::"memory"); return c; }
__device__ __forceinline__ unsigned gtime() { unsigned t; asm volatile("mov.u32 %0, %%globaltimer_lo;" : "=r"(t)::"memory"); return t; }
__device__ __forceinline__ uint32_t mapa(uint32_t a, uint32_t r) { uint32_t o; asm("mapa.shared::cluster.u32 %0, %1, %2;" : "=r"(o) : "r"(a), "r"(r)); return o; }
__device__ __forceinline__ void mbar_init(uint32_t b, uint32_t n) { asm volatile("mbarrier.init.shared::cta.b64 [%0], %1;" ::"r"(b), "r"(n) : "memory"); }
__device__ __forceinline__ void mbar_arrive(uint32_t b) { asm volatile("mbarrier.arrive.shared::cta.b64 _, [%0];" ::"r"(b) : "memory"); }
__device__ __forceinline__ void mbar_expect(uint32_t b, uint32_t tx) { asm volatile("mbarrier.arrive.expect_tx.shared::cta.b64 _, [%0], %1;" ::"r"(b), "r"(tx) : "memory"); }
__device__ __forceinline__ bool mbar_try(uint32_t b, uint32_t par) {
    uint32_t ok;
    asm volatile("{.reg .pred p; mbarrier.try_wait.parity.shared::cta.b64 p, [%1], %2; selp.u32 %0, 1, 0, p;}" : "=r"(ok) : "r"(b), "r"(par) : "memory");
    return ok;
}
__device__ __forceinline__ bool mbar_test(uint32_t b, uint32_t par) {
    uint32_t ok;
    asm volatile("{.reg .pred p; mbarrier.test_wait.parity.shared::cta.b64 p, [%1], %2; selp.u32 %0, 1, 0, p;}" : "=r"(ok) : "r"(b), "r"(par) : "memory");
    return ok;
}
__device__ __forceinline__ void mbar_wait(uint32_t b, uint32_t par) {
    asm volatile("{.reg .pred p, q; .reg .u32 c; mov.u32 c, 0;\n"
                 "W: mbarrier.try_wait.parity.shared::cta.b64 p, [%0], %1;\n"
                 "@p bra D;\n add.u32 c, c, 1; setp.lt.u32 q, c, %2;\n @q bra W;\n D:\n}" ::"r"(b), "r"(par), "n"(SPIN_LIM) : "memory");
}
constexpr unsigned LONG_LIM = 1u << 17;
__device__ __forceinline__ void mbar_wait_long(uint32_t b, uint32_t par) {
    asm volatile("{.reg .pred p, q; .reg .u32 c; mov.u32 c, 0;\n"
                 "W: mbarrier.try_wait.parity.shared::cta.b64 p, [%0], %1;\n"
                 "@p bra D;\n add.u32 c, c, 1; setp.lt.u32 q, c, %2;\n @q bra W;\n D:\n}" ::"r"(b), "r"(par), "n"(LONG_LIM) : "memory");
}
__device__ __forceinline__ void cluster_sync() { asm volatile("barrier.cluster.arrive.aligned; barrier.cluster.wait.aligned;" ::: "memory"); }
__device__ __forceinline__ void fence_async_smem() { asm volatile("fence.proxy.async.shared::cta;" ::: "memory"); }
__device__ __forceinline__ void ldsm4(uint32_t* r, uint32_t a) { asm volatile("ldmatrix.sync.aligned.m8n8.x4.shared.b16 {%0,%1,%2,%3},[%4];" : "=r"(r[0]), "=r"(r[1]), "=r"(r[2]), "=r"(r[3]) : "r"(a) : "memory"); }
__device__ __forceinline__ void ldsm4t(uint32_t* r, uint32_t a) { asm volatile("ldmatrix.sync.aligned.m8n8.x4.trans.shared.b16 {%0,%1,%2,%3},[%4];" : "=r"(r[0]), "=r"(r[1]), "=r"(r[2]), "=r"(r[3]) : "r"(a) : "memory"); }
__device__ __forceinline__ void stsm1(uint32_t a, uint32_t r0) { asm volatile("stmatrix.sync.aligned.m8n8.x1.shared.b16 [%0],{%1};" ::"r"(a), "r"(r0) : "memory"); }
__device__ __forceinline__ void stsm2t(uint32_t a, uint32_t r0, uint32_t r1) { asm volatile("stmatrix.sync.aligned.m8n8.x2.trans.shared.b16 [%0],{%1,%2};" ::"r"(a), "r"(r0), "r"(r1) : "memory"); }
__device__ __forceinline__ void stsm4t(uint32_t a, uint32_t r0, uint32_t r1, uint32_t r2, uint32_t r3) { asm volatile("stmatrix.sync.aligned.m8n8.x4.trans.shared.b16 [%0],{%1,%2,%3,%4};" ::"r"(a), "r"(r0), "r"(r1), "r"(r2), "r"(r3) : "memory"); }
__device__ __forceinline__ void sts32(uint32_t a, uint32_t v) { asm volatile("st.shared.b32 [%0], %1;" ::"r"(a), "r"(v) : "memory"); }
__device__ __forceinline__ void sts64(uint32_t a, uint32_t x, uint32_t y) { asm volatile("st.shared.v2.b32 [%0], {%1,%2};" ::"r"(a), "r"(x), "r"(y) : "memory"); }
__device__ __forceinline__ void sts128(uint32_t a, uint32_t x, uint32_t y, uint32_t z, uint32_t w) { asm volatile("st.shared.v4.b32 [%0], {%1,%2,%3,%4};" ::"r"(a), "r"(x), "r"(y), "r"(z), "r"(w) : "memory"); }
__device__ __forceinline__ void lds64(uint32_t* r, uint32_t a) { asm volatile("ld.shared.v2.b32 {%0,%1},[%2];" : "=r"(r[0]), "=r"(r[1]) : "r"(a) : "memory"); }
__device__ __forceinline__ float2 lds64f(uint32_t a) { float2 v; asm volatile("ld.shared.v2.f32 {%0,%1},[%2];" : "=f"(v.x), "=f"(v.y) : "r"(a) : "memory"); return v; }
__device__ __forceinline__ void lds128(uint32_t* r, uint32_t a) { asm volatile("ld.shared.v4.b32 {%0,%1,%2,%3},[%4];" : "=r"(r[0]), "=r"(r[1]), "=r"(r[2]), "=r"(r[3]) : "r"(a) : "memory"); }
__device__ __forceinline__ void st_async64(uint32_t a, uint32_t x, uint32_t y, uint32_t bar) {
    asm volatile("st.async.weak.shared::cluster.mbarrier::complete_tx::bytes.v2.b32 [%0], {%1,%2}, [%3];" ::"r"(a), "r"(x), "r"(y), "r"(bar) : "memory");
}
__device__ __forceinline__ void st_async32(uint32_t a, uint32_t x, uint32_t bar) {
    asm volatile("st.async.weak.shared::cluster.mbarrier::complete_tx::bytes.b32 [%0], %1, [%2];" ::"r"(a), "r"(x), "r"(bar) : "memory");
}
__device__ __forceinline__ void ldsm2(uint32_t* r, uint32_t a) { asm volatile("ldmatrix.sync.aligned.m8n8.x2.shared.b16 {%0,%1},[%2];" : "=r"(r[0]), "=r"(r[1]) : "r"(a) : "memory"); }
__device__ __forceinline__ uint32_t pack_f16_sat(float lo, float hi) { uint32_t r; asm("cvt.rn.satfinite.f16x2.f32 %0, %1, %2;" : "=r"(r) : "f"(hi), "f"(lo)); return r; }
__device__ __forceinline__ __half2 as_h2(uint32_t x) { return *reinterpret_cast<__half2*>(&x); }
__device__ __forceinline__ uint32_t as_u32(__half2 x) { return *reinterpret_cast<uint32_t*>(&x); }
__device__ __forceinline__ uint32_t pack_bf16(float lo, float hi) { uint32_t r; asm("cvt.rn.bf16x2.f32 %0, %1, %2;" : "=r"(r) : "f"(hi), "f"(lo)); return r; }
__device__ __forceinline__ float ex2(float x) { float r; asm("ex2.approx.ftz.f32 %0, %1;" : "=f"(r) : "f"(x)); return r; }
__device__ __forceinline__ float rcp(float x) { float r; asm("rcp.approx.ftz.f32 %0, %1;" : "=f"(r) : "f"(x)); return r; }
__device__ __forceinline__ void mma16(float* d, const uint32_t* a, uint32_t b0, uint32_t b1) {
    asm volatile("mma.sync.aligned.m16n8k16.row.col.f32.bf16.bf16.f32 {%0,%1,%2,%3},{%4,%5,%6,%7},{%8,%9},{%0,%1,%2,%3};"
                 : "+f"(d[0]), "+f"(d[1]), "+f"(d[2]), "+f"(d[3]) : "r"(a[0]), "r"(a[1]), "r"(a[2]), "r"(a[3]), "r"(b0), "r"(b1));
}
__device__ __forceinline__ void mma16z(float* d, const uint32_t* a, uint32_t b0, uint32_t b1) {
    asm volatile("mma.sync.aligned.m16n8k16.row.col.f32.bf16.bf16.f32 {%0,%1,%2,%3},{%4,%5,%6,%7},{%8,%9},{%10,%10,%10,%10};"
                 : "=f"(d[0]), "=f"(d[1]), "=f"(d[2]), "=f"(d[3]) : "r"(a[0]), "r"(a[1]), "r"(a[2]), "r"(a[3]), "r"(b0), "r"(b1), "f"(0.f));
}
__device__ __forceinline__ void mma8(float* d, uint32_t a0, uint32_t a1, uint32_t b0) {
    asm volatile("mma.sync.aligned.m16n8k8.row.col.f32.bf16.bf16.f32 {%0,%1,%2,%3},{%4,%5},{%6},{%0,%1,%2,%3};"
                 : "+f"(d[0]), "+f"(d[1]), "+f"(d[2]), "+f"(d[3]) : "r"(a0), "r"(a1), "r"(b0));
}
template <int ACC>
__device__ __forceinline__ void mma_sp(float* d, const uint32_t* a, const uint32_t* b) {
    if (ACC)
        asm volatile("mma.sp::ordered_metadata.sync.aligned.m16n8k32.row.col.f32.bf16.bf16.f32 {%0,%1,%2,%3},{%4,%5,%6,%7},{%8,%9,%10,%11},{%0,%1,%2,%3},%12,0x0;"
                     : "+f"(d[0]), "+f"(d[1]), "+f"(d[2]), "+f"(d[3])
                     : "r"(a[0]), "r"(a[1]), "r"(a[2]), "r"(a[3]), "r"(b[0]), "r"(b[1]), "r"(b[2]), "r"(b[3]), "r"(0xEEEE4444u));
    else
        asm volatile("mma.sp::ordered_metadata.sync.aligned.m16n8k32.row.col.f32.bf16.bf16.f32 {%0,%1,%2,%3},{%4,%5,%6,%7},{%8,%9,%10,%11},{%13,%13,%13,%13},%12,0x0;"
                     : "=f"(d[0]), "=f"(d[1]), "=f"(d[2]), "=f"(d[3])
                     : "r"(a[0]), "r"(a[1]), "r"(a[2]), "r"(a[3]), "r"(b[0]), "r"(b[1]), "r"(b[2]), "r"(b[3]), "r"(0xEEEE4444u), "f"(0.f));
}
__device__ __forceinline__ void mbar_arrive_if0(uint32_t b, uint32_t z) { asm volatile("{.reg .pred p; setp.eq.u32 p, %1, 0; @p mbarrier.arrive.shared::cta.b64 _, [%0];}" ::"r"(b), "r"(z) : "memory"); }
__device__ __forceinline__ void mbar_expect_if0(uint32_t b, uint32_t tx, uint32_t z) { asm volatile("{.reg .pred p; setp.eq.u32 p, %2, 0; @p mbarrier.arrive.expect_tx.shared::cta.b64 _, [%0], %1;}" ::"r"(b), "r"(tx), "r"(z) : "memory"); }
__device__ __forceinline__ float lds32f(uint32_t a) { float v; asm volatile("ld.shared.f32 %0,[%1];" : "=f"(v) : "r"(a) : "memory"); return v; }
__device__ __forceinline__ void wg_fence() { asm volatile("wgmma.fence.sync.aligned;" ::: "memory"); }
__device__ __forceinline__ void wg_commit() { asm volatile("wgmma.commit_group.sync.aligned;" ::: "memory"); }
template <int N> __device__ __forceinline__ void wg_wait() { asm volatile("wgmma.wait_group.sync.aligned %0;" ::"n"(N) : "memory"); }
__device__ __forceinline__ void delay(unsigned n) { if (n) { const unsigned t0 = clk(); while (clk() - t0 < n) {} } }
template <int ACC, uint32_t DHI = 0x40000040u>
__device__ __forceinline__ void wg_rs_n32(float* d, const uint32_t* a, uint32_t dlo) {
    if (ACC)
        asm volatile("{.reg .b64 db; mov.b64 db, {%20, %21};\n"
                     "wgmma.mma_async.sync.aligned.m64n32k16.f32.bf16.bf16 {%0,%1,%2,%3,%4,%5,%6,%7,%8,%9,%10,%11,%12,%13,%14,%15},{%16,%17,%18,%19},db,1,1,1,0;}"
                     : "+f"(d[0]), "+f"(d[1]), "+f"(d[2]), "+f"(d[3]), "+f"(d[4]), "+f"(d[5]), "+f"(d[6]), "+f"(d[7]),
                       "+f"(d[8]), "+f"(d[9]), "+f"(d[10]), "+f"(d[11]), "+f"(d[12]), "+f"(d[13]), "+f"(d[14]), "+f"(d[15])
                     : "r"(a[0]), "r"(a[1]), "r"(a[2]), "r"(a[3]), "r"(dlo), "r"(DHI));
    else
        asm volatile("{.reg .b64 db; mov.b64 db, {%20, %21};\n"
                     "wgmma.mma_async.sync.aligned.m64n32k16.f32.bf16.bf16 {%0,%1,%2,%3,%4,%5,%6,%7,%8,%9,%10,%11,%12,%13,%14,%15},{%16,%17,%18,%19},db,0,1,1,0;}"
                     : "=f"(d[0]), "=f"(d[1]), "=f"(d[2]), "=f"(d[3]), "=f"(d[4]), "=f"(d[5]), "=f"(d[6]), "=f"(d[7]),
                       "=f"(d[8]), "=f"(d[9]), "=f"(d[10]), "=f"(d[11]), "=f"(d[12]), "=f"(d[13]), "=f"(d[14]), "=f"(d[15])
                     : "r"(a[0]), "r"(a[1]), "r"(a[2]), "r"(a[3]), "r"(dlo), "r"(DHI));
}
__device__ __forceinline__ uint32_t desc_lo(uint32_t addr) { return ((addr & 0x3FFFF) >> 4) | (1u << 16); }
__device__ __forceinline__ void tma2d(uint32_t dst, const CUtensorMap* m, int c0, int c1, uint32_t bar) {
    asm volatile("cp.async.bulk.tensor.2d.shared::cluster.global.mbarrier::complete_tx::bytes [%0], [%1, {%2,%3}], [%4];"
                 ::"r"(dst), "l"(m), "r"(c0), "r"(c1), "r"(bar) : "memory");
}
__device__ __forceinline__ void tma3d(uint32_t dst, const CUtensorMap* m, int c0, int c1, int c2, uint32_t bar) {
    asm volatile("cp.async.bulk.tensor.3d.shared::cluster.global.mbarrier::complete_tx::bytes [%0], [%1, {%2,%3,%4}], [%5];"
                 ::"r"(dst), "l"(m), "r"(c0), "r"(c1), "r"(c2), "r"(bar) : "memory");
}
__device__ __forceinline__ void tma3d_mc(uint32_t dst, const CUtensorMap* m, int c0, int c1, int c2, uint32_t bar, uint16_t mask) {
    asm volatile("cp.async.bulk.tensor.3d.shared::cluster.global.mbarrier::complete_tx::bytes.multicast::cluster [%0], [%1, {%2,%3,%4}], [%5], %6;"
                 ::"r"(dst), "l"(m), "r"(c0), "r"(c1), "r"(c2), "r"(bar), "h"(mask) : "memory");
}
__device__ __forceinline__ void bulk_g2s_mc(uint32_t dst, const void* src, uint32_t bytes, uint32_t bar, uint16_t mask) {
    asm volatile("cp.async.bulk.shared::cluster.global.mbarrier::complete_tx::bytes.multicast::cluster [%0], [%1], %2, [%3], %4;"
                 ::"r"(dst), "l"(src), "r"(bytes), "r"(bar), "h"(mask) : "memory");
}
__device__ __forceinline__ void tma2d_prefetch(const CUtensorMap* m, int c0, int c1) {
    asm volatile("cp.async.bulk.prefetch.tensor.2d.L2.global [%0, {%1,%2}];" ::"l"(m), "r"(c0), "r"(c1) : "memory");
}
__device__ __forceinline__ void bulk_s2c(uint32_t dst, uint32_t src, uint32_t bytes, uint32_t bar) {
    asm volatile("cp.async.bulk.shared::cluster.shared::cta.mbarrier::complete_tx::bytes [%0], [%1], %2, [%3];" ::"r"(dst), "r"(src), "r"(bytes), "r"(bar) : "memory");
}
__device__ __forceinline__ void bulk_s2g(void* dst, uint32_t src, uint32_t bytes) {
    asm volatile("cp.async.bulk.global.shared::cta.bulk_group [%0], [%1], %2;" ::"l"(dst), "r"(src), "r"(bytes) : "memory");
}
__device__ __forceinline__ void bulk_commit() { asm volatile("cp.async.bulk.commit_group;" ::: "memory"); }
__device__ __forceinline__ void bulk_wait0() { asm volatile("cp.async.bulk.wait_group 0;" ::: "memory"); }
__device__ __forceinline__ uint4 ld_poll(const void* p) {
    uint4 v;
    asm volatile("ld.relaxed.gpu.global.v4.u32 {%0,%1,%2,%3},[%4];" : "=r"(v.x), "=r"(v.y), "=r"(v.z), "=r"(v.w) : "l"(p) : "memory");
    return v;
}
__device__ __forceinline__ unsigned ld_acquire(const unsigned* p) { unsigned v; asm volatile("ld.acquire.gpu.global.u32 %0,[%1];" : "=r"(v) : "l"(p) : "memory"); return v; }
__device__ __forceinline__ void red_release(unsigned* p, unsigned v) { asm volatile("red.release.gpu.global.add.u32 [%0], %1;" ::"l"(p), "r"(v) : "memory"); }

__device__ __forceinline__ void publish(unsigned* p) {
    asm volatile("fence.proxy.async.global;" ::: "memory");
    asm volatile("red.relaxed.gpu.global.add.u32 [%0], 1;" ::"l"(p) : "memory");
}
template <int ID, int N> __device__ __forceinline__ void bar_sync() { asm volatile("bar.sync %0, %1;" ::"n"(ID), "n"(N) : "memory"); }
template <int ID, int N> __device__ __forceinline__ void bar_arrive() { asm volatile("bar.arrive %0, %1;" ::"n"(ID), "n"(N) : "memory"); }
__device__ __forceinline__ void cluster_arrive() { asm volatile("barrier.cluster.arrive.relaxed.aligned;" ::: "memory"); }
__device__ __forceinline__ void cluster_wait() { asm volatile("barrier.cluster.wait.aligned;" ::: "memory"); }

constexpr uint32_t XB_BYTES = 36864;
constexpr uint32_t S_XB = 0;
constexpr uint32_t S_QM = 73728;
constexpr uint32_t S_KM = 74752;
constexpr uint32_t S_OM = 75776;
constexpr uint32_t S_SP = 77824;
constexpr uint32_t S_SUM = 80384;
constexpr uint32_t S_TGT = 81408;
constexpr uint32_t S_VM = 147456;
constexpr uint32_t S_QX = 86016;
constexpr uint32_t S_PX = S_QX;
constexpr uint32_t S_KX = 94208;
constexpr uint32_t S_VX = 102400;
constexpr uint32_t S_SX = 135168;
constexpr uint32_t S_OX = 155648;
constexpr uint32_t S_MEM = 172032;
constexpr uint32_t S_WO = 181248;
constexpr uint32_t S_BAR = 230400;
constexpr uint32_t A_SMEM = S_BAR + 128;
__host__ __device__ constexpr uint32_t s_w(int c) { return c == 0 ? S_WO : 73728 + (c - 1) * 49152; }
constexpr uint32_t B_W = S_BAR, B_WO = S_BAR + 24, B_X = S_BAR + 32, B_S = S_BAR + 48, B_VX = S_BAR + 56, B_SX = S_BAR + 72, B_M = S_BAR + 88, B_T = S_BAR + 112;
constexpr int NB_QK = 1, NB_O = 2, NB_RED = 3, NB_P = 4, NB_AUX = 5, NB_PRO = 6, NB_X = 7, NB_GO = 8;

constexpr float SM_SCALE = 0.08838834764831845f * 1.4426950408889634f;
constexpr uint32_t ONES = 0x3F803F80u;
constexpr uint32_t FULL_COUNT = 0x4200u;
#define XLIM NSEG
#define XTMA_DELAY 0
#define SX_DELAY 0
#define TGT_NS 1120
#define LOOK_NS 100
#define RCP_AT 2
#define NCH 2
#define POLL_AT 1
#define OX_DELAY 0
#define XTMA_NS 50
#define REG_MAIN0 232
#define REG_MAIN1 232
#define REG_AUX 40

#define PV_MODE 1
#define OX_AT 1
#define FLAG_NS 40
#define OFF 0
static_assert(REG_MAIN0 + REG_MAIN1 + REG_AUX <= 504, "the three warpgroups share 3 x 168 registers");
#define HSTAMP(i) do {} while (0)
#define HSTAMP2(i) do {} while (0)
#define TSTAMP(i, e) do {} while (0)

__device__ __forceinline__ void load_scores(uint32_t a, __half2 (&hs)[5]) {
    uint32_t r[10];
    ldsm4(r, a);
    ldsm4(r + 4, a + 512);
    ldsm2(r + 8, a + 1024);
    const __half2 hf = as_h2(0x38003800u);
#pragma unroll
    for (int T = 0; T < 5; T++) hs[T] = __hfma2(as_h2(r[2 * T]), hf, __hmul2(as_h2(r[2 * T + 1]), hf));
}
__device__ __forceinline__ void softmax_exp(const __half2 (&hs)[5], float (&ev)[10]) {
    __half2 m = __hmax2(__hmax2(__hmax2(hs[0], hs[1]), __hmax2(hs[2], hs[3])), hs[4]);
    const uint32_t mu = as_u32(m);
    const uint32_t m1 = __shfl_xor_sync(0xffffffffu, mu, 1), m2 = __shfl_xor_sync(0xffffffffu, mu, 2), m3 = __shfl_xor_sync(0xffffffffu, mu, 3);
    m = __hmax2(__hmax2(m, as_h2(m1)), __hmax2(as_h2(m2), as_h2(m3)));
    const float mc = -fmaxf(__low2float(m), __high2float(m)) * (2.f * SM_SCALE);
#pragma unroll
    for (int T = 0; T < 5; T++) {
        ev[2 * T] = ex2(fmaf(__low2float(hs[T]), 2.f * SM_SCALE, mc));
        ev[2 * T + 1] = ex2(fmaf(__high2float(hs[T]), 2.f * SM_SCALE, mc));
    }
}

__device__ __forceinline__ void x_scores(uint32_t sb, int seg, int wq, uint32_t L16, float (&ev)[10]) {
    __half2 hs[5];
    load_scores(sb + S_SX + (seg & 1) * 5120 + wq * 1280 + L16, hs);
    const int dg = (int)(L16 >> 6) - (int)((L16 >> 3) & 6) + 8 * wq;
#pragma unroll
    for (int T = 0; T < 4; T++) {
        uint32_t u = as_u32(hs[T]);
        if (dg < 8 * T + 1) u = (u & 0xFFFFu) | 0xFC000000u;
        if (dg < 8 * T) u = 0xFC00FC00u;
        hs[T] = as_h2(u);
    }
    softmax_exp(hs, ev);
}
__device__ __forceinline__ void x_probs(uint32_t sb, int seg, int wq, uint32_t L16, const float (&ev)[10]) {
    float l = ((ev[0] + ev[1]) + (ev[2] + ev[3])) + ((ev[4] + ev[5]) + (ev[6] + ev[7])) + (ev[8] + ev[9]);
    const float l1 = __shfl_xor_sync(0xffffffffu, l, 1), l2 = __shfl_xor_sync(0xffffffffu, l, 2), l3 = __shfl_xor_sync(0xffffffffu, l, 3);
    const float r = rcp((l + l1) + (l2 + l3));
    const uint32_t a = sb + S_PX + (seg & 1) * 4096 + wq * 640 + (L16 >> 2);
#pragma unroll
    for (int i = 0; i < 5; i++) sts32(a + i * 128, pack_bf16(ev[2 * i] * r, ev[2 * i + 1] * r));
    fence_async_smem();
}
__device__ __forceinline__ void x_pv_load(uint32_t sb, int seg, int w, uint32_t L16, uint32_t (&a)[3][4]) {
    lds128(a[0], sb + S_VX + (seg & 3) * 8192 + w * 1024 + L16);
    lds128(a[1], sb + S_VX + (seg & 3) * 8192 + w * 1024 + 512 + L16);
    lds64(a[2], sb + S_VM + (seg & 3) * 2048 + w * 256 + (L16 >> 1));
    a[2][2] = 0; a[2][3] = 0;
}
__device__ __forceinline__ void x_pv_run(uint32_t sb, int seg, int w, uint32_t L16, const uint32_t (&a)[3][4]) {
    const uint32_t d = ((sb + S_PX + (seg & 1) * 4096) & 0x3FFFF) >> 4;
    float o[16];
    wg_fence();
    wg_rs_n32<0, 40>(o, a[0], d | (8u << 16));
    wg_rs_n32<1, 40>(o, a[1], (d + 16) | (8u << 16));
    wg_rs_n32<1, 40>(o, a[2], d + 32);
    wg_commit();
    wg_wait<0>();
    const uint32_t ox = sb + S_OX + (seg & 1) * 8192 + (w >> 2) * 4096 + (L16 & 0x100) * 4 + (L16 & 0x70) * 8 +
                        ((((w & 3) * 32) | ((L16 >> 3) & 0x10)) ^ (L16 & 0x70));
    stsm4t(ox, pack_bf16(o[0], o[1]), pack_bf16(o[2], o[3]), pack_bf16(o[4], o[5]), pack_bf16(o[6], o[7]));
    stsm4t(ox + 2048, pack_bf16(o[8], o[9]), pack_bf16(o[10], o[11]), pack_bf16(o[12], o[13]), pack_bf16(o[14], o[15]));
}
__device__ __forceinline__ void ox_publish(int seg, uint32_t h) { bulk_wait0(); publish(&g_flag[seg * 4 + (h >> 3)]); }
__device__ __forceinline__ void ox_store(uint32_t sb, int seg, uint32_t h) {
    fence_async_smem();
    bulk_s2g(g_ox + (seg * NH + h) * 512, sb + S_OX + (seg & 1) * 8192, 8192);
    bulk_commit();
}

__device__ __forceinline__ void x_epilogue(uint32_t sb, const float (&d)[16], int seg, bool isv, int w, uint32_t L16) {
    uint32_t pk[8];
#pragma unroll
    for (int i = 0; i < 8; i++) pk[i] = pack_bf16(d[2 * i], d[2 * i + 1]);
    if (!isv) {
        const uint32_t a = sb + S_QX + (w >> 2) * 8192 + (seg & 1) * 4096 + (w & 3) * 256 + (L16 & 0xF0) + (L16 & 0x100) * 4;
        stsm4t(a, pk[0], pk[1], pk[2], pk[3]);
        stsm4t(a + 2048, pk[4], pk[5], pk[6], pk[7]);
    } else {
        const uint32_t a = sb + S_VX + (seg & 3) * 8192 + w * 1024 + L16;
        sts128(a, pk[0], pk[1], pk[2], pk[3]);
        sts128(a + 512, pk[4], pk[5], pk[6], pk[7]);
    }
}

template <int K0, int K1>
__device__ __forceinline__ void x_project(float (&d)[16], const uint32_t (&wA)[36][4], uint32_t desc) {
#pragma unroll
    for (int i = K0; i < K1; i++) {
        const uint32_t db = desc + (((i >> 2) * 4096 + (i & 3) * 32) >> 4);
        if (i == 0) wg_rs_n32<0>(d, wA[i], db); else wg_rs_n32<1>(d, wA[i], db);
    }
}

__device__ __forceinline__ void mem_scores(uint32_t sb, uint32_t peerA, uint32_t peerB, uint32_t off, const uint32_t (&q0)[4], const uint32_t (&q1)[4],
                                           const uint32_t (&k0)[4], const uint32_t (&k1)[4]) {
    float e0[4], o0[4], e1[4], o1[4];
    mma16z(e0, q0, k0[0], k0[1]);
    mma16z(o0, q0, k0[2], k0[3]);
    mma16z(e1, q1, k1[0], k1[1]);
    mma16z(o1, q1, k1[2], k1[3]);
    const uint32_t sc = pack_f16_sat((e0[0] + o0[2]) + (e1[0] + o1[2]), (e0[1] + o0[3]) + (e1[1] + o1[3]));
    st_async32(peerB + off, sc, peerB + B_S);
    st_async32(peerA + off, sc, peerA + B_S);
    sts32(sb + off, sc);
    __syncwarp();
}

__device__ __forceinline__ unsigned post_time(int s, uint32_t L16) {
    delay(1);
    const unsigned t = gtime() | 1;
    if (L16 == 0) asm volatile("st.relaxed.gpu.global.u32 [%0], %1;" ::"l"(reinterpret_cast<unsigned*>(g_acc) + s * 96 + blockIdx.x), "r"(t) : "memory");
    return t;
}
__device__ __forceinline__ void plan_look(uint32_t sb, int s, uint32_t L16, unsigned t) {
    const char* p = reinterpret_cast<const char*>(g_acc) + s * 384 + (L16 < 384 ? L16 : 0);
    uint4 v;
    unsigned c = 0;
    do { v = ld_poll(p); } while (__any_sync(0xffffffffu, (v.x & v.y & v.z & v.w & 1) == 0) && ++c < SPIN_LIM);
    const int d = max(max((int)(v.x - t), (int)(v.y - t)), max((int)(v.z - t), (int)(v.w - t)));
    const unsigned tgt = t + min(__reduce_max_sync(0xffffffffu, d), 20000) + TGT_NS;
    if (L16 < 48) { const uint32_t r = mapa(sb, L16 >> 4); st_async32(r + S_TGT, tgt, r + B_T); }
}

template <int ROLE>
__device__ __forceinline__ void chain_main(const uint32_t sb, const uint32_t lane16, const int wq, const uint32_t j, const uint32_t h,
                                           const uint32_t peerA, const uint32_t peerB) {
    uint32_t L16 = lane16;
    constexpr bool isv = ROLE >= 2;
    constexpr int wg = ROLE & 1;
    const int w = wg * 4 + wq;
    const uint32_t xdesc = desc_lo(sb + S_XB);
    const uint32_t zero = h >> 20;
    uint32_t wA[36][4], woA[8][4], woB[4][4];
    float xd[16];
    {
        const int m = L16 >> 7, r = (L16 >> 4) & 7;
        const int blk = (ROLE == 1) ? ((wq & 2) * 2 + (wq & 1) + (m & 1) * 2) : (2 * wq + (m & 1));
        const uint32_t a = sb + wg * 24576 + ((m >> 1) * 8 + r) * 128 + ((blk ^ r) << 4);
        mbar_wait(sb + B_X, 0);
#pragma unroll
        for (int c = 0; c < 3; c++) {
            mbar_wait(sb + B_W + 8 * c, 0);
#pragma unroll
            for (int i = 0; i < 12; i++) ldsm4t(wA[12 * c + i], a + s_w(c) + i * 2048);
            if (c == 0) bar_arrive<NB_PRO, 384>();
            if (c == 2) { bar_sync<NB_O, 256>(); cluster_arrive(); }
            wg_fence();
            if (c == 0) x_project<0, 12>(xd, wA, xdesc);
            if (c == 1) x_project<12, 24>(xd, wA, xdesc);
            if (c == 2) x_project<24, 36>(xd, wA, xdesc);
            wg_commit();
            wg_wait<0>();
        }
        x_epilogue(sb, xd, 0, isv, w, L16);
        bar_arrive<NB_RED, 384>();
        mbar_wait(sb + B_WO, 0);
        const int ca = 3 * w + (m & 1), cb = 3 * w + 2;
        const uint32_t aA = sb + S_WO + (ca >> 3) * 16384 + ((m >> 1) * 8 + r) * 128 + (((ca & 7) ^ r) << 4);
        const int eB = ((m & 2) + ((r >> 1) & 1)) * 8 + 4 * (m & 1) + 2 * (r >> 2) + (r & 1);
        const uint32_t aB = sb + S_WO + (cb >> 3) * 16384 + eB * 128 + (((cb & 7) ^ (eB & 7)) << 4);
#pragma unroll
        for (int i = 0; i < 8; i++) ldsm4t(woA[i], aA + i * 2048);
#pragma unroll
        for (int i = 0; i < 4; i++) ldsm4t(woB[i], aB + i * 4096);
        mbar_wait(sb + B_X + 8, 0);
        cluster_wait();
        bar_sync<NB_O, 256>();
        wg_fence();
        x_project<0, 36>(xd, wA, xdesc + (XB_BYTES >> 4));
        wg_commit();
    }
    int s = 0;
#pragma unroll 1
    while (true) {
        const uint32_t par = s & 1;
        const uint32_t kx = sb + S_KX + par * 4096;
        asm volatile("" : "+r"(L16));
        wg_wait<0>();
        x_epilogue(sb, xd, s + 1, isv, w, L16);
        float c0[4], c1[4];
        uint32_t k0[4], k1[4], pva[3][4];
        {
            const uint32_t a = sb + S_MEM + L16;
            constexpr int CH = 18 / NCH;
            uint32_t b[3][4];
            bool ready = true;
            mbar_wait(sb + B_M, par);
            ldsm4(b[0], a);
            ldsm4(b[1], a + 512);
            bar_arrive<NB_GO, 288>();
#pragma unroll
            for (int i = 0; i < 18; i++) {
                if ((i + 4) % CH == 0 && i + 4 < 18) ready = mbar_test(sb + B_M + ((i + 4) / CH) * 8, par);
                if ((i + 2) % CH == 0 && i + 2 < 18) { if (__builtin_expect(!ready, 0)) mbar_wait(sb + B_M + ((i + 2) / CH) * 8, par); }
                if (i + 2 < 18) ldsm4(b[(i + 2) % 3], a + (i + 2) * 512);
                if (ROLE == 0 && i == 16) ldsm4(k0, kx + wq * 1024 + L16);
                if (ROLE == 0 && i == 17) ldsm4(k1, kx + wq * 1024 + 512 + L16);
                if (PV_MODE == 0 && !(OFF & 8) && isv && i == 17) x_pv_load(sb, s + 2, w, L16, pva);
                if (i == 0) { mma16z(c0, wA[0], b[0][0], b[0][1]); mma16z(c1, wA[1], b[0][2], b[0][3]); }
                else { mma16(c0, wA[2 * i], b[i % 3][0], b[i % 3][1]); mma16(c1, wA[2 * i + 1], b[i % 3][2], b[i % 3][3]); }
            }
        }
        const uint32_t p0 = pack_bf16(c0[0] + c1[0], c0[1] + c1[1]), p1 = pack_bf16(c0[2] + c1[2], c0[3] + c1[3]);
        if (!isv) {
            stsm2t(sb + S_QM + w * 256 + L16, p0, p1);
            bar_sync<NB_QK, 384>();
            if (ROLE == 0) {
                uint32_t q0[4], q1[4];
                ldsm4(q0, sb + S_QM + L16);
                ldsm4(q1, sb + S_QM + 512 + L16);
                mem_scores(sb, peerA, peerB, S_SP + j * 128 + wq * 256 + (L16 >> 2), q0, q1, k0, k1);
                mbar_arrive_if0(sb + B_S, L16);
            } else {
                if (s + 2 < XLIM) mbar_wait(sb + B_X + par * 8, ((s + 2) >> 1) & 1);
                if (wq != 0 && !(OFF & 16)) {
                    const int rt = (wq == 3) ? 0 : 1;
                    const uint32_t qa = sb + S_QX + par * 4096 + rt * 2048 + (L16 & 0x80) * 8 + (L16 & 0x170);
                    const uint32_t kb0 = (wq == 2 ? kx + 2048 : sb + S_KM) + L16;
                    const uint32_t kb1 = (wq == 2 ? kx + 3072 : kx) + L16;
                    const uint32_t kb2 = kx + 1024 + L16;
                    float a0[4], a1[4], a2[4];
#pragma unroll
                    for (int hf = 0; hf < 2; hf++) {
                        uint32_t qa0[4], qa1[4], b[4];
                        ldsm4(qa0, qa + hf * 512);
                        ldsm4(qa1, qa + hf * 512 + 128);
                        ldsm4(b, kb0 + hf * 512);
                        if (hf == 0) mma16z(a0, qa0, b[0], b[1]); else mma16(a0, qa0, b[0], b[1]);
                        mma16(a0, qa1, b[2], b[3]);
                        ldsm4(b, kb1 + hf * 512);
                        if (hf == 0) mma16z(a1, qa0, b[0], b[1]); else mma16(a1, qa0, b[0], b[1]);
                        mma16(a1, qa1, b[2], b[3]);
                        ldsm4(b, kb2 + hf * 512);
                        if (hf == 0) mma16z(a2, qa0, b[0], b[1]); else mma16(a2, qa0, b[0], b[1]);
                        mma16(a2, qa1, b[2], b[3]);
                    }
                    mbar_wait(sb + B_S, par);
                    delay(SX_DELAY);
                    const uint32_t dst = peerB + S_SX + par * 5120 + j * 128 + rt * 2560 + (L16 >> 2);
                    const uint32_t bar = peerB + B_SX + par * 8;
                    const uint32_t T0 = (wq == 2 ? 2 : 4) * 256, T1 = (wq == 2 ? 3 : 0) * 256;
                    st_async32(dst + T0, pack_f16_sat(a0[0], a0[1]), bar);
                    st_async32(dst + 1280 + T0, pack_f16_sat(a0[2], a0[3]), bar);
                    if (wq != 2) st_async32(dst + T1, pack_f16_sat(a1[0], a1[1]), bar);
                    st_async32(dst + 1280 + T1, pack_f16_sat(a1[2], a1[3]), bar);
                    if (wq == 1) st_async32(dst + 256, pack_f16_sat(a2[0], a2[1]), bar);
                    if (wq != 2) st_async32(dst + 1280 + 256, pack_f16_sat(a2[2], a2[3]), bar);
                }
            }
        } else {
            const uint32_t off = S_VM + (s & 3) * 2048 + w * 256 + (L16 >> 1);
            st_async64(peerA + off, p0, p1, peerA + B_S);
            st_async64(peerB + off, p0, p1, peerB + B_S);
            sts64(sb + off, p0, p1);
            __syncwarp();
            mbar_expect_if0(sb + B_S, 160, L16);
            if (PV_MODE == 1 || (PV_MODE == 2 && ROLE == 3)) x_pv_load(sb, s + 2, w, L16, pva);
            if (PV_MODE == 2 && ROLE == 2) bar_arrive<NB_P, 384>(); else bar_sync<NB_P, 384>();
            if (PV_MODE == 2) {
                if (ROLE == 3) { x_pv_run(sb, s + 2, w, L16, pva); x_pv_load(sb, s + 2, wq, L16, pva); x_pv_run(sb, s + 2, wq, L16, pva); }
            } else
            if (!(OFF & 8)) x_pv_run(sb, s + 2, w, L16, pva);
            if (ROLE == 3 && s + 2 < XLIM) mbar_wait(sb + B_X + par * 8, ((s + 2) >> 1) & 1);
        }
        if (s == NSEG - 1) break;
        if (wg == 0) {
            if (!isv) mbar_wait(sb + B_VX + par * 8, (s >> 1) & 1);
            uint32_t va[4][4];
            const uint32_t vx = sb + S_VX + (s & 3) * 8192 + wq * 2048 + L16;
            const uint32_t vm = sb + S_VM + (s & 3) * 2048 + wq * 512 + (L16 >> 1);
            lds128(va[0], vx);
            lds128(va[2], vx + 1024);
            mbar_wait(sb + B_S, par);
            __half2 hs[5];
            load_scores(sb + S_SP + L16, hs);
            float ev[10];
            softmax_exp(hs, ev);
            lds128(va[1], vx + 512);
            lds128(va[3], vx + 1536);
            uint32_t p[5];
#pragma unroll
            for (int i = 0; i < 5; i++) p[i] = pack_bf16(ev[2 * i], ev[2 * i + 1]);
            uint32_t vm0[2], vm1[2];
            const uint32_t ones[4] = {ONES, ONES, ONES, ONES};
            float sum[4], o0[4], o1[4];
            mma16z(o0, va[0], p[0], p[1]);
            mma16z(o1, va[2], p[0], p[1]);
            mma16z(sum, ones, p[0], p[1]);
            lds64(vm0, vm);
            lds64(vm1, vm + 256);
            mma16(o0, va[1], p[2], p[3]);
            mma16(o1, va[3], p[2], p[3]);
            mma16(sum, ones, p[2], p[3]);
            mma8(o0, vm0[0], vm0[1], p[4]);
            mma8(o1, vm1[0], vm1[1], p[4]);
            mma8(sum, ONES, ONES, p[4]);
            stsm4t(sb + S_OM + wq * 512 + L16, pack_bf16(o0[0], o0[1]), pack_bf16(o0[2], o0[3]), pack_bf16(o1[0], o1[1]), pack_bf16(o1[2], o1[3]));
            sts64(sb + S_SUM + wq * 256 + (L16 >> 1), __float_as_uint(sum[0]), __float_as_uint(sum[1]));
        }
        bar_sync<NB_O, 256>();
        {
            float a0[4], a1[4], e[4];
            float2 sc;
            float sr, r0, r1, rr;
#pragma unroll
            for (int i = 0; i < 4; i++) {
                uint32_t b[4];
                ldsm4(b, sb + S_OM + i * 512 + L16);
                if (i == 0) {
                    mma16z(a0, woA[0], b[0], b[1]); mma16z(a1, woA[1], b[2], b[3]);
                    mma_sp<0>(e, b, woB[0]);
                } else {
                    if (i == 1) { sc = lds64f(sb + S_SUM + (L16 >> 1)); sr = lds32f(sb + S_SUM + ((L16 >> 4) & 0x1C)); }
                    const uint32_t z = __float_as_uint(a0[0]) & zero;
                    mma16(a0, woA[2 * i], b[0], b[1]); mma16(a1, woA[2 * i + 1], b[2], b[3]);
                    mma_sp<1>(e, b, woB[i]);
                    if (i == RCP_AT) {
                        r0 = rcp(__uint_as_float(__float_as_uint(sc.x) | z));
                        r1 = rcp(__uint_as_float(__float_as_uint(sc.y) | z));
                        rr = rcp(__uint_as_float(__float_as_uint(sr) | z));
                    }
                }
            }
            asm volatile("" : "+r"(L16));
            char* const rslot = reinterpret_cast<char*>(g_acc) + ((s + 1) * SLOT_BYTES + j * 8192 + w * 1024) + (L16 + (L16 & 0x1C0));
            asm volatile("red.relaxed.gpu.global.add.noftz.v4.bf16x2 [%0], {%1,%2,%3,%4};"
                         ::"l"(rslot), "r"(pack_bf16((a0[0] + a1[0]) * r0, (a0[1] + a1[1]) * r1)), "r"(pack_bf16((a0[2] + a1[2]) * r0, (a0[3] + a1[3]) * r1)),
                           "r"(pack_bf16((e[0] + e[2]) * rr, (e[1] + e[3]) * rr)), "r"(0x3F80u) : "memory");
        }
        bar_sync<NB_X, 256>();
        wg_fence();
        x_project<0, POLL_AT>(xd, wA, xdesc + par * (XB_BYTES >> 4));
        bar_arrive<NB_RED, 384>();
        x_project<POLL_AT, 36>(xd, wA, xdesc + par * (XB_BYTES >> 4));
        wg_commit();
        s++;
    }
    if (isv) {
        uint32_t pva[3][4];
        x_pv_load(sb, NSEG - 2, w, L16, pva);
        bar_sync<NB_RED, 384>();
        x_pv_run(sb, NSEG - 2, w, L16, pva);
        bar_arrive<NB_QK, 384>();
        x_pv_load(sb, NSEG - 1, w, L16, pva);
        bar_sync<NB_P, 384>();
        x_pv_run(sb, NSEG - 1, w, L16, pva);
        bar_arrive<NB_PRO, 384>();
    }
}

template <bool isv>
__device__ __forceinline__ void chain_aux(const uint32_t sb, const uint32_t lane16, const int wq, const uint32_t j, const uint32_t h,
                                          const uint32_t peerA, const uint32_t peerB, const CUtensorMap* tmWo, const CUtensorMap* tmX,
                                          const bf16* __restrict__ mem0) {
    const int t = wq * 32 + (lane16 >> 4);
    TSTAMP(64, 0);
    cluster_arrive();
    {
        uint4* z = g_acc + blockIdx.x * 1024 + t;
#pragma unroll
        for (int i = 0; i < 8; i++) z[i * 128] = make_uint4(0, 0, 0, 0);
        if (blockIdx.x == 0) { g_flag[t] = 0; g_flag[128 + t] = 0; }
        for (int i = t; i < 576; i += 128) {
            const uint4 v = *reinterpret_cast<const uint4*>(mem0 + (i & 7) * DM + (i >> 3) * 8);
            sts128(sb + S_MEM + i * 16, v.x, v.y, v.z, v.w);
        }
        __threadfence();
        bar_sync<NB_AUX, 128>();
        if (t == 0) red_release(&g_zero_cnt, 1);
        asm volatile("griddepcontrol.launch_dependents;" ::: "memory");
        bar_sync<NB_PRO, 384>();
        if (t == 0) {
            fence_async_smem();
            mbar_expect(sb + B_WO, 49152);
            for (int b = 0; b < 3; b++) tma2d(sb + S_WO + b * 16384, tmWo, 192 * j + 64 * b, h * 128, sb + B_WO);
        }
        unsigned c = 0;
        while (ld_acquire(&g_zero_cnt) < 96 && ++c < SPIN_LIM) {}
        __syncwarp();
        for (int c2 = 0; c2 < 3; c2++) mbar_arrive_if0(sb + B_M + c2 * 8, lane16);
        cluster_wait();
        bar_sync<NB_RED, 384>();
        if (t == 0) {
            fence_async_smem();
            if (!isv) mbar_expect(sb + B_VX, 8192);
            else {
                bulk_s2c(peerA + S_VX, sb + S_VX, 8192, peerA + B_VX);
                bulk_s2c(peerB + S_VX, sb + S_VX, 8192, peerB + B_VX);
            }
            mbar_expect(sb + B_X, XB_BYTES);
            tma3d(sb + S_XB, tmX, 0, 64, 0, sb + B_X);
        }
        __syncwarp();
    }
    TSTAMP(0, 0);
    uint32_t L16 = lane16;
    const char* slot = reinterpret_cast<const char*>(g_acc) + wq * 1024 + (L16 + (L16 & 0x1C0));
    float ev[10];
    int s = 0;
#pragma unroll 1
    while (true) {
        const uint32_t par = s & 1;
        asm volatile("" : "+r"(L16));
        if (!isv) {
            if (wq == 0) {
                bar_sync<NB_QK, 384>();
                uint32_t q0[4], q1[4], k0[4], k1[4];
                ldsm4(q0, sb + S_QM + L16);
                ldsm4(k0, sb + S_KM + L16);
                ldsm4(q1, sb + S_QM + 512 + L16);
                ldsm4(k1, sb + S_KM + 512 + L16);
                mem_scores(sb, peerA, peerB, S_SP + j * 128 + 1024 + (L16 >> 2), q0, q1, k0, k1);
                mbar_expect_if0(sb + B_S, 640 + 2048, L16);
            } else if (wq == 3) {
                bar_sync<NB_GO, 288>();
                const unsigned t = post_time(s, L16);
                bar_sync<NB_QK, 384>();
                if (j == 0 && s < NSEG - 1) {
                    if (LOOK_NS) __nanosleep(LOOK_NS);
                    plan_look(sb, s, L16, t);
                }
            } else {
                bar_arrive<NB_QK, 384>();
                if (wq == 2) {
                    if (L16 == 0) {
                        if (s + 3 < XLIM) mbar_expect(sb + B_X + (par ^ 1) * 8, XB_BYTES);
                        mbar_expect(sb + B_VX + (par ^ 1) * 8, (OFF & 2) ? 0 : 8192);
                        mbar_expect(sb + B_T, 4);
                        if (s == 2 && h == 0 && j == 0) g_zero_cnt = 0;
                    }
                } else if (s + 3 < XLIM && j == 1) {
                    mbar_wait(sb + B_S, par);
                    delay(XTMA_DELAY);
                    if (XTMA_NS) __nanosleep(XTMA_NS);
                    if (L16 == 0) tma3d_mc(sb + S_XB + (par ^ 1) * XB_BYTES, tmX, 0, (s + 3) * SEG, 0, sb + B_X + (par ^ 1) * 8, 7);
                }
                __syncwarp();
            }
        } else {
            if (wq == 3) {
                bar_sync<NB_GO, 288>();
                post_time(s, L16);
            } else if (L16 == 0) {
                if (wq == 0) {
                    if (!(OFF & 2) && s >= 1) {
                        bulk_wait0();
                        bulk_g2s_mc(sb + S_VX + (s & 3) * 8192, g_vx + (h * 2 + par) * 512, 8192, sb + B_VX + par * 8, 3);
                    }
                } else if (wq == 1) {
                    if (OX_AT == 0 && s >= 3) ox_publish(s - 3, h);
                    if (OX_AT != 0 && s >= 4) ox_publish(s - 4, h);
                } else {
                    mbar_expect(sb + B_SX + par * 8, (OFF & 16) ? 0 : 3584);
                    mbar_expect(sb + B_T, 4);
                    if (s + 3 < XLIM) mbar_expect(sb + B_X + (par ^ 1) * 8, XB_BYTES);
                }
            }
            __syncwarp();
            if (s >= 1) mbar_wait(sb + B_SX + (par ^ 1) * 8, ((s - 1) >> 1) & 1);
            bar_sync<NB_P, 384>();
            if (OX_AT == 1 && wq == 1) { if (L16 == 0 && s >= 3) ox_store(sb, s - 3, h); __syncwarp(); }
            if (!(OFF & 4) || s == NSEG - 1) x_scores(sb, s + 1, wq, L16, ev);
            if (OX_AT == 2 && wq == 1) { if (L16 == 0 && s >= 3) ox_store(sb, s - 3, h); __syncwarp(); }
            if (wq == 0) {
                if (!(OFF & 2) && L16 == 0 && s + 1 < NSEG) {
                    fence_async_smem();
                    bulk_s2g(g_vx + (h * 2 + (par ^ 1)) * 512, sb + S_VX + ((s + 1) & 3) * 8192, 8192);
                    bulk_commit();
                }
                __syncwarp();
            }
        }
        if (s == NSEG - 1) break;
        bar_sync<NB_RED, 384>();
        if (isv && !(OFF & 4)) x_probs(sb, s + 1, wq, L16, ev);
        asm volatile("" : "+r"(L16));
        slot += SLOT_BYTES;
        mbar_wait(sb + B_T, par);
        {
            const unsigned tgt = __float_as_uint(lds32f(sb + S_TGT));
            while ((int)(gtime() - tgt) < 0) {}
        }
        uint4 v[6];
#pragma unroll
        for (int i = 0; i < 6; i++) v[i] = ld_poll(slot + i * 4096);
        if (OX_AT == 0 && !(OFF & 1) && isv && wq == 1 && s >= 2) { delay(OX_DELAY); if (L16 == 0) ox_store(sb, s - 2, h); __syncwarp(); }
        s++;
        const uint32_t ma = sb + S_MEM + wq * 384 + L16;
        unsigned c = 0;
        constexpr int CW = 6 / NCH;
        int done = NCH;
#pragma unroll
        for (int k = 0; k < NCH; k++) {
            uint32_t bad = 0;
#pragma unroll
            for (int i = CW * k; i < CW * k + CW; i++) { stsm2t(ma + i * 1536, v[i].x, v[i].y); stsm1(ma + i * 1536 + 256, v[i].z); bad |= v[i].w ^ FULL_COUNT; }
            const bool again = __any_sync(0xffffffffu, bad != 0);
            mbar_arrive_if0(sb + B_M + k * 8, L16 | (uint32_t)again);
            if (again) { done = k; break; }
        }
        if (done < NCH) {
            uint32_t bad;
            do {
#pragma unroll
                for (int i = 0; i < 6; i++) if (i >= CW * done) v[i] = ld_poll(slot + i * 4096);
                bad = 0;
#pragma unroll
                for (int i = 0; i < 6; i++) if (i >= CW * done) { stsm2t(ma + i * 1536, v[i].x, v[i].y); stsm1(ma + i * 1536 + 256, v[i].z); bad |= v[i].w ^ FULL_COUNT; }
            } while (++c < SPIN_LIM && __any_sync(0xffffffffu, bad != 0));
            __syncwarp();
#pragma unroll
            for (int k = 0; k < NCH; k++) if (k >= done) mbar_arrive_if0(sb + B_M + k * 8, L16);
        }
        TSTAMP(s, c | t_pack);
    }
    if (!isv) {
        mbar_wait(sb + B_VX + 8, ((NSEG - 1) >> 1) & 1);
        mbar_wait(sb + B_S, 1);
    } else {
        x_probs(sb, NSEG - 2, wq, L16, ev);
        if (OX_AT != 0 && wq == 1) { if (L16 == 0) ox_publish(NSEG - 4, h); __syncwarp(); }
        bar_sync<NB_RED, 384>();
        if (wq == 1 && L16 == 0) ox_store(sb, NSEG - 3, h);
        __syncwarp();
        bar_sync<NB_QK, 384>();
        if (wq == 2 && L16 == 0) ox_store(sb, NSEG - 2, h);
        __syncwarp();
        mbar_wait(sb + B_S, 1);
        mbar_wait(sb + B_SX + 8, ((NSEG - 1) >> 1) & 1);
        x_scores(sb, NSEG - 1, wq, L16, ev);
        x_probs(sb, NSEG - 1, wq, L16, ev);
        if (wq == 1 && L16 == 0) ox_publish(NSEG - 3, h);
        __syncwarp();
        bar_arrive<NB_P, 384>();
        if (wq == 2) { if (L16 == 0) ox_publish(NSEG - 2, h); __syncwarp(); bar_arrive<NB_PRO, 384>(); }
        else bar_sync<NB_PRO, 384>();
        if (wq == 3 && L16 == 0) { ox_store(sb, NSEG - 1, h); ox_publish(NSEG - 1, h); }
    }
}

__global__ void __launch_bounds__(384, 1)
chain_kernel(const __grid_constant__ CUtensorMap tmWq, const __grid_constant__ CUtensorMap tmWk, const __grid_constant__ CUtensorMap tmWv,
             const __grid_constant__ CUtensorMap tmWo, const __grid_constant__ CUtensorMap tmX, const bf16* __restrict__ mem0) {
    extern __shared__ __align__(1024) uint8_t smem[];
    const uint32_t sb = smem_u32(smem);
    const int tid = threadIdx.x;
    const uint32_t L16 = __shfl_sync(0xffffffffu, (tid & 31) * 16, tid & 31);
    const int w = __shfl_sync(0xffffffffu, tid >> 5, 0), wg = w >> 2, wq = w & 3;
    uint32_t j, h;
    asm("mov.u32 %0, %%cluster_ctarank;" : "=r"(j));
    asm("mov.u32 %0, %%clusterid.x;" : "=r"(h));
    const bool isv = (j == 2);
    const uint32_t peerA = mapa(sb, isv ? 0 : (j ^ 1)), peerB = mapa(sb, isv ? 1 : 2);
    if (tid == 256) {
        for (int c = 0; c < 3; c++) { mbar_init(sb + B_W + 8 * c, 1); mbar_init(sb + B_M + 8 * c, 4); }
        mbar_init(sb + B_WO, 1); mbar_init(sb + B_T, 1);
        mbar_init(sb + B_X, 1); mbar_init(sb + B_X + 8, 1);
        mbar_init(sb + B_S, isv ? 8 : 5);
        mbar_init(sb + B_VX, 1); mbar_init(sb + B_VX + 8, 1);
        mbar_init(sb + B_SX, 1); mbar_init(sb + B_SX + 8, 1);
        asm volatile("fence.mbarrier_init.release.cluster;" ::: "memory");
        const CUtensorMap* m0 = isv ? &tmWv : &tmWq;
        const CUtensorMap* m1 = isv ? &tmWv : &tmWk;
        const int c0 = h * 128 + (isv ? 0 : 64 * j), c1 = h * 128 + (isv ? 64 : 64 * j);
        mbar_expect(sb + B_X, XB_BYTES);
        tma3d(sb + S_XB, &tmX, 0, 0, 0, sb + B_X);
#pragma unroll
        for (int c = 0; c < 3; c++) {
            mbar_expect(sb + B_W + 8 * c, 49152);
            tma2d(sb + s_w(c), m0, c0, c * 192, sb + B_W + 8 * c);
            tma2d(sb + s_w(c) + 24576, m1, c1, c * 192, sb + B_W + 8 * c);
        }
        mbar_expect(sb + B_X + 8, XB_BYTES);
        tma3d(sb + S_XB + XB_BYTES, &tmX, 0, 32, 0, sb + B_X + 8);
    }
    __syncthreads();
    if (wg == 2) {
        asm volatile("setmaxnreg.dec.sync.aligned.u32 %0;" ::"n"(REG_AUX));
        if (!isv) chain_aux<false>(sb, L16, wq, j, h, peerA, peerB, &tmWo, &tmX, mem0);
        else chain_aux<true>(sb, L16, wq, j, h, peerA, peerB, &tmWo, &tmX, mem0);
        __syncwarp();
        cluster_arrive(); cluster_wait();
        TSTAMP(65, 0);
    } else if (wg == 0) {
        asm volatile("setmaxnreg.inc.sync.aligned.u32 %0;" ::"n"(REG_MAIN0));
        if (!isv) chain_main<0>(sb, L16, wq, j, h, peerA, peerB);
        else chain_main<2>(sb, L16, wq, j, h, peerA, peerB);
        cluster_arrive(); cluster_wait();
    } else {
        asm volatile("setmaxnreg.inc.sync.aligned.u32 %0;" ::"n"(REG_MAIN1));
        if (!isv) chain_main<1>(sb, L16, wq, j, h, peerA, peerB);
        else chain_main<3>(sb, L16, wq, j, h, peerA, peerB);
        cluster_arrive(); cluster_wait();
    }
}

constexpr int NHELP = 36;
constexpr uint32_t H_U = 0;
constexpr uint32_t UT_PITCH = 4368;
constexpr uint32_t H_UT = 65536;
constexpr uint32_t KW_BYTES = 8320;
constexpr uint32_t H_KW = 135424;
constexpr uint32_t H_PAR = 201984;
constexpr uint32_t H_KD = 218368;
constexpr uint32_t H_STAGE = 0;
constexpr uint32_t H_RED = 196608;
constexpr uint32_t H_FIN = 212992;
constexpr uint32_t H_BAR = 229376;
constexpr uint32_t B_SMEM = H_BAR + 256;
constexpr uint32_t HB_U = H_BAR, HB_WO = H_BAR + 8, HB_FULL = H_BAR + 16, HB_EMPTY = H_BAR + 64, HB_RFULL = H_BAR + 112, HB_REMPTY = H_BAR + 128, HB_FIN = H_BAR + 144;
__device__ __align__(1024) uint4 g_part[4 * 9 * 4 * 4 * 128];

__device__ __forceinline__ float2 cmul(float2 a, float2 b) { return make_float2(fmaf(a.x, b.x, -a.y * b.y), fmaf(a.x, b.y, a.y * b.x)); }
__device__ __forceinline__ float2 csqr(float2 a) { return make_float2(fmaf(a.x, a.x, -a.y * a.y), (a.x + a.x) * a.y); }
__device__ __forceinline__ float2 cexp(float zr, float zi, float p) {
    const float m = ex2(zr * p);
    const float r = zi * p;
    const float a = (r - rintf(r)) * 6.283185307179586f;
    return make_float2(m * __cosf(a), m * __sinf(a));
}
__device__ __forceinline__ uint32_t pack_f16(float lo, float hi) { uint32_t r; asm("cvt.rn.f16x2.f32 %0, %1, %2;" : "=r"(r) : "f"(hi), "f"(lo)); return r; }
__device__ __forceinline__ void mma16h(float* d, const uint32_t* a, uint32_t b0, uint32_t b1) {
    asm volatile("mma.sync.aligned.m16n8k16.row.col.f32.f16.f16.f32 {%0,%1,%2,%3},{%4,%5,%6,%7},{%8,%9},{%0,%1,%2,%3};"
                 : "+f"(d[0]), "+f"(d[1]), "+f"(d[2]), "+f"(d[3]) : "r"(a[0]), "r"(a[1]), "r"(a[2]), "r"(a[3]), "r"(b0), "r"(b1));
}
__device__ __forceinline__ float bf_round(float x) { return __bfloat162float(__float2bfloat16_rn(x)); }
__device__ __forceinline__ uint32_t lds32(uint32_t a) { uint32_t v; asm volatile("ld.shared.b32 %0,[%1];" : "=r"(v) : "r"(a) : "memory"); return v; }
__device__ __forceinline__ uint32_t lds16(uint32_t a) { uint16_t v; asm volatile("ld.shared.u16 %0,[%1];" : "=h"(v) : "r"(a) : "memory"); return v; }
__device__ __forceinline__ void stsm4(uint32_t a, uint32_t r0, uint32_t r1, uint32_t r2, uint32_t r3) { asm volatile("stmatrix.sync.aligned.m8n8.x4.shared.b16 [%0],{%1,%2,%3,%4};" ::"r"(a), "r"(r0), "r"(r1), "r"(r2), "r"(r3) : "memory"); }

__device__ __forceinline__ void s4d_kernel(uint32_t par, uint32_t kd, uint32_t kw, int d, int lane, const bf16* __restrict__ logA, const bf16* __restrict__ Aim,
                                           const bf16* __restrict__ Cre, const bf16* __restrict__ Cim, const bf16* __restrict__ logdt) {
    const float dt = bf_round(expf(__bfloat162float(logdt[d])));
    float4 q[4];
    float cmax = 0.f, last = 0.f;
#pragma unroll
    for (int i = 0; i < 4; i++) {
        const int n = d * NST + i * 32 + lane;
        q[i].x = -bf_round(expf(__bfloat162float(logA[n]))) * dt * 1.4426950408889634f;
        q[i].y = __bfloat162float(Aim[n]) * dt * 0.15915494309189535f;
        q[i].z = 2.f * (__bfloat162float(Cre[n]) * dt);
        q[i].w = 2.f * (__bfloat162float(Cim[n]) * dt);
        cmax = fmaxf(cmax, fmaxf(fabsf(q[i].z), fabsf(q[i].w)));
        const float2 e = cexp(q[i].x, q[i].y, 2048.f);
        last += q[i].z * e.x - q[i].w * e.y;
    }
#pragma unroll
    for (int o = 16; o; o >>= 1) { cmax = fmaxf(cmax, __shfl_xor_sync(0xffffffffu, cmax, o)); last += __shfl_xor_sync(0xffffffffu, last, o); }
    const float cs = __uint_as_float(max(__float_as_uint(cmax) & 0x7F800000u, 0x00800000u));
    const float ci = 1.f / cs;
#pragma unroll
    for (int i = 0; i < 4; i++) sts128(par + (i * 32 + lane) * 16, __float_as_uint(q[i].x), __float_as_uint(q[i].y), __float_as_uint(q[i].z * ci), __float_as_uint(q[i].w * ci));
    __syncwarp();
    float acc[5][4];
#pragma unroll
    for (int i = 0; i < 5; i++) acc[i][0] = acc[i][1] = acc[i][2] = acc[i][3] = 0.f;
    const float g = (float)(lane >> 2);
#pragma unroll 1
    for (int ks = 0; ks < 16; ks++) {
        uint32_t A[5][4], B[4][2];
#pragma unroll
        for (int hf = 0; hf < 2; hf++) {
            uint32_t r[4];
            lds128(r, par + (ks * 8 + hf * 4 + (lane & 3)) * 16);
            const float zr = __uint_as_float(r[0]), zi = __uint_as_float(r[1]);
            const float2 c = make_float2(__uint_as_float(r[2]), __uint_as_float(r[3]));
            float2 y = cexp(zr, zi, g), x0 = cexp(zr, zi, 8.f * g + 128.f), x1 = cexp(zr, zi, 8.f * g + 192.f);
            const float2 xl = cexp(zr, zi, 8.f * g + 64.f);
#pragma unroll
            for (int k = 0; k < 4; k++) {
                const float2 cy = cmul(c, y);
                B[k][hf] = pack_f16(cy.x, -cy.y);
                A[k + 1][2 * hf] = pack_f16(x0.x, x0.y);
                A[k + 1][2 * hf + 1] = pack_f16(x1.x, x1.y);
                if (k < 3) { y = csqr(y); x0 = csqr(x0); x1 = csqr(x1); }
            }
            A[0][2 * hf] = pack_f16(y.x, y.y);
            A[0][2 * hf + 1] = pack_f16(xl.x, xl.y);
        }
        mma16h(acc[0], A[0], B[0][0], B[0][1]);
#pragma unroll
        for (int k = 0; k < 4; k++) mma16h(acc[k + 1], A[k + 1], B[k][0], B[k][1]);
    }
#pragma unroll
    for (int i = 0; i < 5; i++) {
        sts32(kd + i * 256 + lane * 4, pack_bf16(acc[i][0] * cs, acc[i][1] * cs));
        sts32(kd + i * 256 + 128 + lane * 4, pack_bf16(acc[i][2] * cs, acc[i][3] * cs));
    }
    if (lane == 0) sts32(kd + 1280, pack_bf16(last, 0.f));
    if (lane < 16) sts32(kw + lane * 4, 0);
    __syncwarp();
    uint32_t carry = 0;
#pragma unroll 4
    for (int it = 0; it < 64; it++) {
        const int l = it * 32 + lane;
        const int jx = l < 128 ? l : (int)__bfloat16_as_ushort(__float2bfloat16_rn((float)l)) - (133 << 7);
        const uint32_t v = lds16(kd + jx * 2);
        uint32_t pv = __shfl_up_sync(0xffffffffu, v, 1);
        if (lane == 0) pv = carry;
        carry = __shfl_sync(0xffffffffu, v, 31);
        sts32(kw + 64 + l * 4, v | (pv << 16));
    }
    __syncwarp();
}

__device__ __forceinline__ void s4d_conv(uint32_t ut, uint32_t kw, int lane) {
    float acc[16][4];
#pragma unroll
    for (int i = 0; i < 16; i++) acc[i][0] = acc[i][1] = acc[i][2] = acc[i][3] = 0.f;
    const uint32_t ka = kw + 64 + ((lane >> 2) - 2 * (lane & 3)) * 4;
    const uint32_t ua = ut + 256 + lane * 8;
#pragma unroll 1
    for (int rho = 0; rho < 8; rho++) {
        uint32_t B[16][2];
#pragma unroll
        for (int q = 0; q < 16; q++) lds64(B[q], ua + q * 256 - rho * 32);
#pragma unroll
        for (int m = 0; m < 16; m++) {
            uint32_t A[4];
            const uint32_t x = ka + m * 512 + rho * 64;
            A[0] = lds32(x); A[1] = lds32(x + 32); A[2] = lds32(x - 32); A[3] = A[0];
#pragma unroll
            for (int i = m; i < 16; i++) mma16(acc[i], A, B[i - m][0], B[i - m][1]);
        }
    }
    __syncwarp();
    const uint32_t ya = ut + 256 + (lane & 7) * 32 + ((lane >> 3) & 1) * 16 + (lane >> 4) * 256;
#pragma unroll
    for (int i = 0; i < 16; i += 2)
        stsm4t(ya + i * 256, pack_bf16(acc[i][0], acc[i][1]), pack_bf16(acc[i][2], acc[i][3]),
               pack_bf16(acc[i + 1][0], acc[i + 1][1]), pack_bf16(acc[i + 1][2], acc[i + 1][3]));
}

__global__ void __launch_bounds__(384, 1)
helper_kernel(const __grid_constant__ CUtensorMap tmU, const __grid_constant__ CUtensorMap tmY, const __grid_constant__ CUtensorMap tmWo,
              const bf16* __restrict__ logA, const bf16* __restrict__ Aim, const bf16* __restrict__ Cre, const bf16* __restrict__ Cim,
              const bf16* __restrict__ logdt, const bf16* __restrict__ Dskip, bf16* __restrict__ out) {
    extern __shared__ __align__(1024) uint8_t smem[];
    const uint32_t sb = smem_u32(smem);
    const int tid = threadIdx.x, lane = tid & 31;
    const int w = __shfl_sync(0xffffffffu, tid >> 5, 0);
    const int d0 = blockIdx.x * 16;
    HSTAMP(0);
    if (tid == 0) {
        mbar_init(sb + HB_U, 1); mbar_init(sb + HB_WO, 1);
        for (int i = 0; i < 6; i++) { mbar_init(sb + HB_FULL + 8 * i, 1); mbar_init(sb + HB_EMPTY + 8 * i, 4); }
        for (int i = 0; i < 2; i++) { mbar_init(sb + HB_RFULL + 8 * i, 4); mbar_init(sb + HB_REMPTY + 8 * i, 4); mbar_init(sb + HB_FIN + 8 * i, 2); }
        fence_async_smem();
        mbar_expect(sb + HB_U, 65536);
        for (int i = 0; i < 8; i++) tma2d(sb + H_U + i * 8192, &tmU, d0, i * 256, sb + HB_U);
    }
    __syncthreads();
    const int m = lane >> 3, r = lane & 7;
    if (w < 8) {
        s4d_kernel(sb + H_PAR + w * 2048, sb + H_KD + w * 1296, sb + H_KW + w * KW_BYTES, d0 + w, lane, logA, Aim, Cre, Cim, logdt);
    } else {
        for (int i = tid - 256; i < 256; i += 128) sts128(sb + H_UT + (i >> 4) * UT_PITCH + (i & 15) * 16, 0, 0, 0, 0);
        mbar_wait(sb + HB_U, 0);
        const uint32_t src = sb + H_U + ((m & 1) * 8 + r) * 32 + (((m >> 1) ^ (r >> 2)) << 4);
        const uint32_t dst = sb + H_UT + 256 + (lane >> 2) * UT_PITCH + (lane & 3) * 8;
#pragma unroll 4
        for (int grp = w - 8; grp < 128; grp += 4) {
            uint32_t v[4];
            ldsm4t(v, src + grp * 512);
            sts64(dst + grp * 32, v[0], v[1]);
            sts64(dst + 8 * UT_PITCH + grp * 32, v[2], v[3]);
        }
    }
    __syncthreads();
    HSTAMP(1);
    if (w < 8) {
        s4d_conv(sb + H_UT + w * UT_PITCH, sb + H_KW + w * KW_BYTES, lane);
        s4d_kernel(sb + H_PAR + w * 2048, sb + H_KD + w * 1296, sb + H_KW + w * KW_BYTES, d0 + 8 + w, lane, logA, Aim, Cre, Cim, logdt);
        s4d_conv(sb + H_UT + (8 + w) * UT_PITCH, sb + H_KW + w * KW_BYTES, lane);
    }
    __syncthreads();
    HSTAMP(2);
    const int cc = blockIdx.x % 9, kq = blockIdx.x / 9;
    {
        const __nv_bfloat162 D0 = *reinterpret_cast<const __nv_bfloat162*>(Dskip + d0 + (lane & 3) * 2);
        const __nv_bfloat162 D1 = *reinterpret_cast<const __nv_bfloat162*>(Dskip + d0 + 8 + (lane & 3) * 2);
        const uint32_t ua = sb + H_U + ((m & 1) * 8 + r) * 32 + (((m >> 1) ^ (r >> 2)) << 4);
        const uint32_t ya = sb + H_UT + 256 + ((m >> 1) * 8 + r) * UT_PITCH + (m & 1) * 16;
        for (int grp = w; grp < 128; grp += 12) {
            uint32_t u[4], y[4];
            ldsm4(u, ua + grp * 512);
            ldsm4t(y, ya + grp * 32);
#pragma unroll
            for (int i = 0; i < 4; i++) {
                const __nv_bfloat162 o = __hadd2_rn(*reinterpret_cast<__nv_bfloat162*>(&y[i]), __hmul2_rn(*reinterpret_cast<__nv_bfloat162*>(&u[i]), i < 2 ? D0 : D1));
                y[i] = *reinterpret_cast<const uint32_t*>(&o);
            }
            stsm4(ua + grp * 512, y[0], y[1], y[2], y[3]);
        }
        fence_async_smem();
        __syncthreads();
        if (tid == 0) {
            for (int i = 0; i < 8; i++)
                asm volatile("cp.async.bulk.tensor.2d.global.shared::cta.bulk_group [%0, {%1,%2}], [%3];" ::"l"(&tmY), "r"(DM + d0), "r"(i * 256), "r"(sb + H_U + i * 8192) : "memory");
            bulk_commit();
            mbar_expect(sb + HB_WO, 131072);
            for (int i = 0; i < 8; i++) tma2d(sb + 65536 + i * 16384, &tmWo, cc * 64, (kq * 8 + i) * 128, sb + HB_WO);
            asm volatile("cp.async.bulk.wait_group.read 0;" ::: "memory");
        }
    }
    __syncwarp();
    if (w < 8) {
        asm volatile("setmaxnreg.inc.sync.aligned.u32 208;");
        const int wg = w >> 2;
        uint32_t wo[32][4];
        mbar_wait(sb + HB_WO, 0);
        const uint32_t a = sb + 65536 + wg * 65536 + ((m >> 1) * 8 + r) * 128 + (((2 * (w & 3) + (m & 1)) ^ r) << 4);
#pragma unroll
        for (int i = 0; i < 32; i++) ldsm4t(wo[i], a + i * 2048);
        __syncthreads();
        HSTAMP(3);
        const int t = tid & 127;
        int st = 0, ph = 0;
#pragma unroll 1
        for (int s = 0; s < NSEG; s++) {
            mbar_wait_long(sb + HB_FULL + (st * 2 + wg) * 8, ph);
            const uint32_t desc = desc_lo(sb + H_STAGE + st * 65536 + wg * 32768);
            float d[16];
            wg_fence();
#pragma unroll
            for (int i = 0; i < 32; i++) {
                const uint32_t db = desc + (((i >> 2) * 4096 + (i & 3) * 32) >> 4);
                if (i == 0) wg_rs_n32<0>(d, wo[i], db); else wg_rs_n32<1>(d, wo[i], db);
            }
            wg_commit();
            wg_wait<0>();
            mbar_arrive_if0(sb + HB_EMPTY + (st * 2 + wg) * 8, lane);
            if (++st == 3) { st = 0; ph ^= 1; }
            const uint32_t ra = sb + H_RED + (s & 1) * 8192 + t * 16;
            if (wg == 0) {
                if (s >= 2) mbar_wait_long(sb + HB_REMPTY + (s & 1) * 8, ((s - 2) >> 1) & 1);
#pragma unroll
                for (int i = 0; i < 4; i++) sts128(ra + i * 2048, __float_as_uint(d[4 * i]), __float_as_uint(d[4 * i + 1]), __float_as_uint(d[4 * i + 2]), __float_as_uint(d[4 * i + 3]));
                __syncwarp();
                mbar_arrive_if0(sb + HB_RFULL + (s & 1) * 8, lane);
            } else {
                mbar_wait_long(sb + HB_RFULL + (s & 1) * 8, (s >> 1) & 1);
                if (s >= 2) mbar_wait_long(sb + HB_FIN + (s & 1) * 8, ((s - 2) >> 1) & 1);
                uint4* dst = g_part + (((s & 3) * 9 + cc) * 16 + kq) * 128 + t;
#pragma unroll
                for (int i = 0; i < 4; i++) {
                    uint32_t p[4];
                    lds128(p, ra + i * 2048);
#pragma unroll
                    for (int k = 0; k < 4; k++) p[k] = ((__float_as_uint(__uint_as_float(p[k]) + d[4 * i + k]) + 64) & ~127u) | (s + 1);
                    asm volatile("st.relaxed.gpu.global.v4.u32 [%0], {%1,%2,%3,%4};" ::"l"(dst + i * 512), "r"(p[0]), "r"(p[1]), "r"(p[2]), "r"(p[3]) : "memory");
                }
                __syncwarp();
                mbar_arrive_if0(sb + HB_REMPTY + (s & 1) * 8, lane);
            }
        }
        if (tid == 0) bulk_wait0();
    } else {
        asm volatile("setmaxnreg.dec.sync.aligned.u32 88;");
        __syncthreads();
        if (w == 8) {
            if (lane == 0) {
                int st = 0, ph = 1;
                for (int s = 0; s < NSEG; s++) {
                    unsigned c = 0;
                    while (ld_acquire(&g_flag[s * 4 + kq]) < 8 && ++c < LONG_LIM) __nanosleep(FLAG_NS);
                    asm volatile("fence.proxy.async;" ::: "memory");
                    for (int g = 0; g < 2; g++) {
                        const uint32_t bar = sb + HB_FULL + (st * 2 + g) * 8;
                        mbar_wait_long(sb + HB_EMPTY + (st * 2 + g) * 8, ph);
                        mbar_expect(bar, 32768);
                        asm volatile("cp.async.bulk.shared::cluster.global.mbarrier::complete_tx::bytes [%0], [%1], %2, [%3];"
                                     ::"r"(sb + H_STAGE + st * 65536 + g * 32768), "l"(g_ox + (s * NH + kq * 8 + g * 4) * 512), "r"(32768), "r"(bar) : "memory");
                    }
                    if (++st == 3) { st = 0; ph ^= 1; }
                }
            }
        } else if (w < 11) {
            const int f = w - 9;
            const uint32_t fa = sb + H_FIN + f * 512;
            for (int s = 0; s < NSEG; s++) {
                mbar_wait_long(sb + HB_REMPTY + (s & 1) * 8, (s >> 1) & 1);
                const uint4* src = g_part + (((s & 3) * 9 + cc) * 16 + kq * 4) * 128 + f * 64 + lane;
                uint4 v[8];
                unsigned c = 0;
                while (true) {
                    uint32_t bad = 0;
#pragma unroll
                    for (int i = 0; i < 8; i++) v[i] = ld_poll(src + (i >> 1) * 128 + (i & 1) * 32);
#pragma unroll
                    for (int i = 0; i < 8; i++) bad |= (v[i].x ^ (s + 1)) | (v[i].y ^ (s + 1)) | (v[i].z ^ (s + 1)) | (v[i].w ^ (s + 1));
                    if (!__any_sync(0xffffffffu, (bad & 127) != 0) || ++c >= LONG_LIM) break;
                    __nanosleep(FLAG_NS);
                }
                mbar_arrive_if0(sb + HB_FIN + (s & 1) * 8, lane);
                uint32_t pk[4];
#pragma unroll
                for (int u = 0; u < 2; u++) {
                    float o[4] = {0.f, 0.f, 0.f, 0.f};
#pragma unroll
                    for (int k = 0; k < 4; k++) {
                        o[0] += __uint_as_float(v[2 * k + u].x & ~127u); o[1] += __uint_as_float(v[2 * k + u].y & ~127u);
                        o[2] += __uint_as_float(v[2 * k + u].z & ~127u); o[3] += __uint_as_float(v[2 * k + u].w & ~127u);
                    }
                    pk[2 * u] = pack_bf16(o[0], o[1]); pk[2 * u + 1] = pack_bf16(o[2], o[3]);
                }
                stsm4t(fa + r * 64 + ((m ^ (r >> 1)) << 4), pk[0], pk[1], pk[2], pk[3]);
                __syncwarp();
                uint32_t o4[4];
                lds128(o4, fa + (lane >> 2) * 64 + (((lane & 3) ^ (lane >> 3)) << 4));
                *reinterpret_cast<uint4*>(out + (s * SEG + kq * 8 + (lane >> 2)) * OUTW + cc * 64 + f * 32 + (lane & 3) * 8) = make_uint4(o4[0], o4[1], o4[2], o4[3]);
                __syncwarp();
                HSTAMP2(s);
            }
            asm volatile("griddepcontrol.wait;" ::: "memory");
        }
    }
}

typedef CUresult (*EncodeFn)(CUtensorMap*, CUtensorMapDataType, cuuint32_t, void*, const cuuint64_t*, const cuuint64_t*, const cuuint32_t*,
                             const cuuint32_t*, CUtensorMapInterleave, CUtensorMapSwizzle, CUtensorMapL2promotion, CUtensorMapFloatOOBfill);

void make_map(EncodeFn fn, CUtensorMap* m, const void* p, int rank, const cuuint64_t* dims, const cuuint64_t* strides, const cuuint32_t* box,
              CUtensorMapSwizzle sw = CU_TENSOR_MAP_SWIZZLE_128B, CUtensorMapL2promotion pr = CU_TENSOR_MAP_L2_PROMOTION_L2_128B) {
    const cuuint32_t es[3] = {1, 1, 1};
    fn(m, CU_TENSOR_MAP_DATA_TYPE_BFLOAT16, rank, const_cast<void*>(p), dims, strides, box, es, CU_TENSOR_MAP_INTERLEAVE_NONE,
       sw, pr, CU_TENSOR_MAP_FLOAT_OOB_FILL_NONE);
}

}

extern "C" void kernel_launch(void* const* d_in, const int* in_sizes, int n_in, void* d_out, int out_size) {
    const bf16* x = (const bf16*)d_in[0];
    const bf16* mem0 = (const bf16*)d_in[1];
    const bf16* Wo = (const bf16*)d_in[5];
    bf16* out = (bf16*)d_out;

    static EncodeFn enc = nullptr;
    if (!enc) {
        void* fn = nullptr;
        cudaDriverEntryPointQueryResult st;
        cudaGetDriverEntryPoint("cuTensorMapEncodeTiled", &fn, cudaEnableDefault, &st);
        enc = (EncodeFn)fn;
        cudaFuncSetAttribute(chain_kernel, cudaFuncAttributeMaxDynamicSharedMemorySize, A_SMEM);
        cudaFuncSetAttribute(helper_kernel, cudaFuncAttributeMaxDynamicSharedMemorySize, B_SMEM);
    }
    CUtensorMap tmW[3], tmWo, tmX;
    {
        const cuuint64_t dims[2] = {4096, 576}, str[1] = {8192};
        const cuuint32_t box[2] = {64, 192};
        for (int i = 0; i < 3; i++) make_map(enc, &tmW[i], d_in[2 + i], 2, dims, str, box);
    }
    {
        const cuuint64_t dims[2] = {576, 4096}, str[1] = {1152};
        const cuuint32_t box[2] = {64, 128};
        make_map(enc, &tmWo, Wo, 2, dims, str, box);
    }
    {
        const cuuint64_t dims[3] = {64, 2048, 9}, str[2] = {1152, 128};
        const cuuint32_t box[3] = {64, 32, 9};
        make_map(enc, &tmX, x, 3, dims, str, box);
    }
    CUtensorMap tmU, tmY;
    {
        const cuuint64_t dimsU[2] = {576, 2048}, strU[1] = {1152}, dimsY[2] = {1152, 2048}, strY[1] = {2304};
        const cuuint32_t box[2] = {16, 256};
        make_map(enc, &tmU, d_in[7], 2, dimsU, strU, box, CU_TENSOR_MAP_SWIZZLE_32B);
        make_map(enc, &tmY, out, 2, dimsY, strY, box, CU_TENSOR_MAP_SWIZZLE_32B, CU_TENSOR_MAP_L2_PROMOTION_NONE);
    }
    cudaStream_t st = cudaStreamPerThread;
    {
        cudaLaunchConfig_t cfg = {};
        cfg.gridDim = dim3(96); cfg.blockDim = dim3(384); cfg.dynamicSmemBytes = A_SMEM; cfg.stream = st;
        cudaLaunchAttribute at[1];
        at[0].id = cudaLaunchAttributeClusterDimension;
        at[0].val.clusterDim.x = 3; at[0].val.clusterDim.y = 1; at[0].val.clusterDim.z = 1;
        cfg.attrs = at; cfg.numAttrs = 1;
        cudaLaunchKernelEx(&cfg, chain_kernel, tmW[0], tmW[1], tmW[2], tmWo, tmX, mem0);
    }
    {
        cudaLaunchConfig_t cfg = {};
        cfg.gridDim = dim3(NHELP); cfg.blockDim = dim3(384); cfg.dynamicSmemBytes = B_SMEM; cfg.stream = st;
        cudaLaunchAttribute at[1];
        at[0].id = cudaLaunchAttributeProgrammaticStreamSerialization;
        at[0].val.programmaticStreamSerializationAllowed = 1;
        cfg.attrs = at; cfg.numAttrs = 1;
        cudaLaunchKernelEx(&cfg, helper_kernel, tmU, tmY, tmWo, (const bf16*)d_in[8], (const bf16*)d_in[9], (const bf16*)d_in[10],
                           (const bf16*)d_in[11], (const bf16*)d_in[12], (const bf16*)d_in[13], out);
    }
}
```

```cpp
#include <cuda_runtime.h>
#include <cuda_bf16.h>
#include <cuda_fp16.h>
#include <cuda.h>
#include <stdint.h>

typedef __nv_bfloat16 bf16;

namespace {

constexpr int DM = 576, NH = 32, DH = 128, SEG = 32, NSEG = 64, SEQ = 2048, NST = 128;
constexpr int OUTW = 2 * DM;
constexpr unsigned SPIN_LIM = 1u << 15;

__device__ __align__(1024) uint4 g_acc[33 * 2048];
__device__ __align__(128) unsigned g_time[NSEG * 96];
__device__ __align__(1024) uint4 g_ox[NSEG * NH * 512];
__device__ __align__(1024) uint4 g_vx[NH * 2 * 512];
__device__ unsigned g_flag[NSEG * 4];
__device__ unsigned g_zero_cnt;

__device__ __forceinline__ uint32_t smem_u32(const void* p) { return (uint32_t)__cvta_generic_to_shared(p); }
__device__ __forceinline__ unsigned clk() { unsigned c; asm volatile("mov.u32 %0, %%clock;" : "=r"(c)::"memory"); return c; }
__device__ __forceinline__ unsigned gtime() { unsigned t; asm volatile("mov.u32 %0, %%globaltimer_lo;" : "=r"(t)::"memory"); return t; }
__device__ __forceinline__ uint32_t slot_off(int s) { return (s >> 1) * 32768 + (s & 1) * 512; }
__device__ __forceinline__ uint32_t lane_off(uint32_t L16) { return (L16 & 0x180) * 8 + (L16 & 0x40) * 4 + (L16 & 0x30); }
__device__ __forceinline__ uint32_t mapa(uint32_t a, uint32_t r) { uint32_t o; asm("mapa.shared::cluster.u32 %0, %1, %2;" : "=r"(o) : "r"(a), "r"(r)); return o; }
__device__ __forceinline__ void mbar_init(uint32_t b, uint32_t n) { asm volatile("mbarrier.init.shared::cta.b64 [%0], %1;" ::"r"(b), "r"(n) : "memory"); }
__device__ __forceinline__ void mbar_arrive(uint32_t b) { asm volatile("mbarrier.arrive.shared::cta.b64 _, [%0];" ::"r"(b) : "memory"); }
__device__ __forceinline__ void mbar_expect(uint32_t b, uint32_t tx) { asm volatile("mbarrier.arrive.expect_tx.shared::cta.b64 _, [%0], %1;" ::"r"(b), "r"(tx) : "memory"); }
__device__ __forceinline__ bool mbar_try(uint32_t b, uint32_t par) {
    uint32_t ok;
    asm volatile("{.reg .pred p; mbarrier.try_wait.parity.shared::cta.b64 p, [%1], %2; selp.u32 %0, 1, 0, p;}" : "=r"(ok) : "r"(b), "r"(par) : "memory");
    return ok;
}
__device__ __forceinline__ bool mbar_test(uint32_t b, uint32_t par) {
    uint32_t ok;
    asm volatile("{.reg .pred p; mbarrier.test_wait.parity.shared::cta.b64 p, [%1], %2; selp.u32 %0, 1, 0, p;}" : "=r"(ok) : "r"(b), "r"(par) : "memory");
    return ok;
}
__device__ __forceinline__ void mbar_wait(uint32_t b, uint32_t par) {
    asm volatile("{.reg .pred p, q; .reg .u32 c; mov.u32 c, 0;\n"
                 "W: mbarrier.try_wait.parity.shared::cta.b64 p, [%0], %1;\n"
                 "@p bra D;\n add.u32 c, c, 1; setp.lt.u32 q, c, %2;\n @q bra W;\n D:\n}" ::"r"(b), "r"(par), "n"(SPIN_LIM) : "memory");
}
constexpr unsigned LONG_LIM = 1u << 17;
__device__ __forceinline__ void mbar_wait_long(uint32_t b, uint32_t par) {
    asm volatile("{.reg .pred p, q; .reg .u32 c; mov.u32 c, 0;\n"
                 "W: mbarrier.try_wait.parity.shared::cta.b64 p, [%0], %1;\n"
                 "@p bra D;\n add.u32 c, c, 1; setp.lt.u32 q, c, %2;\n @q bra W;\n D:\n}" ::"r"(b), "r"(par), "n"(LONG_LIM) : "memory");
}
__device__ __forceinline__ void cluster_sync() { asm volatile("barrier.cluster.arrive.aligned; barrier.cluster.wait.aligned;" ::: "memory"); }
__device__ __forceinline__ void fence_async_smem() { asm volatile("fence.proxy.async.shared::cta;" ::: "memory"); }
__device__ __forceinline__ void ldsm4(uint32_t* r, uint32_t a) { asm volatile("ldmatrix.sync.aligned.m8n8.x4.shared.b16 {%0,%1,%2,%3},[%4];" : "=r"(r[0]), "=r"(r[1]), "=r"(r[2]), "=r"(r[3]) : "r"(a) : "memory"); }
__device__ __forceinline__ void ldsm4t(uint32_t* r, uint32_t a) { asm volatile("ldmatrix.sync.aligned.m8n8.x4.trans.shared.b16 {%0,%1,%2,%3},[%4];" : "=r"(r[0]), "=r"(r[1]), "=r"(r[2]), "=r"(r[3]) : "r"(a) : "memory"); }
__device__ __forceinline__ void stsm1(uint32_t a, uint32_t r0) { asm volatile("stmatrix.sync.aligned.m8n8.x1.shared.b16 [%0],{%1};" ::"r"(a), "r"(r0) : "memory"); }
__device__ __forceinline__ void stsm2t(uint32_t a, uint32_t r0, uint32_t r1) { asm volatile("stmatrix.sync.aligned.m8n8.x2.trans.shared.b16 [%0],{%1,%2};" ::"r"(a), "r"(r0), "r"(r1) : "memory"); }
__device__ __forceinline__ void stsm4t(uint32_t a, uint32_t r0, uint32_t r1, uint32_t r2, uint32_t r3) { asm volatile("stmatrix.sync.aligned.m8n8.x4.trans.shared.b16 [%0],{%1,%2,%3,%4};" ::"r"(a), "r"(r0), "r"(r1), "r"(r2), "r"(r3) : "memory"); }
__device__ __forceinline__ void sts32(uint32_t a, uint32_t v) { asm volatile("st.shared.b32 [%0], %1;" ::"r"(a), "r"(v) : "memory"); }
__device__ __forceinline__ void sts64(uint32_t a, uint32_t x, uint32_t y) { asm volatile("st.shared.v2.b32 [%0], {%1,%2};" ::"r"(a), "r"(x), "r"(y) : "memory"); }
__device__ __forceinline__ void sts128(uint32_t a, uint32_t x, uint32_t y, uint32_t z, uint32_t w) { asm volatile("st.shared.v4.b32 [%0], {%1,%2,%3,%4};" ::"r"(a), "r"(x), "r"(y), "r"(z), "r"(w) : "memory"); }
__device__ __forceinline__ void lds64(uint32_t* r, uint32_t a) { asm volatile("ld.shared.v2.b32 {%0,%1},[%2];" : "=r"(r[0]), "=r"(r[1]) : "r"(a) : "memory"); }
__device__ __forceinline__ float2 lds64f(uint32_t a) { float2 v; asm volatile("ld.shared.v2.f32 {%0,%1},[%2];" : "=f"(v.x), "=f"(v.y) : "r"(a) : "memory"); return v; }
__device__ __forceinline__ void lds128(uint32_t* r, uint32_t a) { asm volatile("ld.shared.v4.b32 {%0,%1,%2,%3},[%4];" : "=r"(r[0]), "=r"(r[1]), "=r"(r[2]), "=r"(r[3]) : "r"(a) : "memory"); }
__device__ __forceinline__ void st_async64(uint32_t a, uint32_t x, uint32_t y, uint32_t bar) {
    asm volatile("st.async.weak.shared::cluster.mbarrier::complete_tx::bytes.v2.b32 [%0], {%1,%2}, [%3];" ::"r"(a), "r"(x), "r"(y), "r"(bar) : "memory");
}
__device__ __forceinline__ void st_async32(uint32_t a, uint32_t x, uint32_t bar) {
    asm volatile("st.async.weak.shared::cluster.mbarrier::complete_tx::bytes.b32 [%0], %1, [%2];" ::"r"(a), "r"(x), "r"(bar) : "memory");
}
__device__ __forceinline__ void ldsm2(uint32_t* r, uint32_t a) { asm volatile("ldmatrix.sync.aligned.m8n8.x2.shared.b16 {%0,%1},[%2];" : "=r"(r[0]), "=r"(r[1]) : "r"(a) : "memory"); }
__device__ __forceinline__ uint32_t pack_f16_sat(float lo, float hi) { uint32_t r; asm("cvt.rn.satfinite.f16x2.f32 %0, %1, %2;" : "=r"(r) : "f"(hi), "f"(lo)); return r; }
__device__ __forceinline__ __half2 as_h2(uint32_t x) { return *reinterpret_cast<__half2*>(&x); }
__device__ __forceinline__ uint32_t as_u32(__half2 x) { return *reinterpret_cast<uint32_t*>(&x); }
__device__ __forceinline__ uint32_t pack_bf16(float lo, float hi) { uint32_t r; asm("cvt.rn.bf16x2.f32 %0, %1, %2;" : "=r"(r) : "f"(hi), "f"(lo)); return r; }
__device__ __forceinline__ float ex2(float x) { float r; asm("ex2.approx.ftz.f32 %0, %1;" : "=f"(r) : "f"(x)); return r; }
__device__ __forceinline__ float rcp(float x) { float r; asm("rcp.approx.ftz.f32 %0, %1;" : "=f"(r) : "f"(x)); return r; }
__device__ __forceinline__ void mma16(float* d, const uint32_t* a, uint32_t b0, uint32_t b1) {
    asm volatile("mma.sync.aligned.m16n8k16.row.col.f32.bf16.bf16.f32 {%0,%1,%2,%3},{%4,%5,%6,%7},{%8,%9},{%0,%1,%2,%3};"
                 : "+f"(d[0]), "+f"(d[1]), "+f"(d[2]), "+f"(d[3]) : "r"(a[0]), "r"(a[1]), "r"(a[2]), "r"(a[3]), "r"(b0), "r"(b1));
}
__device__ __forceinline__ void mma16z(float* d, const uint32_t* a, uint32_t b0, uint32_t b1) {
    asm volatile("mma.sync.aligned.m16n8k16.row.col.f32.bf16.bf16.f32 {%0,%1,%2,%3},{%4,%5,%6,%7},{%8,%9},{%10,%10,%10,%10};"
                 : "=f"(d[0]), "=f"(d[1]), "=f"(d[2]), "=f"(d[3]) : "r"(a[0]), "r"(a[1]), "r"(a[2]), "r"(a[3]), "r"(b0), "r"(b1), "f"(0.f));
}
__device__ __forceinline__ void mma8(float* d, uint32_t a0, uint32_t a1, uint32_t b0) {
    asm volatile("mma.sync.aligned.m16n8k8.row.col.f32.bf16.bf16.f32 {%0,%1,%2,%3},{%4,%5},{%6},{%0,%1,%2,%3};"
                 : "+f"(d[0]), "+f"(d[1]), "+f"(d[2]), "+f"(d[3]) : "r"(a0), "r"(a1), "r"(b0));
}
template <int ACC>
__device__ __forceinline__ void mma_sp(float* d, const uint32_t* a, const uint32_t* b) {
    if (ACC)
        asm volatile("mma.sp::ordered_metadata.sync.aligned.m16n8k32.row.col.f32.bf16.bf16.f32 {%0,%1,%2,%3},{%4,%5,%6,%7},{%8,%9,%10,%11},{%0,%1,%2,%3},%12,0x0;"
                     : "+f"(d[0]), "+f"(d[1]), "+f"(d[2]), "+f"(d[3])
                     : "r"(a[0]), "r"(a[1]), "r"(a[2]), "r"(a[3]), "r"(b[0]), "r"(b[1]), "r"(b[2]), "r"(b[3]), "r"(0xEEEE4444u));
    else
        asm volatile("mma.sp::ordered_metadata.sync.aligned.m16n8k32.row.col.f32.bf16.bf16.f32 {%0,%1,%2,%3},{%4,%5,%6,%7},{%8,%9,%10,%11},{%13,%13,%13,%13},%12,0x0;"
                     : "=f"(d[0]), "=f"(d[1]), "=f"(d[2]), "=f"(d[3])
                     : "r"(a[0]), "r"(a[1]), "r"(a[2]), "r"(a[3]), "r"(b[0]), "r"(b[1]), "r"(b[2]), "r"(b[3]), "r"(0xEEEE4444u), "f"(0.f));
}
__device__ __forceinline__ void mbar_arrive_if0(uint32_t b, uint32_t z) { asm volatile("{.reg .pred p; setp.eq.u32 p, %1, 0; @p mbarrier.arrive.shared::cta.b64 _, [%0];}" ::"r"(b), "r"(z) : "memory"); }
__device__ __forceinline__ void mbar_expect_if0(uint32_t b, uint32_t tx, uint32_t z) { asm volatile("{.reg .pred p; setp.eq.u32 p, %2, 0; @p mbarrier.arrive.expect_tx.shared::cta.b64 _, [%0], %1;}" ::"r"(b), "r"(tx), "r"(z) : "memory"); }
__device__ __forceinline__ float lds32f(uint32_t a) { float v; asm volatile("ld.shared.f32 %0,[%1];" : "=f"(v) : "r"(a) : "memory"); return v; }
__device__ __forceinline__ void wg_fence() { asm volatile("wgmma.fence.sync.aligned;" ::: "memory"); }
__device__ __forceinline__ void wg_commit() { asm volatile("wgmma.commit_group.sync.aligned;" ::: "memory"); }
template <int N> __device__ __forceinline__ void wg_wait() { asm volatile("wgmma.wait_group.sync.aligned %0;" ::"n"(N) : "memory"); }
__device__ __forceinline__ void delay(unsigned n) { if (n) { const unsigned t0 = clk(); while (clk() - t0 < n) {} } }
template <int ACC, uint32_t DHI = 0x40000040u>
__device__ __forceinline__ void wg_rs_n32(float* d, const uint32_t* a, uint32_t dlo) {
    if (ACC)
        asm volatile("{.reg .b64 db; mov.b64 db, {%20, %21};\n"
                     "wgmma.mma_async.sync.aligned.m64n32k16.f32.bf16.bf16 {%0,%1,%2,%3,%4,%5,%6,%7,%8,%9,%10,%11,%12,%13,%14,%15},{%16,%17,%18,%19},db,1,1,1,0;}"
                     : "+f"(d[0]), "+f"(d[1]), "+f"(d[2]), "+f"(d[3]), "+f"(d[4]), "+f"(d[5]), "+f"(d[6]), "+f"(d[7]),
                       "+f"(d[8]), "+f"(d[9]), "+f"(d[10]), "+f"(d[11]), "+f"(d[12]), "+f"(d[13]), "+f"(d[14]), "+f"(d[15])
                     : "r"(a[0]), "r"(a[1]), "r"(a[2]), "r"(a[3]), "r"(dlo), "r"(DHI));
    else
        asm volatile("{.reg .b64 db; mov.b64 db, {%20, %21};\n"
                     "wgmma.mma_async.sync.aligned.m64n32k16.f32.bf16.bf16 {%0,%1,%2,%3,%4,%5,%6,%7,%8,%9,%10,%11,%12,%13,%14,%15},{%16,%17,%18,%19},db,0,1,1,0;}"
                     : "=f"(d[0]), "=f"(d[1]), "=f"(d[2]), "=f"(d[3]), "=f"(d[4]), "=f"(d[5]), "=f"(d[6]), "=f"(d[7]),
                       "=f"(d[8]), "=f"(d[9]), "=f"(d[10]), "=f"(d[11]), "=f"(d[12]), "=f"(d[13]), "=f"(d[14]), "=f"(d[15])
                     : "r"(a[0]), "r"(a[1]), "r"(a[2]), "r"(a[3]), "r"(dlo), "r"(DHI));
}
__device__ __forceinline__ uint32_t desc_lo(uint32_t addr) { return ((addr & 0x3FFFF) >> 4) | (1u << 16); }
__device__ __forceinline__ void tma2d(uint32_t dst, const CUtensorMap* m, int c0, int c1, uint32_t bar) {
    asm volatile("cp.async.bulk.tensor.2d.shared::cluster.global.mbarrier::complete_tx::bytes [%0], [%1, {%2,%3}], [%4];"
                 ::"r"(dst), "l"(m), "r"(c0), "r"(c1), "r"(bar) : "memory");
}
__device__ __forceinline__ void tma3d(uint32_t dst, const CUtensorMap* m, int c0, int c1, int c2, uint32_t bar) {
    asm volatile("cp.async.bulk.tensor.3d.shared::cluster.global.mbarrier::complete_tx::bytes [%0], [%1, {%2,%3,%4}], [%5];"
                 ::"r"(dst), "l"(m), "r"(c0), "r"(c1), "r"(c2), "r"(bar) : "memory");
}
__device__ __forceinline__ void tma3d_mc(uint32_t dst, const CUtensorMap* m, int c0, int c1, int c2, uint32_t bar, uint16_t mask) {
    asm volatile("cp.async.bulk.tensor.3d.shared::cluster.global.mbarrier::complete_tx::bytes.multicast::cluster [%0], [%1, {%2,%3,%4}], [%5], %6;"
                 ::"r"(dst), "l"(m), "r"(c0), "r"(c1), "r"(c2), "r"(bar), "h"(mask) : "memory");
}
__device__ __forceinline__ void bulk_g2s_mc(uint32_t dst, const void* src, uint32_t bytes, uint32_t bar, uint16_t mask) {
    asm volatile("cp.async.bulk.shared::cluster.global.mbarrier::complete_tx::bytes.multicast::cluster [%0], [%1], %2, [%3], %4;"
                 ::"r"(dst), "l"(src), "r"(bytes), "r"(bar), "h"(mask) : "memory");
}
__device__ __forceinline__ void tma2d_prefetch(const CUtensorMap* m, int c0, int c1) {
    asm volatile("cp.async.bulk.prefetch.tensor.2d.L2.global [%0, {%1,%2}];" ::"l"(m), "r"(c0), "r"(c1) : "memory");
}
__device__ __forceinline__ void bulk_s2c(uint32_t dst, uint32_t src, uint32_t bytes, uint32_t bar) {
    asm volatile("cp.async.bulk.shared::cluster.shared::cta.mbarrier::complete_tx::bytes [%0], [%1], %2, [%3];" ::"r"(dst), "r"(src), "r"(bytes), "r"(bar) : "memory");
}
__device__ __forceinline__ void bulk_s2g(void* dst, uint32_t src, uint32_t bytes) {
    asm volatile("cp.async.bulk.global.shared::cta.bulk_group [%0], [%1], %2;" ::"l"(dst), "r"(src), "r"(bytes) : "memory");
}
__device__ __forceinline__ void bulk_commit() { asm volatile("cp.async.bulk.commit_group;" ::: "memory"); }
__device__ __forceinline__ void bulk_wait0() { asm volatile("cp.async.bulk.wait_group 0;" ::: "memory"); }
__device__ __forceinline__ uint4 ld_poll(const void* p) {
    uint4 v;
    asm volatile("ld.relaxed.gpu.global.v4.u32 {%0,%1,%2,%3},[%4];" : "=r"(v.x), "=r"(v.y), "=r"(v.z), "=r"(v.w) : "l"(p) : "memory");
    return v;
}
template <int IMM>
__device__ __forceinline__ void ld_poll_at(uint4& v, const void* p) {
    asm volatile("ld.relaxed.gpu.global.v4.u32 {%0,%1,%2,%3},[%4+%5];" : "=r"(v.x), "=r"(v.y), "=r"(v.z), "=r"(v.w) : "l"(p), "n"(IMM) : "memory");
}
__device__ __forceinline__ void look(uint4 (&v)[6], const void* p) {
    ld_poll_at<0>(v[0], p); ld_poll_at<16384>(v[1], p); ld_poll_at<64>(v[2], p);
    ld_poll_at<16384 + 64>(v[3], p); ld_poll_at<128>(v[4], p); ld_poll_at<16384 + 128>(v[5], p);
}
__device__ __forceinline__ unsigned ld_acquire(const unsigned* p) { unsigned v; asm volatile("ld.acquire.gpu.global.u32 %0,[%1];" : "=r"(v) : "l"(p) : "memory"); return v; }
__device__ __forceinline__ void red_release(unsigned* p, unsigned v) { asm volatile("red.release.gpu.global.add.u32 [%0], %1;" ::"l"(p), "r"(v) : "memory"); }

__device__ __forceinline__ void publish(unsigned* p) {
    asm volatile("fence.proxy.async.global;" ::: "memory");
    asm volatile("red.relaxed.gpu.global.add.u32 [%0], 1;" ::"l"(p) : "memory");
}
template <int ID, int N> __device__ __forceinline__ void bar_sync() { asm volatile("bar.sync %0, %1;" ::"n"(ID), "n"(N) : "memory"); }
template <int ID, int N> __device__ __forceinline__ void bar_arrive() { asm volatile("bar.arrive %0, %1;" ::"n"(ID), "n"(N) : "memory"); }
__device__ __forceinline__ void cluster_arrive() { asm volatile("barrier.cluster.arrive.relaxed.aligned;" ::: "memory"); }
__device__ __forceinline__ void cluster_wait() { asm volatile("barrier.cluster.wait.aligned;" ::: "memory"); }

constexpr uint32_t XB_BYTES = 36864;
constexpr uint32_t S_XB = 0;
constexpr uint32_t S_QM = 73728;
constexpr uint32_t S_KM = 74752;
constexpr uint32_t S_OM = 75776;
constexpr uint32_t S_SP = 77824;
constexpr uint32_t S_SUM = 80384;
constexpr uint32_t S_TGT = 81408;
constexpr uint32_t S_VM = 147456;
constexpr uint32_t S_QX = 86016;
constexpr uint32_t S_PX = S_QX;
constexpr uint32_t S_KX = 94208;
constexpr uint32_t S_VX = 102400;
constexpr uint32_t S_SX = 135168;
constexpr uint32_t S_OX = 155648;
constexpr uint32_t S_MEM = 172032;
constexpr uint32_t S_WO = 181248;
constexpr uint32_t S_BAR = 230400;
constexpr uint32_t A_SMEM = S_BAR + 128;
__host__ __device__ constexpr uint32_t s_w(int c) { return c == 0 ? S_WO : 73728 + (c - 1) * 49152; }
constexpr uint32_t B_W = S_BAR, B_WO = S_BAR + 24, B_X = S_BAR + 32, B_S = S_BAR + 48, B_VX = S_BAR + 56, B_SX = S_BAR + 72, B_M = S_BAR + 88, B_T = S_BAR + 112;
constexpr int NB_QK = 1, NB_O = 2, NB_RED = 3, NB_P = 4, NB_AUX = 5, NB_PRO = 6, NB_X = 7, NB_GO = 8, NB_L = 9;

constexpr float SM_SCALE = 0.08838834764831845f * 1.4426950408889634f;
constexpr uint32_t ONES = 0x3F803F80u;
constexpr uint32_t FULL_COUNT = 0x4200u;
#define XLIM NSEG
#define XTMA_DELAY 0
#define SX_DELAY 0
#define TGT_NS 1120
#define LOOK_NS 100
#define RCP_AT 2
#define NCH 2
#define POLL_AT 1
#define OX_DELAY 0
#define XTMA_NS 50
#define REG_MAIN0 232
#define REG_MAIN1 232
#define REG_AUX 40

#define PV_MODE 1
#define OX_AT 1
#define FLAG_NS 40
#define VX_EARLY 0
#define PROBS_EARLY 0
#define OFF 0
static_assert(REG_MAIN0 + REG_MAIN1 + REG_AUX <= 504, "the three warpgroups share 3 x 168 registers");
#define HSTAMP(i) do {} while (0)
#define HSTAMP2(i) do {} while (0)
#define TSTAMP(i, e) do {} while (0)

__device__ __forceinline__ void load_scores(uint32_t a, __half2 (&hs)[5]) {
    uint32_t r[10];
    ldsm4(r, a);
    ldsm4(r + 4, a + 512);
    ldsm2(r + 8, a + 1024);
    const __half2 hf = as_h2(0x38003800u);
#pragma unroll
    for (int T = 0; T < 5; T++) hs[T] = __hfma2(as_h2(r[2 * T]), hf, __hmul2(as_h2(r[2 * T + 1]), hf));
}
__device__ __forceinline__ void softmax_exp(const __half2 (&hs)[5], float (&ev)[10]) {
    __half2 m = __hmax2(__hmax2(__hmax2(hs[0], hs[1]), __hmax2(hs[2], hs[3])), hs[4]);
    const uint32_t mu = as_u32(m);
    const uint32_t m1 = __shfl_xor_sync(0xffffffffu, mu, 1), m2 = __shfl_xor_sync(0xffffffffu, mu, 2), m3 = __shfl_xor_sync(0xffffffffu, mu, 3);
    m = __hmax2(__hmax2(m, as_h2(m1)), __hmax2(as_h2(m2), as_h2(m3)));
    const float mc = -fmaxf(__low2float(m), __high2float(m)) * (2.f * SM_SCALE);
#pragma unroll
    for (int T = 0; T < 5; T++) {
        ev[2 * T] = ex2(fmaf(__low2float(hs[T]), 2.f * SM_SCALE, mc));
        ev[2 * T + 1] = ex2(fmaf(__high2float(hs[T]), 2.f * SM_SCALE, mc));
    }
}

__device__ __forceinline__ void x_scores(uint32_t sb, int seg, int wq, uint32_t L16, float (&ev)[10]) {
    __half2 hs[5];
    load_scores(sb + S_SX + (seg & 1) * 5120 + wq * 1280 + L16, hs);
    const int dg = (int)(L16 >> 6) - (int)((L16 >> 3) & 6) + 8 * wq;
#pragma unroll
    for (int T = 0; T < 4; T++) {
        uint32_t u = as_u32(hs[T]);
        if (dg < 8 * T + 1) u = (u & 0xFFFFu) | 0xFC000000u;
        if (dg < 8 * T) u = 0xFC00FC00u;
        hs[T] = as_h2(u);
    }
    softmax_exp(hs, ev);
}
__device__ __forceinline__ void x_probs(uint32_t sb, int seg, int wq, uint32_t L16, const float (&ev)[10]) {
    float l = ((ev[0] + ev[1]) + (ev[2] + ev[3])) + ((ev[4] + ev[5]) + (ev[6] + ev[7])) + (ev[8] + ev[9]);
    const float l1 = __shfl_xor_sync(0xffffffffu, l, 1), l2 = __shfl_xor_sync(0xffffffffu, l, 2), l3 = __shfl_xor_sync(0xffffffffu, l, 3);
    const float r = rcp((l + l1) + (l2 + l3));
    const uint32_t a = sb + S_PX + (seg & 1) * 4096 + wq * 640 + (L16 >> 2);
#pragma unroll
    for (int i = 0; i < 5; i++) sts32(a + i * 128, pack_bf16(ev[2 * i] * r, ev[2 * i + 1] * r));
}
__device__ __forceinline__ void x_pv_load(uint32_t sb, int seg, int w, uint32_t L16, uint32_t (&a)[3][4]) {
    lds128(a[0], sb + S_VX + (seg & 3) * 8192 + w * 1024 + L16);
    lds128(a[1], sb + S_VX + (seg & 3) * 8192 + w * 1024 + 512 + L16);
    lds64(a[2], sb + S_VM + (seg & 3) * 2048 + w * 256 + (L16 >> 1));
    a[2][2] = 0; a[2][3] = 0;
}
__device__ __forceinline__ void x_pv_run(uint32_t sb, int seg, int w, uint32_t L16, const uint32_t (&a)[3][4]) {
    const uint32_t d = ((sb + S_PX + (seg & 1) * 4096) & 0x3FFFF) >> 4;
    float o[16];
    wg_fence();
    wg_rs_n32<0, 40>(o, a[0], d | (8u << 16));
    wg_rs_n32<1, 40>(o, a[1], (d + 16) | (8u << 16));
    wg_rs_n32<1, 40>(o, a[2], d + 32);
    wg_commit();
    wg_wait<0>();
    const uint32_t ox = sb + S_OX + (seg & 1) * 8192 + (w >> 2) * 4096 + (L16 & 0x100) * 4 + (L16 & 0x70) * 8 +
                        ((((w & 3) * 32) | ((L16 >> 3) & 0x10)) ^ (L16 & 0x70));
    stsm4t(ox, pack_bf16(o[0], o[1]), pack_bf16(o[2], o[3]), pack_bf16(o[4], o[5]), pack_bf16(o[6], o[7]));
    stsm4t(ox + 2048, pack_bf16(o[8], o[9]), pack_bf16(o[10], o[11]), pack_bf16(o[12], o[13]), pack_bf16(o[14], o[15]));
}
__device__ __forceinline__ void ox_publish(int seg, uint32_t h) { bulk_wait0(); publish(&g_flag[seg * 4 + (h >> 3)]); }
__device__ __forceinline__ void ox_store(uint32_t sb, int seg, uint32_t h) {
    fence_async_smem();
    bulk_s2g(g_ox + (seg * NH + h) * 512, sb + S_OX + (seg & 1) * 8192, 8192);
    bulk_commit();
}

__device__ __forceinline__ void x_epilogue(uint32_t sb, const float (&d)[16], int seg, bool isv, int w, uint32_t L16) {
    uint32_t pk[8];
#pragma unroll
    for (int i = 0; i < 8; i++) pk[i] = pack_bf16(d[2 * i], d[2 * i + 1]);
    if (!isv) {
        const uint32_t a = sb + S_QX + (w >> 2) * 8192 + (seg & 1) * 4096 + (w & 3) * 256 + (L16 & 0xF0) + (L16 & 0x100) * 4;
        stsm4t(a, pk[0], pk[1], pk[2], pk[3]);
        stsm4t(a + 2048, pk[4], pk[5], pk[6], pk[7]);
    } else {
        const uint32_t a = sb + S_VX + (seg & 3) * 8192 + w * 1024 + L16;
        sts128(a, pk[0], pk[1], pk[2], pk[3]);
        sts128(a + 512, pk[4], pk[5], pk[6], pk[7]);
    }
}

template <int K0, int K1>
__device__ __forceinline__ void x_project(float (&d)[16], const uint32_t (&wA)[36][4], uint32_t desc) {
#pragma unroll
    for (int i = K0; i < K1; i++) {
        const uint32_t db = desc + (((i >> 2) * 4096 + (i & 3) * 32) >> 4);
        if (i == 0) wg_rs_n32<0>(d, wA[i], db); else wg_rs_n32<1>(d, wA[i], db);
    }
}

__device__ __forceinline__ void mem_scores(uint32_t sb, uint32_t peerA, uint32_t peerB, uint32_t off, const uint32_t (&q0)[4], const uint32_t (&q1)[4],
                                           const uint32_t (&k0)[4], const uint32_t (&k1)[4]) {
    float e0[4], o0[4], e1[4], o1[4];
    mma16z(e0, q0, k0[0], k0[1]);
    mma16z(o0, q0, k0[2], k0[3]);
    mma16z(e1, q1, k1[0], k1[1]);
    mma16z(o1, q1, k1[2], k1[3]);
    const uint32_t sc = pack_f16_sat((e0[0] + o0[2]) + (e1[0] + o1[2]), (e0[1] + o0[3]) + (e1[1] + o1[3]));
    st_async32(peerB + off, sc, peerB + B_S);
    st_async32(peerA + off, sc, peerA + B_S);
    sts32(sb + off, sc);
    __syncwarp();
}

__device__ __forceinline__ unsigned post_time(int s, uint32_t L16) {
    delay(1);
    const unsigned t = gtime() | 1;
    if (L16 == 0) asm volatile("st.relaxed.gpu.global.u32 [%0], %1;" ::"l"(g_time + s * 96 + blockIdx.x), "r"(t) : "memory");
    return t;
}
__device__ __forceinline__ void plan_look(uint32_t sb, int s, uint32_t L16, unsigned t) {
    const char* p = reinterpret_cast<const char*>(g_time) + s * 384 + (L16 < 384 ? L16 : 0);
    uint4 v;
    unsigned c = 0;
    do { v = ld_poll(p); } while (__any_sync(0xffffffffu, (v.x & v.y & v.z & v.w & 1) == 0) && ++c < SPIN_LIM);
    const int d = max(max((int)(v.x - t), (int)(v.y - t)), max((int)(v.z - t), (int)(v.w - t)));
    const unsigned tgt = t + min(__reduce_max_sync(0xffffffffu, d), 20000) + TGT_NS;
    if (L16 < 48) { const uint32_t r = mapa(sb, L16 >> 4); st_async32(r + S_TGT, tgt, r + B_T); }
}

template <int ROLE>
__device__ __forceinline__ void chain_main(const uint32_t sb, const uint32_t lane16, const int wq, const uint32_t j, const uint32_t h,
                                           const uint32_t peerA, const uint32_t peerB, char* const acc) {
    uint32_t L16 = lane16;
    constexpr bool isv = ROLE >= 2;
    constexpr int wg = ROLE & 1;
    const int w = wg * 4 + wq;
    const uint32_t xdesc = desc_lo(sb + S_XB);
    const uint32_t zero = h >> 20;
    uint32_t wA[36][4], woA[8][4], woB[4][4];
    float xd[16];
    {
        const int m = L16 >> 7, r = (L16 >> 4) & 7;
        const int blk = (ROLE == 1) ? ((wq & 2) * 2 + (wq & 1) + (m & 1) * 2) : (2 * wq + (m & 1));
        const uint32_t a = sb + wg * 24576 + ((m >> 1) * 8 + r) * 128 + ((blk ^ r) << 4);
        mbar_wait(sb + B_X, 0);
#pragma unroll
        for (int c = 0; c < 3; c++) {
            mbar_wait(sb + B_W + 8 * c, 0);
#pragma unroll
            for (int i = 0; i < 12; i++) ldsm4t(wA[12 * c + i], a + s_w(c) + i * 2048);
            if (c == 0) bar_arrive<NB_PRO, 384>();
            if (c == 2) { bar_sync<NB_O, 256>(); cluster_arrive(); }
            wg_fence();
            if (c == 0) x_project<0, 12>(xd, wA, xdesc);
            if (c == 1) x_project<12, 24>(xd, wA, xdesc);
            if (c == 2) x_project<24, 36>(xd, wA, xdesc);
            wg_commit();
            wg_wait<0>();
        }
        x_epilogue(sb, xd, 0, isv, w, L16);
        bar_arrive<NB_RED, 384>();
        mbar_wait(sb + B_WO, 0);
        const int ca = 3 * w + (m & 1), cb = 3 * w + 2;
        const uint32_t aA = sb + S_WO + (ca >> 3) * 16384 + ((m >> 1) * 8 + r) * 128 + (((ca & 7) ^ r) << 4);
        const int eB = ((m & 2) + ((r >> 1) & 1)) * 8 + 4 * (m & 1) + 2 * (r >> 2) + (r & 1);
        const uint32_t aB = sb + S_WO + (cb >> 3) * 16384 + eB * 128 + (((cb & 7) ^ (eB & 7)) << 4);
#pragma unroll
        for (int i = 0; i < 8; i++) ldsm4t(woA[i], aA + i * 2048);
#pragma unroll
        for (int i = 0; i < 4; i++) ldsm4t(woB[i], aB + i * 4096);
        mbar_wait(sb + B_X + 8, 0);
        cluster_wait();
        bar_sync<NB_O, 256>();
        wg_fence();
        x_project<0, 36>(xd, wA, xdesc + (XB_BYTES >> 4));
        wg_commit();
    }
    int s = 0;
#pragma unroll 1
    while (true) {
        const uint32_t par = s & 1;
        const uint32_t kx = sb + S_KX + par * 4096;
        asm volatile("" : "+r"(L16));
        if (OX_AT == 3 && ROLE == 3 && wq == 0 && s >= 1) {
            bar_sync<NB_L, 160>();
            if (L16 == 0 && s >= 3) ox_store(sb, s - 3, h);
            __syncwarp();
        }
        wg_wait<0>();
        x_epilogue(sb, xd, s + 1, isv, w, L16);
        float c0[4], c1[4];
        uint32_t k0[4], k1[4], pva[3][4];
        {
            const uint32_t a = sb + S_MEM + L16;
            constexpr int CH = 18 / NCH;
            uint32_t b[3][4];
            bool ready = true;
            mbar_wait(sb + B_M, par);
            ldsm4(b[0], a);
            ldsm4(b[1], a + 512);
            bar_arrive<NB_GO, 288>();
#pragma unroll
            for (int i = 0; i < 18; i++) {
                if ((i + 4) % CH == 0 && i + 4 < 18) ready = mbar_test(sb + B_M + ((i + 4) / CH) * 8, par);
                if ((i + 2) % CH == 0 && i + 2 < 18) { if (__builtin_expect(!ready, 0)) mbar_wait(sb + B_M + ((i + 2) / CH) * 8, par); }
                if (i + 2 < 18) ldsm4(b[(i + 2) % 3], a + (i + 2) * 512);
                if (ROLE == 0 && i == 16) ldsm4(k0, kx + wq * 1024 + L16);
                if (ROLE == 0 && i == 17) ldsm4(k1, kx + wq * 1024 + 512 + L16);
                if (PV_MODE == 0 && !(OFF & 8) && isv && i == 17) x_pv_load(sb, s + 2, w, L16, pva);
                if (i == 0) { mma16z(c0, wA[0], b[0][0], b[0][1]); mma16z(c1, wA[1], b[0][2], b[0][3]); }
                else { mma16(c0, wA[2 * i], b[i % 3][0], b[i % 3][1]); mma16(c1, wA[2 * i + 1], b[i % 3][2], b[i % 3][3]); }
            }
        }
        const uint32_t p0 = pack_bf16(c0[0] + c1[0], c0[1] + c1[1]), p1 = pack_bf16(c0[2] + c1[2], c0[3] + c1[3]);
        if (!isv) {
            stsm2t(sb + S_QM + w * 256 + L16, p0, p1);
            bar_sync<NB_QK, 384>();
            if (ROLE == 0) {
                uint32_t q0[4], q1[4];
                ldsm4(q0, sb + S_QM + L16);
                ldsm4(q1, sb + S_QM + 512 + L16);
                mem_scores(sb, peerA, peerB, S_SP + j * 128 + wq * 256 + (L16 >> 2), q0, q1, k0, k1);
                mbar_arrive_if0(sb + B_S, L16);
            } else {
                if (s + 2 < XLIM) mbar_wait(sb + B_X + par * 8, ((s + 2) >> 1) & 1);
                if (wq != 0 && !(OFF & 16)) {
                    const int rt = (wq == 3) ? 0 : 1;
                    const uint32_t qa = sb + S_QX + par * 4096 + rt * 2048 + (L16 & 0x80) * 8 + (L16 & 0x170);
                    const uint32_t kb0 = (wq == 2 ? kx + 2048 : sb + S_KM) + L16;
                    const uint32_t kb1 = (wq == 2 ? kx + 3072 : kx) + L16;
                    const uint32_t kb2 = kx + 1024 + L16;
                    float a0[4], a1[4], a2[4];
#pragma unroll
                    for (int hf = 0; hf < 2; hf++) {
                        uint32_t qa0[4], qa1[4], b[4];
                        ldsm4(qa0, qa + hf * 512);
                        ldsm4(qa1, qa + hf * 512 + 128);
                        ldsm4(b, kb0 + hf * 512);
                        if (hf == 0) mma16z(a0, qa0, b[0], b[1]); else mma16(a0, qa0, b[0], b[1]);
                        mma16(a0, qa1, b[2], b[3]);
                        ldsm4(b, kb1 + hf * 512);
                        if (hf == 0) mma16z(a1, qa0, b[0], b[1]); else mma16(a1, qa0, b[0], b[1]);
                        mma16(a1, qa1, b[2], b[3]);
                        ldsm4(b, kb2 + hf * 512);
                        if (hf == 0) mma16z(a2, qa0, b[0], b[1]); else mma16(a2, qa0, b[0], b[1]);
                        mma16(a2, qa1, b[2], b[3]);
                    }
                    mbar_wait(sb + B_S, par);
                    delay(SX_DELAY);
                    const uint32_t dst = peerB + S_SX + par * 5120 + j * 128 + rt * 2560 + (L16 >> 2);
                    const uint32_t bar = peerB + B_SX + par * 8;
                    const uint32_t T0 = (wq == 2 ? 2 : 4) * 256, T1 = (wq == 2 ? 3 : 0) * 256;
                    st_async32(dst + T0, pack_f16_sat(a0[0], a0[1]), bar);
                    st_async32(dst + 1280 + T0, pack_f16_sat(a0[2], a0[3]), bar);
                    if (wq != 2) st_async32(dst + T1, pack_f16_sat(a1[0], a1[1]), bar);
                    st_async32(dst + 1280 + T1, pack_f16_sat(a1[2], a1[3]), bar);
                    if (wq == 1) st_async32(dst + 256, pack_f16_sat(a2[0], a2[1]), bar);
                    if (wq != 2) st_async32(dst + 1280 + 256, pack_f16_sat(a2[2], a2[3]), bar);
                }
            }
        } else {
            const uint32_t off = S_VM + (s & 3) * 2048 + w * 256 + (L16 >> 1);
            st_async64(peerA + off, p0, p1, peerA + B_S);
            st_async64(peerB + off, p0, p1, peerB + B_S);
            sts64(sb + off, p0, p1);
            __syncwarp();
            mbar_expect_if0(sb + B_S, 160, L16);
            if (PV_MODE == 1 || (PV_MODE == 2 && ROLE == 3)) x_pv_load(sb, s + 2, w, L16, pva);
            if (PV_MODE == 2 && ROLE == 2) bar_arrive<NB_P, 384>(); else bar_sync<NB_P, 384>();
            if (PV_MODE == 2) {
                if (ROLE == 3) { x_pv_run(sb, s + 2, w, L16, pva); x_pv_load(sb, s + 2, wq, L16, pva); x_pv_run(sb, s + 2, wq, L16, pva); }
            } else
            if (!(OFF & 8)) x_pv_run(sb, s + 2, w, L16, pva);
            if (OX_AT == 3 && ROLE == 3 && wq == 0) { if (L16 == 0 && s >= 3) ox_publish(s - 3, h); __syncwarp(); }
            else if (ROLE == 3 && s + 2 < XLIM) mbar_wait(sb + B_X + par * 8, ((s + 2) >> 1) & 1);
        }
        if (s == NSEG - 1) break;
        if (wg == 0) {
            if (!isv) mbar_wait(sb + B_VX + par * 8, (s >> 1) & 1);
            uint32_t va[4][4];
            const uint32_t vx = sb + S_VX + (s & 3) * 8192 + wq * 2048 + L16;
            const uint32_t vm = sb + S_VM + (s & 3) * 2048 + wq * 512 + (L16 >> 1);
            lds128(va[0], vx);
            lds128(va[2], vx + 1024);
            mbar_wait(sb + B_S, par);
            __half2 hs[5];
            load_scores(sb + S_SP + L16, hs);
            float ev[10];
            softmax_exp(hs, ev);
            lds128(va[1], vx + 512);
            lds128(va[3], vx + 1536);
            uint32_t p[5];
#pragma unroll
            for (int i = 0; i < 5; i++) p[i] = pack_bf16(ev[2 * i], ev[2 * i + 1]);
            uint32_t vm0[2], vm1[2];
            const uint32_t ones[4] = {ONES, ONES, ONES, ONES};
            float sum[4], o0[4], o1[4];
            mma16z(o0, va[0], p[0], p[1]);
            mma16z(o1, va[2], p[0], p[1]);
            mma16z(sum, ones, p[0], p[1]);
            lds64(vm0, vm);
            lds64(vm1, vm + 256);
            mma16(o0, va[1], p[2], p[3]);
            mma16(o1, va[3], p[2], p[3]);
            mma16(sum, ones, p[2], p[3]);
            mma8(o0, vm0[0], vm0[1], p[4]);
            mma8(o1, vm1[0], vm1[1], p[4]);
            mma8(sum, ONES, ONES, p[4]);
            stsm4t(sb + S_OM + wq * 512 + L16, pack_bf16(o0[0], o0[1]), pack_bf16(o0[2], o0[3]), pack_bf16(o1[0], o1[1]), pack_bf16(o1[2], o1[3]));
            sts64(sb + S_SUM + wq * 256 + (L16 >> 1), __float_as_uint(sum[0]), __float_as_uint(sum[1]));
        }
        bar_sync<NB_O, 256>();
        {
            float a0[4], a1[4], e[4];
            float2 sc;
            float sr, r0, r1, rr;
#pragma unroll
            for (int i = 0; i < 4; i++) {
                uint32_t b[4];
                ldsm4(b, sb + S_OM + i * 512 + L16);
                if (i == 0) {
                    mma16z(a0, woA[0], b[0], b[1]); mma16z(a1, woA[1], b[2], b[3]);
                    mma_sp<0>(e, b, woB[0]);
                } else {
                    if (i == 1) { sc = lds64f(sb + S_SUM + (L16 >> 1)); sr = lds32f(sb + S_SUM + ((L16 >> 4) & 0x1C)); }
                    const uint32_t z = __float_as_uint(a0[0]) & zero;
                    mma16(a0, woA[2 * i], b[0], b[1]); mma16(a1, woA[2 * i + 1], b[2], b[3]);
                    mma_sp<1>(e, b, woB[i]);
                    if (i == RCP_AT) {
                        r0 = rcp(__uint_as_float(__float_as_uint(sc.x) | z));
                        r1 = rcp(__uint_as_float(__float_as_uint(sc.y) | z));
                        rr = rcp(__uint_as_float(__float_as_uint(sr) | z));
                    }
                }
            }
            asm volatile("" : "+r"(L16));
            char* const rslot = acc + (slot_off(s + 1) + j * 64 + w * 4096) + lane_off(L16);
            asm volatile("red.relaxed.gpu.global.add.noftz.v4.bf16x2 [%0], {%1,%2,%3,%4};"
                         ::"l"(rslot), "r"(pack_bf16((a0[0] + a1[0]) * r0, (a0[1] + a1[1]) * r1)), "r"(pack_bf16((a0[2] + a1[2]) * r0, (a0[3] + a1[3]) * r1)),
                           "r"(pack_bf16((e[0] + e[2]) * rr, (e[1] + e[3]) * rr)), "r"(0x3F80u) : "memory");
        }
        bar_sync<NB_X, 256>();
        wg_fence();
        x_project<0, POLL_AT>(xd, wA, xdesc + par * (XB_BYTES >> 4));
        bar_arrive<NB_RED, 384>();
        x_project<POLL_AT, 36>(xd, wA, xdesc + par * (XB_BYTES >> 4));
        wg_commit();
        s++;
    }
    if (isv) {
        uint32_t pva[3][4];
        x_pv_load(sb, NSEG - 2, w, L16, pva);
        bar_sync<NB_RED, 384>();
        x_pv_run(sb, NSEG - 2, w, L16, pva);
        bar_arrive<NB_QK, 384>();
        x_pv_load(sb, NSEG - 1, w, L16, pva);
        bar_sync<NB_P, 384>();
        x_pv_run(sb, NSEG - 1, w, L16, pva);
        bar_arrive<NB_PRO, 384>();
    }
}

template <bool isv>
__device__ __forceinline__ void chain_aux(const uint32_t sb, const uint32_t lane16, const int wq, const uint32_t j, const uint32_t h,
                                          const uint32_t peerA, const uint32_t peerB, const CUtensorMap* tmWo, const CUtensorMap* tmX,
                                          const bf16* __restrict__ mem0, char* const acc) {
    const int t = wq * 32 + (lane16 >> 4);
    TSTAMP(64, 0);
    cluster_arrive();
    {
        char* z = acc + h * 32768 + j * 64 + (t >> 2) * 256 + (t & 3) * 16;
#pragma unroll
        for (int i = 0; i < 4; i++) *reinterpret_cast<uint4*>(z + i * 8192) = make_uint4(0, 0, 0, 0);
        if (t < 64) g_time[blockIdx.x * 64 + t] = 0;
        if (blockIdx.x == 0) { g_flag[t] = 0; g_flag[128 + t] = 0; }
        for (int i = t; i < 576; i += 128) {
            const uint4 v = *reinterpret_cast<const uint4*>(mem0 + (i & 7) * DM + (i >> 3) * 8);
            sts128(sb + S_MEM + i * 16, v.x, v.y, v.z, v.w);
        }
        __threadfence();
        bar_sync<NB_AUX, 128>();
        if (t == 0) red_release(&g_zero_cnt, 1);
        asm volatile("griddepcontrol.launch_dependents;" ::: "memory");
        bar_sync<NB_PRO, 384>();
        if (t == 0) {
            fence_async_smem();
            mbar_expect(sb + B_WO, 49152);
            for (int b = 0; b < 3; b++) tma2d(sb + S_WO + b * 16384, tmWo, 192 * j + 64 * b, h * 128, sb + B_WO);
        }
        unsigned c = 0;
        while (ld_acquire(&g_zero_cnt) < 96 && ++c < SPIN_LIM) {}
        __syncwarp();
        for (int c2 = 0; c2 < 3; c2++) mbar_arrive_if0(sb + B_M + c2 * 8, lane16);
        cluster_wait();
        bar_sync<NB_RED, 384>();
        if (t == 0) {
            fence_async_smem();
            if (!isv) mbar_expect(sb + B_VX, 8192);
            else {
                bulk_s2c(peerA + S_VX, sb + S_VX, 8192, peerA + B_VX);
                bulk_s2c(peerB + S_VX, sb + S_VX, 8192, peerB + B_VX);
            }
            mbar_expect(sb + B_X, XB_BYTES);
            tma3d(sb + S_XB, tmX, 0, 64, 0, sb + B_X);
        }
        __syncwarp();
    }
    TSTAMP(0, 0);
    uint32_t L16 = lane16;
    const char* slot = acc + wq * 4096 + lane_off(L16);
    float ev[10];
    int s = 0;
#pragma unroll 1
    while (true) {
        const uint32_t par = s & 1;
        asm volatile("" : "+r"(L16));
        if (!isv) {
            if (wq == 0) {
                bar_sync<NB_QK, 384>();
                uint32_t q0[4], q1[4], k0[4], k1[4];
                ldsm4(q0, sb + S_QM + L16);
                ldsm4(k0, sb + S_KM + L16);
                ldsm4(q1, sb + S_QM + 512 + L16);
                ldsm4(k1, sb + S_KM + 512 + L16);
                mem_scores(sb, peerA, peerB, S_SP + j * 128 + 1024 + (L16 >> 2), q0, q1, k0, k1);
                mbar_expect_if0(sb + B_S, 640 + 2048, L16);
            } else if (wq == 3) {
                bar_sync<NB_GO, 288>();
                const unsigned t = post_time(s, L16);
                bar_sync<NB_QK, 384>();
                if (j == 0 && s < NSEG - 1) {
                    if (LOOK_NS) __nanosleep(LOOK_NS);
                    plan_look(sb, s, L16, t);
                }
            } else {
                bar_arrive<NB_QK, 384>();
                if (wq == 2) {
                    if (L16 == 0) {
                        if (s + 3 < XLIM) mbar_expect(sb + B_X + (par ^ 1) * 8, XB_BYTES);
                        mbar_expect(sb + B_VX + (par ^ 1) * 8, (OFF & 2) ? 0 : 8192);
                        mbar_expect(sb + B_T, 4);
                        if (s == 2 && h == 0 && j == 0) g_zero_cnt = 0;
                    }
                } else if (s + 3 < XLIM && j == 1) {
                    mbar_wait(sb + B_S, par);
                    delay(XTMA_DELAY);
                    if (XTMA_NS) __nanosleep(XTMA_NS);
                    if (L16 == 0) tma3d_mc(sb + S_XB + (par ^ 1) * XB_BYTES, tmX, 0, (s + 3) * SEG, 0, sb + B_X + (par ^ 1) * 8, 7);
                }
                __syncwarp();
            }
        } else {
            if (wq == 3) {
                bar_sync<NB_GO, 288>();
                post_time(s, L16);
            } else if (L16 == 0) {
                if (wq == 0) {
                    if (!(OFF & 2) && s >= 1) {
                        bulk_wait0();
                        bulk_g2s_mc(sb + S_VX + (s & 3) * 8192, g_vx + (h * 2 + par) * 512, 8192, sb + B_VX + par * 8, 3);
                    }
                } else if (wq == 1) {
                    if (OX_AT == 0 && s >= 3) ox_publish(s - 3, h);
                    if ((OX_AT == 1 || OX_AT == 2) && s >= 4) ox_publish(s - 4, h);
                } else {
                    mbar_expect(sb + B_SX + par * 8, (OFF & 16) ? 0 : 3584);
                    mbar_expect(sb + B_T, 4);
                    if (s + 3 < XLIM) mbar_expect(sb + B_X + (par ^ 1) * 8, XB_BYTES);
                }
            }
            __syncwarp();
            if (s >= 1) mbar_wait(sb + B_SX + (par ^ 1) * 8, ((s - 1) >> 1) & 1);
            fence_async_smem();
            bar_sync<NB_P, 384>();
            if (OX_AT == 1 && wq == 1) { if (L16 == 0 && s >= 3) ox_store(sb, s - 3, h); __syncwarp(); }
            if (VX_EARLY && wq == 0) {
                if (L16 == 0 && s + 1 < NSEG) {
                    fence_async_smem();
                    bulk_s2g(g_vx + (h * 2 + (par ^ 1)) * 512, sb + S_VX + ((s + 1) & 3) * 8192, 8192);
                    bulk_commit();
                }
                __syncwarp();
            }
            if (!(OFF & 4) || s == NSEG - 1) x_scores(sb, s + 1, wq, L16, ev);
            if (OX_AT == 2 && wq == 1) { if (L16 == 0 && s >= 3) ox_store(sb, s - 3, h); __syncwarp(); }
            if (!VX_EARLY && wq == 0) {
                if (!(OFF & 2) && L16 == 0 && s + 1 < NSEG) {
                    fence_async_smem();
                    bulk_s2g(g_vx + (h * 2 + (par ^ 1)) * 512, sb + S_VX + ((s + 1) & 3) * 8192, 8192);
                    bulk_commit();
                }
                __syncwarp();
            }
        }
        if (PROBS_EARLY && isv) x_probs(sb, s + 1, wq, L16, ev);
        if (s == NSEG - 1) break;
        mbar_wait(sb + B_T, par);
        const unsigned tgt = __float_as_uint(lds32f(sb + S_TGT));
        bar_sync<NB_RED, 384>();
        if (!PROBS_EARLY && isv && !(OFF & 4)) x_probs(sb, s + 1, wq, L16, ev);
        asm volatile("" : "+r"(L16));
        slot += par ? 32768 - 512 : 512;
        while ((int)(gtime() - tgt) < 0) {}
        uint4 v[6];
        look(v, slot);
        if (OX_AT == 3 && isv) bar_arrive<NB_L, 160>();
        if (OX_AT == 0 && !(OFF & 1) && isv && wq == 1 && s >= 2) { delay(OX_DELAY); if (L16 == 0) ox_store(sb, s - 2, h); __syncwarp(); }
        s++;
        const uint32_t ma = sb + S_MEM + wq * 384 + L16;
        unsigned c = 0;
        constexpr int CW = 6 / NCH;
        int done = NCH;
#pragma unroll
        for (int k = 0; k < NCH; k++) {
            uint32_t bad = 0;
#pragma unroll
            for (int i = CW * k; i < CW * k + CW; i++) { stsm2t(ma + i * 1536, v[i].x, v[i].y); stsm1(ma + i * 1536 + 256, v[i].z); bad |= v[i].w ^ FULL_COUNT; }
            const bool again = __any_sync(0xffffffffu, bad != 0);
            mbar_arrive_if0(sb + B_M + k * 8, L16 | (uint32_t)again);
            if (again) { done = k; break; }
        }
        if (done < NCH) {
            uint32_t bad;
            do {
                look(v, slot);
                bad = 0;
#pragma unroll
                for (int i = 0; i < 6; i++) { stsm2t(ma + i * 1536, v[i].x, v[i].y); stsm1(ma + i * 1536 + 256, v[i].z); bad |= v[i].w ^ FULL_COUNT; }
            } while (++c < SPIN_LIM && __any_sync(0xffffffffu, bad != 0));
            __syncwarp();
#pragma unroll
            for (int k = 0; k < NCH; k++) if (k >= done) mbar_arrive_if0(sb + B_M + k * 8, L16);
        }
        TSTAMP(s, c | t_pack);
    }
    if (!isv) {
        mbar_wait(sb + B_VX + 8, ((NSEG - 1) >> 1) & 1);
        mbar_wait(sb + B_S, 1);
    } else {
        if (!PROBS_EARLY) x_probs(sb, NSEG - 2, wq, L16, ev);
        fence_async_smem();
        if ((OX_AT == 1 || OX_AT == 2) && wq == 1) { if (L16 == 0) ox_publish(NSEG - 4, h); __syncwarp(); }
        bar_sync<NB_RED, 384>();
        if (wq == 1 && L16 == 0) ox_store(sb, NSEG - 3, h);
        __syncwarp();
        bar_sync<NB_QK, 384>();
        if (wq == 2 && L16 == 0) ox_store(sb, NSEG - 2, h);
        __syncwarp();
        mbar_wait(sb + B_S, 1);
        mbar_wait(sb + B_SX + 8, ((NSEG - 1) >> 1) & 1);
        x_scores(sb, NSEG - 1, wq, L16, ev);
        x_probs(sb, NSEG - 1, wq, L16, ev);
        fence_async_smem();
        if (wq == 1 && L16 == 0) ox_publish(NSEG - 3, h);
        __syncwarp();
        bar_arrive<NB_P, 384>();
        if (wq == 2) { if (L16 == 0) ox_publish(NSEG - 2, h); __syncwarp(); bar_arrive<NB_PRO, 384>(); }
        else bar_sync<NB_PRO, 384>();
        if (wq == 3 && L16 == 0) { ox_store(sb, NSEG - 1, h); ox_publish(NSEG - 1, h); }
    }
}

__global__ void __launch_bounds__(384, 1)
chain_kernel(const __grid_constant__ CUtensorMap tmWq, const __grid_constant__ CUtensorMap tmWk, const __grid_constant__ CUtensorMap tmWv,
             const __grid_constant__ CUtensorMap tmWo, const __grid_constant__ CUtensorMap tmX, const bf16* __restrict__ mem0, char* const acc) {
    extern __shared__ __align__(1024) uint8_t smem[];
    const uint32_t sb = smem_u32(smem);
    const int tid = threadIdx.x;
    const uint32_t L16 = __shfl_sync(0xffffffffu, (tid & 31) * 16, tid & 31);
    const int w = __shfl_sync(0xffffffffu, tid >> 5, 0), wg = w >> 2, wq = w & 3;
    uint32_t j, h;
    asm("mov.u32 %0, %%cluster_ctarank;" : "=r"(j));
    asm("mov.u32 %0, %%clusterid.x;" : "=r"(h));
    const bool isv = (j == 2);
    const uint32_t peerA = mapa(sb, isv ? 0 : (j ^ 1)), peerB = mapa(sb, isv ? 1 : 2);
    if (tid == 256) {
        for (int c = 0; c < 3; c++) { mbar_init(sb + B_W + 8 * c, 1); mbar_init(sb + B_M + 8 * c, 4); }
        mbar_init(sb + B_WO, 1); mbar_init(sb + B_T, 1);
        mbar_init(sb + B_X, 1); mbar_init(sb + B_X + 8, 1);
        mbar_init(sb + B_S, isv ? 8 : 5);
        mbar_init(sb + B_VX, 1); mbar_init(sb + B_VX + 8, 1);
        mbar_init(sb + B_SX, 1); mbar_init(sb + B_SX + 8, 1);
        asm volatile("fence.mbarrier_init.release.cluster;" ::: "memory");
        const CUtensorMap* m0 = isv ? &tmWv : &tmWq;
        const CUtensorMap* m1 = isv ? &tmWv : &tmWk;
        const int c0 = h * 128 + (isv ? 0 : 64 * j), c1 = h * 128 + (isv ? 64 : 64 * j);
        mbar_expect(sb + B_X, XB_BYTES);
        tma3d(sb + S_XB, &tmX, 0, 0, 0, sb + B_X);
#pragma unroll
        for (int c = 0; c < 3; c++) {
            mbar_expect(sb + B_W + 8 * c, 49152);
            tma2d(sb + s_w(c), m0, c0, c * 192, sb + B_W + 8 * c);
            tma2d(sb + s_w(c) + 24576, m1, c1, c * 192, sb + B_W + 8 * c);
        }
        mbar_expect(sb + B_X + 8, XB_BYTES);
        tma3d(sb + S_XB + XB_BYTES, &tmX, 0, 32, 0, sb + B_X + 8);
    }
    __syncthreads();
    if (wg == 2) {
        asm volatile("setmaxnreg.dec.sync.aligned.u32 %0;" ::"n"(REG_AUX));
        if (!isv) chain_aux<false>(sb, L16, wq, j, h, peerA, peerB, &tmWo, &tmX, mem0, acc);
        else chain_aux<true>(sb, L16, wq, j, h, peerA, peerB, &tmWo, &tmX, mem0, acc);
        __syncwarp();
        cluster_arrive(); cluster_wait();
        TSTAMP(65, 0);
    } else if (wg == 0) {
        asm volatile("setmaxnreg.inc.sync.aligned.u32 %0;" ::"n"(REG_MAIN0));
        if (!isv) chain_main<0>(sb, L16, wq, j, h, peerA, peerB, acc);
        else chain_main<2>(sb, L16, wq, j, h, peerA, peerB, acc);
        cluster_arrive(); cluster_wait();
    } else {
        asm volatile("setmaxnreg.inc.sync.aligned.u32 %0;" ::"n"(REG_MAIN1));
        if (!isv) chain_main<1>(sb, L16, wq, j, h, peerA, peerB, acc);
        else chain_main<3>(sb, L16, wq, j, h, peerA, peerB, acc);
        cluster_arrive(); cluster_wait();
    }
}

constexpr int NHELP = 36;
constexpr uint32_t H_U = 0;
constexpr uint32_t UT_PITCH = 4368;
constexpr uint32_t H_UT = 65536;
constexpr uint32_t KW_BYTES = 8320;
constexpr uint32_t H_KW = 135424;
constexpr uint32_t H_PAR = 201984;
constexpr uint32_t H_KD = 218368;
constexpr uint32_t H_STAGE = 0;
constexpr uint32_t H_RED = 196608;
constexpr uint32_t H_FIN = 212992;
constexpr uint32_t H_BAR = 229376;
constexpr uint32_t B_SMEM = H_BAR + 256;
constexpr uint32_t HB_U = H_BAR, HB_WO = H_BAR + 8, HB_FULL = H_BAR + 16, HB_EMPTY = H_BAR + 64, HB_RFULL = H_BAR + 112, HB_REMPTY = H_BAR + 128, HB_FIN = H_BAR + 144;
__device__ __align__(1024) uint4 g_part[4 * 9 * 4 * 4 * 128];

__device__ __forceinline__ float2 cmul(float2 a, float2 b) { return make_float2(fmaf(a.x, b.x, -a.y * b.y), fmaf(a.x, b.y, a.y * b.x)); }
__device__ __forceinline__ float2 csqr(float2 a) { return make_float2(fmaf(a.x, a.x, -a.y * a.y), (a.x + a.x) * a.y); }
__device__ __forceinline__ float2 cexp(float zr, float zi, float p) {
    const float m = ex2(zr * p);
    const float r = zi * p;
    const float a = (r - rintf(r)) * 6.283185307179586f;
    return make_float2(m * __cosf(a), m * __sinf(a));
}
__device__ __forceinline__ uint32_t pack_f16(float lo, float hi) { uint32_t r; asm("cvt.rn.f16x2.f32 %0, %1, %2;" : "=r"(r) : "f"(hi), "f"(lo)); return r; }
__device__ __forceinline__ void mma16h(float* d, const uint32_t* a, uint32_t b0, uint32_t b1) {
    asm volatile("mma.sync.aligned.m16n8k16.row.col.f32.f16.f16.f32 {%0,%1,%2,%3},{%4,%5,%6,%7},{%8,%9},{%0,%1,%2,%3};"
                 : "+f"(d[0]), "+f"(d[1]), "+f"(d[2]), "+f"(d[3]) : "r"(a[0]), "r"(a[1]), "r"(a[2]), "r"(a[3]), "r"(b0), "r"(b1));
}
__device__ __forceinline__ float bf_round(float x) { return __bfloat162float(__float2bfloat16_rn(x)); }
__device__ __forceinline__ uint32_t lds32(uint32_t a) { uint32_t v; asm volatile("ld.shared.b32 %0,[%1];" : "=r"(v) : "r"(a) : "memory"); return v; }
__device__ __forceinline__ uint32_t lds16(uint32_t a) { uint16_t v; asm volatile("ld.shared.u16 %0,[%1];" : "=h"(v) : "r"(a) : "memory"); return v; }
__device__ __forceinline__ void stsm4(uint32_t a, uint32_t r0, uint32_t r1, uint32_t r2, uint32_t r3) { asm volatile("stmatrix.sync.aligned.m8n8.x4.shared.b16 [%0],{%1,%2,%3,%4};" ::"r"(a), "r"(r0), "r"(r1), "r"(r2), "r"(r3) : "memory"); }

__device__ __forceinline__ void s4d_kernel(uint32_t par, uint32_t kd, uint32_t kw, int d, int lane, const bf16* __restrict__ logA, const bf16* __restrict__ Aim,
                                           const bf16* __restrict__ Cre, const bf16* __restrict__ Cim, const bf16* __restrict__ logdt) {
    const float dt = bf_round(expf(__bfloat162float(logdt[d])));
    float4 q[4];
    float cmax = 0.f, last = 0.f;
#pragma unroll
    for (int i = 0; i < 4; i++) {
        const int n = d * NST + i * 32 + lane;
        q[i].x = -bf_round(expf(__bfloat162float(logA[n]))) * dt * 1.4426950408889634f;
        q[i].y = __bfloat162float(Aim[n]) * dt * 0.15915494309189535f;
        q[i].z = 2.f * (__bfloat162float(Cre[n]) * dt);
        q[i].w = 2.f * (__bfloat162float(Cim[n]) * dt);
        cmax = fmaxf(cmax, fmaxf(fabsf(q[i].z), fabsf(q[i].w)));
        const float2 e = cexp(q[i].x, q[i].y, 2048.f);
        last += q[i].z * e.x - q[i].w * e.y;
    }
#pragma unroll
    for (int o = 16; o; o >>= 1) { cmax = fmaxf(cmax, __shfl_xor_sync(0xffffffffu, cmax, o)); last += __shfl_xor_sync(0xffffffffu, last, o); }
    const float cs = __uint_as_float(max(__float_as_uint(cmax) & 0x7F800000u, 0x00800000u));
    const float ci = 1.f / cs;
#pragma unroll
    for (int i = 0; i < 4; i++) sts128(par + (i * 32 + lane) * 16, __float_as_uint(q[i].x), __float_as_uint(q[i].y), __float_as_uint(q[i].z * ci), __float_as_uint(q[i].w * ci));
    __syncwarp();
    float acc[5][4];
#pragma unroll
    for (int i = 0; i < 5; i++) acc[i][0] = acc[i][1] = acc[i][2] = acc[i][3] = 0.f;
    const float g = (float)(lane >> 2);
#pragma unroll 1
    for (int ks = 0; ks < 16; ks++) {
        uint32_t A[5][4], B[4][2];
#pragma unroll
        for (int hf = 0; hf < 2; hf++) {
            uint32_t r[4];
            lds128(r, par + (ks * 8 + hf * 4 + (lane & 3)) * 16);
            const float zr = __uint_as_float(r[0]), zi = __uint_as_float(r[1]);
            const float2 c = make_float2(__uint_as_float(r[2]), __uint_as_float(r[3]));
            float2 y = cexp(zr, zi, g), x0 = cexp(zr, zi, 8.f * g + 128.f), x1 = cexp(zr, zi, 8.f * g + 192.f);
            const float2 xl = cexp(zr, zi, 8.f * g + 64.f);
#pragma unroll
            for (int k = 0; k < 4; k++) {
                const float2 cy = cmul(c, y);
                B[k][hf] = pack_f16(cy.x, -cy.y);
                A[k + 1][2 * hf] = pack_f16(x0.x, x0.y);
                A[k + 1][2 * hf + 1] = pack_f16(x1.x, x1.y);
                if (k < 3) { y = csqr(y); x0 = csqr(x0); x1 = csqr(x1); }
            }
            A[0][2 * hf] = pack_f16(y.x, y.y);
            A[0][2 * hf + 1] = pack_f16(xl.x, xl.y);
        }
        mma16h(acc[0], A[0], B[0][0], B[0][1]);
#pragma unroll
        for (int k = 0; k < 4; k++) mma16h(acc[k + 1], A[k + 1], B[k][0], B[k][1]);
    }
#pragma unroll
    for (int i = 0; i < 5; i++) {
        sts32(kd + i * 256 + lane * 4, pack_bf16(acc[i][0] * cs, acc[i][1] * cs));
        sts32(kd + i * 256 + 128 + lane * 4, pack_bf16(acc[i][2] * cs, acc[i][3] * cs));
    }
    if (lane == 0) sts32(kd + 1280, pack_bf16(last, 0.f));
    if (lane < 16) sts32(kw + lane * 4, 0);
    __syncwarp();
    uint32_t carry = 0;
#pragma unroll 4
    for (int it = 0; it < 64; it++) {
        const int l = it * 32 + lane;
        const int jx = l < 128 ? l : (int)__bfloat16_as_ushort(__float2bfloat16_rn((float)l)) - (133 << 7);
        const uint32_t v = lds16(kd + jx * 2);
        uint32_t pv = __shfl_up_sync(0xffffffffu, v, 1);
        if (lane == 0) pv = carry;
        carry = __shfl_sync(0xffffffffu, v, 31);
        sts32(kw + 64 + l * 4, v | (pv << 16));
    }
    __syncwarp();
}

__device__ __forceinline__ void s4d_conv(uint32_t ut, uint32_t kw, int lane) {
    float acc[16][4];
#pragma unroll
    for (int i = 0; i < 16; i++) acc[i][0] = acc[i][1] = acc[i][2] = acc[i][3] = 0.f;
    const uint32_t ka = kw + 64 + ((lane >> 2) - 2 * (lane & 3)) * 4;
    const uint32_t ua = ut + 256 + lane * 8;
#pragma unroll 1
    for (int rho = 0; rho < 8; rho++) {
        uint32_t B[16][2];
#pragma unroll
        for (int q = 0; q < 16; q++) lds64(B[q], ua + q * 256 - rho * 32);
#pragma unroll
        for (int m = 0; m < 16; m++) {
            uint32_t A[4];
            const uint32_t x = ka + m * 512 + rho * 64;
            A[0] = lds32(x); A[1] = lds32(x + 32); A[2] = lds32(x - 32); A[3] = A[0];
#pragma unroll
            for (int i = m; i < 16; i++) mma16(acc[i], A, B[i - m][0], B[i - m][1]);
        }
    }
    __syncwarp();
    const uint32_t ya = ut + 256 + (lane & 7) * 32 + ((lane >> 3) & 1) * 16 + (lane >> 4) * 256;
#pragma unroll
    for (int i = 0; i < 16; i += 2)
        stsm4t(ya + i * 256, pack_bf16(acc[i][0], acc[i][1]), pack_bf16(acc[i][2], acc[i][3]),
               pack_bf16(acc[i + 1][0], acc[i + 1][1]), pack_bf16(acc[i + 1][2], acc[i + 1][3]));
}

__global__ void __launch_bounds__(384, 1)
helper_kernel(const __grid_constant__ CUtensorMap tmU, const __grid_constant__ CUtensorMap tmY, const __grid_constant__ CUtensorMap tmWo,
              const bf16* __restrict__ logA, const bf16* __restrict__ Aim, const bf16* __restrict__ Cre, const bf16* __restrict__ Cim,
              const bf16* __restrict__ logdt, const bf16* __restrict__ Dskip, bf16* __restrict__ out) {
    extern __shared__ __align__(1024) uint8_t smem[];
    const uint32_t sb = smem_u32(smem);
    const int tid = threadIdx.x, lane = tid & 31;
    const int w = __shfl_sync(0xffffffffu, tid >> 5, 0);
    const int d0 = blockIdx.x * 16;
    HSTAMP(0);
    if (tid == 0) {
        mbar_init(sb + HB_U, 1); mbar_init(sb + HB_WO, 1);
        for (int i = 0; i < 6; i++) { mbar_init(sb + HB_FULL + 8 * i, 1); mbar_init(sb + HB_EMPTY + 8 * i, 4); }
        for (int i = 0; i < 2; i++) { mbar_init(sb + HB_RFULL + 8 * i, 4); mbar_init(sb + HB_REMPTY + 8 * i, 4); mbar_init(sb + HB_FIN + 8 * i, 2); }
        fence_async_smem();
        mbar_expect(sb + HB_U, 65536);
        for (int i = 0; i < 8; i++) tma2d(sb + H_U + i * 8192, &tmU, d0, i * 256, sb + HB_U);
    }
    __syncthreads();
    const int m = lane >> 3, r = lane & 7;
    if (w < 8) {
        s4d_kernel(sb + H_PAR + w * 2048, sb + H_KD + w * 1296, sb + H_KW + w * KW_BYTES, d0 + w, lane, logA, Aim, Cre, Cim, logdt);
    } else {
        for (int i = tid - 256; i < 256; i += 128) sts128(sb + H_UT + (i >> 4) * UT_PITCH + (i & 15) * 16, 0, 0, 0, 0);
        mbar_wait(sb + HB_U, 0);
        const uint32_t src = sb + H_U + ((m & 1) * 8 + r) * 32 + (((m >> 1) ^ (r >> 2)) << 4);
        const uint32_t dst = sb + H_UT + 256 + (lane >> 2) * UT_PITCH + (lane & 3) * 8;
#pragma unroll 4
        for (int grp = w - 8; grp < 128; grp += 4) {
            uint32_t v[4];
            ldsm4t(v, src + grp * 512);
            sts64(dst + grp * 32, v[0], v[1]);
            sts64(dst + 8 * UT_PITCH + grp * 32, v[2], v[3]);
        }
    }
    __syncthreads();
    HSTAMP(1);
    if (w < 8) {
        s4d_conv(sb + H_UT + w * UT_PITCH, sb + H_KW + w * KW_BYTES, lane);
        s4d_kernel(sb + H_PAR + w * 2048, sb + H_KD + w * 1296, sb + H_KW + w * KW_BYTES, d0 + 8 + w, lane, logA, Aim, Cre, Cim, logdt);
        s4d_conv(sb + H_UT + (8 + w) * UT_PITCH, sb + H_KW + w * KW_BYTES, lane);
    }
    __syncthreads();
    HSTAMP(2);
    const int cc = blockIdx.x % 9, kq = blockIdx.x / 9;
    {
        const __nv_bfloat162 D0 = *reinterpret_cast<const __nv_bfloat162*>(Dskip + d0 + (lane & 3) * 2);
        const __nv_bfloat162 D1 = *reinterpret_cast<const __nv_bfloat162*>(Dskip + d0 + 8 + (lane & 3) * 2);
        const uint32_t ua = sb + H_U + ((m & 1) * 8 + r) * 32 + (((m >> 1) ^ (r >> 2)) << 4);
        const uint32_t ya = sb + H_UT + 256 + ((m >> 1) * 8 + r) * UT_PITCH + (m & 1) * 16;
        for (int grp = w; grp < 128; grp += 12) {
            uint32_t u[4], y[4];
            ldsm4(u, ua + grp * 512);
            ldsm4t(y, ya + grp * 32);
#pragma unroll
            for (int i = 0; i < 4; i++) {
                const __nv_bfloat162 o = __hadd2_rn(*reinterpret_cast<__nv_bfloat162*>(&y[i]), __hmul2_rn(*reinterpret_cast<__nv_bfloat162*>(&u[i]), i < 2 ? D0 : D1));
                y[i] = *reinterpret_cast<const uint32_t*>(&o);
            }
            stsm4(ua + grp * 512, y[0], y[1], y[2], y[3]);
        }
        fence_async_smem();
        __syncthreads();
        if (tid == 0) {
            for (int i = 0; i < 8; i++)
                asm volatile("cp.async.bulk.tensor.2d.global.shared::cta.bulk_group [%0, {%1,%2}], [%3];" ::"l"(&tmY), "r"(DM + d0), "r"(i * 256), "r"(sb + H_U + i * 8192) : "memory");
            bulk_commit();
            mbar_expect(sb + HB_WO, 131072);
            for (int i = 0; i < 8; i++) tma2d(sb + 65536 + i * 16384, &tmWo, cc * 64, (kq * 8 + i) * 128, sb + HB_WO);
            asm volatile("cp.async.bulk.wait_group.read 0;" ::: "memory");
        }
    }
    __syncwarp();
    if (w < 8) {
        asm volatile("setmaxnreg.inc.sync.aligned.u32 208;");
        const int wg = w >> 2;
        uint32_t wo[32][4];
        mbar_wait(sb + HB_WO, 0);
        const uint32_t a = sb + 65536 + wg * 65536 + ((m >> 1) * 8 + r) * 128 + (((2 * (w & 3) + (m & 1)) ^ r) << 4);
#pragma unroll
        for (int i = 0; i < 32; i++) ldsm4t(wo[i], a + i * 2048);
        __syncthreads();
        HSTAMP(3);
        const int t = tid & 127;
        int st = 0, ph = 0;
#pragma unroll 1
        for (int s = 0; s < NSEG; s++) {
            mbar_wait_long(sb + HB_FULL + (st * 2 + wg) * 8, ph);
            const uint32_t desc = desc_lo(sb + H_STAGE + st * 65536 + wg * 32768);
            float d[16];
            wg_fence();
#pragma unroll
            for (int i = 0; i < 32; i++) {
                const uint32_t db = desc + (((i >> 2) * 4096 + (i & 3) * 32) >> 4);
                if (i == 0) wg_rs_n32<0>(d, wo[i], db); else wg_rs_n32<1>(d, wo[i], db);
            }
            wg_commit();
            wg_wait<0>();
            mbar_arrive_if0(sb + HB_EMPTY + (st * 2 + wg) * 8, lane);
            if (++st == 3) { st = 0; ph ^= 1; }
            const uint32_t ra = sb + H_RED + (s & 1) * 8192 + t * 16;
            if (wg == 0) {
                if (s >= 2) mbar_wait_long(sb + HB_REMPTY + (s & 1) * 8, ((s - 2) >> 1) & 1);
#pragma unroll
                for (int i = 0; i < 4; i++) sts128(ra + i * 2048, __float_as_uint(d[4 * i]), __float_as_uint(d[4 * i + 1]), __float_as_uint(d[4 * i + 2]), __float_as_uint(d[4 * i + 3]));
                __syncwarp();
                mbar_arrive_if0(sb + HB_RFULL + (s & 1) * 8, lane);
            } else {
                mbar_wait_long(sb + HB_RFULL + (s & 1) * 8, (s >> 1) & 1);
                if (s >= 2) mbar_wait_long(sb + HB_FIN + (s & 1) * 8, ((s - 2) >> 1) & 1);
                uint4* dst = g_part + (((s & 3) * 9 + cc) * 16 + kq) * 128 + t;
#pragma unroll
                for (int i = 0; i < 4; i++) {
                    uint32_t p[4];
                    lds128(p, ra + i * 2048);
#pragma unroll
                    for (int k = 0; k < 4; k++) p[k] = ((__float_as_uint(__uint_as_float(p[k]) + d[4 * i + k]) + 64) & ~127u) | (s + 1);
                    asm volatile("st.relaxed.gpu.global.v4.u32 [%0], {%1,%2,%3,%4};" ::"l"(dst + i * 512), "r"(p[0]), "r"(p[1]), "r"(p[2]), "r"(p[3]) : "memory");
                }
                __syncwarp();
                mbar_arrive_if0(sb + HB_REMPTY + (s & 1) * 8, lane);
            }
        }
        if (tid == 0) bulk_wait0();
    } else {
        asm volatile("setmaxnreg.dec.sync.aligned.u32 88;");
        __syncthreads();
        if (w == 8) {
            if (lane == 0) {
                int st = 0, ph = 1;
                for (int s = 0; s < NSEG; s++) {
                    unsigned c = 0;
                    while (ld_acquire(&g_flag[s * 4 + kq]) < 8 && ++c < LONG_LIM) __nanosleep(FLAG_NS);
                    asm volatile("fence.proxy.async;" ::: "memory");
                    for (int g = 0; g < 2; g++) {
                        const uint32_t bar = sb + HB_FULL + (st * 2 + g) * 8;
                        mbar_wait_long(sb + HB_EMPTY + (st * 2 + g) * 8, ph);
                        mbar_expect(bar, 32768);
                        asm volatile("cp.async.bulk.shared::cluster.global.mbarrier::complete_tx::bytes [%0], [%1], %2, [%3];"
                                     ::"r"(sb + H_STAGE + st * 65536 + g * 32768), "l"(g_ox + (s * NH + kq * 8 + g * 4) * 512), "r"(32768), "r"(bar) : "memory");
                    }
                    if (++st == 3) { st = 0; ph ^= 1; }
                }
            }
        } else if (w < 11) {
            const int f = w - 9;
            const uint32_t fa = sb + H_FIN + f * 512;
            for (int s = 0; s < NSEG; s++) {
                mbar_wait_long(sb + HB_REMPTY + (s & 1) * 8, (s >> 1) & 1);
                const uint4* src = g_part + (((s & 3) * 9 + cc) * 16 + kq * 4) * 128 + f * 64 + lane;
                uint4 v[8];
                unsigned c = 0;
                while (true) {
                    uint32_t bad = 0;
#pragma unroll
                    for (int i = 0; i < 8; i++) v[i] = ld_poll(src + (i >> 1) * 128 + (i & 1) * 32);
#pragma unroll
                    for (int i = 0; i < 8; i++) bad |= (v[i].x ^ (s + 1)) | (v[i].y ^ (s + 1)) | (v[i].z ^ (s + 1)) | (v[i].w ^ (s + 1));
                    if (!__any_sync(0xffffffffu, (bad & 127) != 0) || ++c >= LONG_LIM) break;
                    __nanosleep(FLAG_NS);
                }
                mbar_arrive_if0(sb + HB_FIN + (s & 1) * 8, lane);
                uint32_t pk[4];
#pragma unroll
                for (int u = 0; u < 2; u++) {
                    float o[4] = {0.f, 0.f, 0.f, 0.f};
#pragma unroll
                    for (int k = 0; k < 4; k++) {
                        o[0] += __uint_as_float(v[2 * k + u].x & ~127u); o[1] += __uint_as_float(v[2 * k + u].y & ~127u);
                        o[2] += __uint_as_float(v[2 * k + u].z & ~127u); o[3] += __uint_as_float(v[2 * k + u].w & ~127u);
                    }
                    pk[2 * u] = pack_bf16(o[0], o[1]); pk[2 * u + 1] = pack_bf16(o[2], o[3]);
                }
                stsm4t(fa + r * 64 + ((m ^ (r >> 1)) << 4), pk[0], pk[1], pk[2], pk[3]);
                __syncwarp();
                uint32_t o4[4];
                lds128(o4, fa + (lane >> 2) * 64 + (((lane & 3) ^ (lane >> 3)) << 4));
                *reinterpret_cast<uint4*>(out + (s * SEG + kq * 8 + (lane >> 2)) * OUTW + cc * 64 + f * 32 + (lane & 3) * 8) = make_uint4(o4[0], o4[1], o4[2], o4[3]);
                __syncwarp();
                HSTAMP2(s);
            }
            asm volatile("griddepcontrol.wait;" ::: "memory");
        }
    }
}

typedef CUresult (*EncodeFn)(CUtensorMap*, CUtensorMapDataType, cuuint32_t, void*, const cuuint64_t*, const cuuint64_t*, const cuuint32_t*,
                             const cuuint32_t*, CUtensorMapInterleave, CUtensorMapSwizzle, CUtensorMapL2promotion, CUtensorMapFloatOOBfill);

void make_map(EncodeFn fn, CUtensorMap* m, const void* p, int rank, const cuuint64_t* dims, const cuuint64_t* strides, const cuuint32_t* box,
              CUtensorMapSwizzle sw = CU_TENSOR_MAP_SWIZZLE_128B, CUtensorMapL2promotion pr = CU_TENSOR_MAP_L2_PROMOTION_L2_128B) {
    const cuuint32_t es[3] = {1, 1, 1};
    fn(m, CU_TENSOR_MAP_DATA_TYPE_BFLOAT16, rank, const_cast<void*>(p), dims, strides, box, es, CU_TENSOR_MAP_INTERLEAVE_NONE,
       sw, pr, CU_TENSOR_MAP_FLOAT_OOB_FILL_NONE);
}

}

extern "C" void kernel_launch(void* const* d_in, const int* in_sizes, int n_in, void* d_out, int out_size) {
    const bf16* x = (const bf16*)d_in[0];
    const bf16* mem0 = (const bf16*)d_in[1];
    const bf16* Wo = (const bf16*)d_in[5];
    bf16* out = (bf16*)d_out;

    static EncodeFn enc = nullptr;
    static char* acc = nullptr;
    if (!enc) {
        void* p = nullptr;
        cudaGetSymbolAddress(&p, g_acc);
        acc = reinterpret_cast<char*>((reinterpret_cast<uintptr_t>(p) + 32767) & ~(uintptr_t)32767);
        void* fn = nullptr;
        cudaDriverEntryPointQueryResult st;
        cudaGetDriverEntryPoint("cuTensorMapEncodeTiled", &fn, cudaEnableDefault, &st);
        enc = (EncodeFn)fn;
        cudaFuncSetAttribute(chain_kernel, cudaFuncAttributeMaxDynamicSharedMemorySize, A_SMEM);
        cudaFuncSetAttribute(helper_kernel, cudaFuncAttributeMaxDynamicSharedMemorySize, B_SMEM);
    }
    CUtensorMap tmW[3], tmWo, tmX;
    {
        const cuuint64_t dims[2] = {4096, 576}, str[1] = {8192};
        const cuuint32_t box[2] = {64, 192};
        for (int i = 0; i < 3; i++) make_map(enc, &tmW[i], d_in[2 + i], 2, dims, str, box);
    }
    {
        const cuuint64_t dims[2] = {576, 4096}, str[1] = {1152};
        const cuuint32_t box[2] = {64, 128};
        make_map(enc, &tmWo, Wo, 2, dims, str, box);
    }
    {
        const cuuint64_t dims[3] = {64, 2048, 9}, str[2] = {1152, 128};
        const cuuint32_t box[3] = {64, 32, 9};
        make_map(enc, &tmX, x, 3, dims, str, box);
    }
    CUtensorMap tmU, tmY;
    {
        const cuuint64_t dimsU[2] = {576, 2048}, strU[1] = {1152}, dimsY[2] = {1152, 2048}, strY[1] = {2304};
        const cuuint32_t box[2] = {16, 256};
        make_map(enc, &tmU, d_in[7], 2, dimsU, strU, box, CU_TENSOR_MAP_SWIZZLE_32B);
        make_map(enc, &tmY, out, 2, dimsY, strY, box, CU_TENSOR_MAP_SWIZZLE_32B, CU_TENSOR_MAP_L2_PROMOTION_NONE);
    }
    cudaStream_t st = cudaStreamPerThread;
    {
        cudaLaunchConfig_t cfg = {};
        cfg.gridDim = dim3(96); cfg.blockDim = dim3(384); cfg.dynamicSmemBytes = A_SMEM; cfg.stream = st;
        cudaLaunchAttribute at[1];
        at[0].id = cudaLaunchAttributeClusterDimension;
        at[0].val.clusterDim.x = 3; at[0].val.clusterDim.y = 1; at[0].val.clusterDim.z = 1;
        cfg.attrs = at; cfg.numAttrs = 1;
        cudaLaunchKernelEx(&cfg, chain_kernel, tmW[0], tmW[1], tmW[2], tmWo, tmX, mem0, acc);
    }
    {
        cudaLaunchConfig_t cfg = {};
        cfg.gridDim = dim3(NHELP); cfg.blockDim = dim3(384); cfg.dynamicSmemBytes = B_SMEM; cfg.stream = st;
        cudaLaunchAttribute at[1];
        at[0].id = cudaLaunchAttributeProgrammaticStreamSerialization;
        at[0].val.programmaticStreamSerializationAllowed = 1;
        cfg.attrs = at; cfg.numAttrs = 1;
        cudaLaunchKernelEx(&cfg, helper_kernel, tmU, tmY, tmWo, (const bf16*)d_in[8], (const bf16*)d_in[9], (const bf16*)d_in[10],
                           (const bf16*)d_in[11], (const bf16*)d_in[12], (const bf16*)d_in[13], out);
    }
}
```

```cpp
#include <cuda_runtime.h>
#include <cuda_bf16.h>
#include <cuda_fp16.h>
#include <cuda.h>
#include <stdint.h>

typedef __nv_bfloat16 bf16;

namespace {

constexpr int DM = 576, NH = 32, DH = 128, SEG = 32, NSEG = 64, SEQ = 2048, NST = 128;
constexpr int OUTW = 2 * DM;
constexpr unsigned SPIN_LIM = 1u << 15;

__device__ __align__(1024) uint4 g_acc[33 * 2048];
__device__ __align__(128) unsigned g_time[NSEG * 96];
__device__ __align__(1024) uint4 g_ox[NSEG * NH * 512];
__device__ __align__(1024) uint4 g_vx[NH * 2 * 512];
__device__ unsigned g_flag[NSEG * 4];
__device__ unsigned g_zero_cnt;

__device__ __forceinline__ uint32_t smem_u32(const void* p) { return (uint32_t)__cvta_generic_to_shared(p); }
__device__ __forceinline__ unsigned clk() { unsigned c; asm volatile("mov.u32 %0, %%clock;" : "=r"(c)::"memory"); return c; }
__device__ __forceinline__ unsigned gtime() { unsigned t; asm volatile("mov.u32 %0, %%globaltimer_lo;" : "=r"(t)::"memory"); return t; }
__device__ __forceinline__ uint32_t slot_off(int s) { return (s >> 1) * 32768 + (s & 1) * 512; }
__device__ __forceinline__ uint32_t lane_off(uint32_t L16) { return (L16 & 0x180) * 8 + (L16 & 0x40) * 4 + (L16 & 0x30); }
__device__ __forceinline__ uint32_t mapa(uint32_t a, uint32_t r) { uint32_t o; asm("mapa.shared::cluster.u32 %0, %1, %2;" : "=r"(o) : "r"(a), "r"(r)); return o; }
__device__ __forceinline__ void mbar_init(uint32_t b, uint32_t n) { asm volatile("mbarrier.init.shared::cta.b64 [%0], %1;" ::"r"(b), "r"(n) : "memory"); }
__device__ __forceinline__ void mbar_arrive(uint32_t b) { asm volatile("mbarrier.arrive.shared::cta.b64 _, [%0];" ::"r"(b) : "memory"); }
__device__ __forceinline__ void mbar_expect(uint32_t b, uint32_t tx) { asm volatile("mbarrier.arrive.expect_tx.shared::cta.b64 _, [%0], %1;" ::"r"(b), "r"(tx) : "memory"); }
__device__ __forceinline__ bool mbar_try(uint32_t b, uint32_t par) {
    uint32_t ok;
    asm volatile("{.reg .pred p; mbarrier.try_wait.parity.shared::cta.b64 p, [%1], %2; selp.u32 %0, 1, 0, p;}" : "=r"(ok) : "r"(b), "r"(par) : "memory");
    return ok;
}
__device__ __forceinline__ bool mbar_test(uint32_t b, uint32_t par) {
    uint32_t ok;
    asm volatile("{.reg .pred p; mbarrier.test_wait.parity.shared::cta.b64 p, [%1], %2; selp.u32 %0, 1, 0, p;}" : "=r"(ok) : "r"(b), "r"(par) : "memory");
    return ok;
}
__device__ __forceinline__ void mbar_wait(uint32_t b, uint32_t par) {
    asm volatile("{.reg .pred p, q; .reg .u32 c; mov.u32 c, 0;\n"
                 "W: mbarrier.try_wait.parity.shared::cta.b64 p, [%0], %1;\n"
                 "@p bra D;\n add.u32 c, c, 1; setp.lt.u32 q, c, %2;\n @q bra W;\n D:\n}" ::"r"(b), "r"(par), "n"(SPIN_LIM) : "memory");
}
constexpr unsigned LONG_LIM = 1u << 17;
__device__ __forceinline__ void mbar_wait_long(uint32_t b, uint32_t par) {
    asm volatile("{.reg .pred p, q; .reg .u32 c; mov.u32 c, 0;\n"
                 "W: mbarrier.try_wait.parity.shared::cta.b64 p, [%0], %1;\n"
                 "@p bra D;\n add.u32 c, c, 1; setp.lt.u32 q, c, %2;\n @q bra W;\n D:\n}" ::"r"(b), "r"(par), "n"(LONG_LIM) : "memory");
}
__device__ __forceinline__ void cluster_sync() { asm volatile("barrier.cluster.arrive.aligned; barrier.cluster.wait.aligned;" ::: "memory"); }
__device__ __forceinline__ void fence_async_smem() { asm volatile("fence.proxy.async.shared::cta;" ::: "memory"); }
__device__ __forceinline__ void ldsm4(uint32_t* r, uint32_t a) { asm volatile("ldmatrix.sync.aligned.m8n8.x4.shared.b16 {%0,%1,%2,%3},[%4];" : "=r"(r[0]), "=r"(r[1]), "=r"(r[2]), "=r"(r[3]) : "r"(a) : "memory"); }
__device__ __forceinline__ void ldsm4t(uint32_t* r, uint32_t a) { asm volatile("ldmatrix.sync.aligned.m8n8.x4.trans.shared.b16 {%0,%1,%2,%3},[%4];" : "=r"(r[0]), "=r"(r[1]), "=r"(r[2]), "=r"(r[3]) : "r"(a) : "memory"); }
__device__ __forceinline__ void stsm1(uint32_t a, uint32_t r0) { asm volatile("stmatrix.sync.aligned.m8n8.x1.shared.b16 [%0],{%1};" ::"r"(a), "r"(r0) : "memory"); }
__device__ __forceinline__ void stsm2t(uint32_t a, uint32_t r0, uint32_t r1) { asm volatile("stmatrix.sync.aligned.m8n8.x2.trans.shared.b16 [%0],{%1,%2};" ::"r"(a), "r"(r0), "r"(r1) : "memory"); }
__device__ __forceinline__ void stsm4t(uint32_t a, uint32_t r0, uint32_t r1, uint32_t r2, uint32_t r3) { asm volatile("stmatrix.sync.aligned.m8n8.x4.trans.shared.b16 [%0],{%1,%2,%3,%4};" ::"r"(a), "r"(r0), "r"(r1), "r"(r2), "r"(r3) : "memory"); }
__device__ __forceinline__ void stsm4(uint32_t a, uint32_t r0, uint32_t r1, uint32_t r2, uint32_t r3) { asm volatile("stmatrix.sync.aligned.m8n8.x4.shared.b16 [%0],{%1,%2,%3,%4};" ::"r"(a), "r"(r0), "r"(r1), "r"(r2), "r"(r3) : "memory"); }
__device__ __forceinline__ void sts32(uint32_t a, uint32_t v) { asm volatile("st.shared.b32 [%0], %1;" ::"r"(a), "r"(v) : "memory"); }
__device__ __forceinline__ void sts64(uint32_t a, uint32_t x, uint32_t y) { asm volatile("st.shared.v2.b32 [%0], {%1,%2};" ::"r"(a), "r"(x), "r"(y) : "memory"); }
__device__ __forceinline__ void sts128(uint32_t a, uint32_t x, uint32_t y, uint32_t z, uint32_t w) { asm volatile("st.shared.v4.b32 [%0], {%1,%2,%3,%4};" ::"r"(a), "r"(x), "r"(y), "r"(z), "r"(w) : "memory"); }
__device__ __forceinline__ void lds64(uint32_t* r, uint32_t a) { asm volatile("ld.shared.v2.b32 {%0,%1},[%2];" : "=r"(r[0]), "=r"(r[1]) : "r"(a) : "memory"); }
__device__ __forceinline__ float2 lds64f(uint32_t a) { float2 v; asm volatile("ld.shared.v2.f32 {%0,%1},[%2];" : "=f"(v.x), "=f"(v.y) : "r"(a) : "memory"); return v; }
__device__ __forceinline__ void lds128(uint32_t* r, uint32_t a) { asm volatile("ld.shared.v4.b32 {%0,%1,%2,%3},[%4];" : "=r"(r[0]), "=r"(r[1]), "=r"(r[2]), "=r"(r[3]) : "r"(a) : "memory"); }
__device__ __forceinline__ void st_async64(uint32_t a, uint32_t x, uint32_t y, uint32_t bar) {
    asm volatile("st.async.weak.shared::cluster.mbarrier::complete_tx::bytes.v2.b32 [%0], {%1,%2}, [%3];" ::"r"(a), "r"(x), "r"(y), "r"(bar) : "memory");
}
__device__ __forceinline__ void st_async32(uint32_t a, uint32_t x, uint32_t bar) {
    asm volatile("st.async.weak.shared::cluster.mbarrier::complete_tx::bytes.b32 [%0], %1, [%2];" ::"r"(a), "r"(x), "r"(bar) : "memory");
}
__device__ __forceinline__ void ldsm2(uint32_t* r, uint32_t a) { asm volatile("ldmatrix.sync.aligned.m8n8.x2.shared.b16 {%0,%1},[%2];" : "=r"(r[0]), "=r"(r[1]) : "r"(a) : "memory"); }
__device__ __forceinline__ uint32_t pack_f16_sat(float lo, float hi) { uint32_t r; asm("cvt.rn.satfinite.f16x2.f32 %0, %1, %2;" : "=r"(r) : "f"(hi), "f"(lo)); return r; }
__device__ __forceinline__ __half2 as_h2(uint32_t x) { return *reinterpret_cast<__half2*>(&x); }
__device__ __forceinline__ uint32_t as_u32(__half2 x) { return *reinterpret_cast<uint32_t*>(&x); }
__device__ __forceinline__ uint32_t pack_bf16(float lo, float hi) { uint32_t r; asm("cvt.rn.bf16x2.f32 %0, %1, %2;" : "=r"(r) : "f"(hi), "f"(lo)); return r; }
__device__ __forceinline__ float ex2(float x) { float r; asm("ex2.approx.ftz.f32 %0, %1;" : "=f"(r) : "f"(x)); return r; }
__device__ __forceinline__ float rcp(float x) { float r; asm("rcp.approx.ftz.f32 %0, %1;" : "=f"(r) : "f"(x)); return r; }
__device__ __forceinline__ void mma16(float* d, const uint32_t* a, uint32_t b0, uint32_t b1) {
    asm volatile("mma.sync.aligned.m16n8k16.row.col.f32.bf16.bf16.f32 {%0,%1,%2,%3},{%4,%5,%6,%7},{%8,%9},{%0,%1,%2,%3};"
                 : "+f"(d[0]), "+f"(d[1]), "+f"(d[2]), "+f"(d[3]) : "r"(a[0]), "r"(a[1]), "r"(a[2]), "r"(a[3]), "r"(b0), "r"(b1));
}
__device__ __forceinline__ void mma16z(float* d, const uint32_t* a, uint32_t b0, uint32_t b1) {
    asm volatile("mma.sync.aligned.m16n8k16.row.col.f32.bf16.bf16.f32 {%0,%1,%2,%3},{%4,%5,%6,%7},{%8,%9},{%10,%10,%10,%10};"
                 : "=f"(d[0]), "=f"(d[1]), "=f"(d[2]), "=f"(d[3]) : "r"(a[0]), "r"(a[1]), "r"(a[2]), "r"(a[3]), "r"(b0), "r"(b1), "f"(0.f));
}
__device__ __forceinline__ void mma8(float* d, uint32_t a0, uint32_t a1, uint32_t b0) {
    asm volatile("mma.sync.aligned.m16n8k8.row.col.f32.bf16.bf16.f32 {%0,%1,%2,%3},{%4,%5},{%6},{%0,%1,%2,%3};"
                 : "+f"(d[0]), "+f"(d[1]), "+f"(d[2]), "+f"(d[3]) : "r"(a0), "r"(a1), "r"(b0));
}
template <int ACC>
__device__ __forceinline__ void mma_sp(float* d, const uint32_t* a, const uint32_t* b) {
    if (ACC)
        asm volatile("mma.sp::ordered_metadata.sync.aligned.m16n8k32.row.col.f32.bf16.bf16.f32 {%0,%1,%2,%3},{%4,%5,%6,%7},{%8,%9,%10,%11},{%0,%1,%2,%3},%12,0x0;"
                     : "+f"(d[0]), "+f"(d[1]), "+f"(d[2]), "+f"(d[3])
                     : "r"(a[0]), "r"(a[1]), "r"(a[2]), "r"(a[3]), "r"(b[0]), "r"(b[1]), "r"(b[2]), "r"(b[3]), "r"(0xEEEE4444u));
    else
        asm volatile("mma.sp::ordered_metadata.sync.aligned.m16n8k32.row.col.f32.bf16.bf16.f32 {%0,%1,%2,%3},{%4,%5,%6,%7},{%8,%9,%10,%11},{%13,%13,%13,%13},%12,0x0;"
                     : "=f"(d[0]), "=f"(d[1]), "=f"(d[2]), "=f"(d[3])
                     : "r"(a[0]), "r"(a[1]), "r"(a[2]), "r"(a[3]), "r"(b[0]), "r"(b[1]), "r"(b[2]), "r"(b[3]), "r"(0xEEEE4444u), "f"(0.f));
}
__device__ __forceinline__ void mbar_arrive_if0(uint32_t b, uint32_t z) { asm volatile("{.reg .pred p; setp.eq.u32 p, %1, 0; @p mbarrier.arrive.shared::cta.b64 _, [%0];}" ::"r"(b), "r"(z) : "memory"); }
__device__ __forceinline__ void mbar_expect_if0(uint32_t b, uint32_t tx, uint32_t z) { asm volatile("{.reg .pred p; setp.eq.u32 p, %2, 0; @p mbarrier.arrive.expect_tx.shared::cta.b64 _, [%0], %1;}" ::"r"(b), "r"(tx), "r"(z) : "memory"); }
__device__ __forceinline__ float lds32f(uint32_t a) { float v; asm volatile("ld.shared.f32 %0,[%1];" : "=f"(v) : "r"(a) : "memory"); return v; }
__device__ __forceinline__ void wg_fence() { asm volatile("wgmma.fence.sync.aligned;" ::: "memory"); }
__device__ __forceinline__ void wg_commit() { asm volatile("wgmma.commit_group.sync.aligned;" ::: "memory"); }
template <int N> __device__ __forceinline__ void wg_wait() { asm volatile("wgmma.wait_group.sync.aligned %0;" ::"n"(N) : "memory"); }
__device__ __forceinline__ void delay(unsigned n) { if (n) { const unsigned t0 = clk(); while (clk() - t0 < n) {} } }
template <int ACC, uint32_t DHI = 0x40000040u, int TB = 0>
__device__ __forceinline__ void wg_rs_n32(float* d, const uint32_t* a, uint32_t dlo) {
    if (ACC)
        asm volatile("{.reg .b64 db; mov.b64 db, {%20, %21};\n"
                     "wgmma.mma_async.sync.aligned.m64n32k16.f32.bf16.bf16 {%0,%1,%2,%3,%4,%5,%6,%7,%8,%9,%10,%11,%12,%13,%14,%15},{%16,%17,%18,%19},db,1,1,1,%22;}"
                     : "+f"(d[0]), "+f"(d[1]), "+f"(d[2]), "+f"(d[3]), "+f"(d[4]), "+f"(d[5]), "+f"(d[6]), "+f"(d[7]),
                       "+f"(d[8]), "+f"(d[9]), "+f"(d[10]), "+f"(d[11]), "+f"(d[12]), "+f"(d[13]), "+f"(d[14]), "+f"(d[15])
                     : "r"(a[0]), "r"(a[1]), "r"(a[2]), "r"(a[3]), "r"(dlo), "r"(DHI), "n"(TB));
    else
        asm volatile("{.reg .b64 db; mov.b64 db, {%20, %21};\n"
                     "wgmma.mma_async.sync.aligned.m64n32k16.f32.bf16.bf16 {%0,%1,%2,%3,%4,%5,%6,%7,%8,%9,%10,%11,%12,%13,%14,%15},{%16,%17,%18,%19},db,0,1,1,%22;}"
                     : "=f"(d[0]), "=f"(d[1]), "=f"(d[2]), "=f"(d[3]), "=f"(d[4]), "=f"(d[5]), "=f"(d[6]), "=f"(d[7]),
                       "=f"(d[8]), "=f"(d[9]), "=f"(d[10]), "=f"(d[11]), "=f"(d[12]), "=f"(d[13]), "=f"(d[14]), "=f"(d[15])
                     : "r"(a[0]), "r"(a[1]), "r"(a[2]), "r"(a[3]), "r"(dlo), "r"(DHI), "n"(TB));
}
__device__ __forceinline__ uint32_t desc_lo(uint32_t addr) { return ((addr & 0x3FFFF) >> 4) | (1u << 16); }
__device__ __forceinline__ void tma2d(uint32_t dst, const CUtensorMap* m, int c0, int c1, uint32_t bar) {
    asm volatile("cp.async.bulk.tensor.2d.shared::cluster.global.mbarrier::complete_tx::bytes [%0], [%1, {%2,%3}], [%4];"
                 ::"r"(dst), "l"(m), "r"(c0), "r"(c1), "r"(bar) : "memory");
}
__device__ __forceinline__ void tma3d(uint32_t dst, const CUtensorMap* m, int c0, int c1, int c2, uint32_t bar) {
    asm volatile("cp.async.bulk.tensor.3d.shared::cluster.global.mbarrier::complete_tx::bytes [%0], [%1, {%2,%3,%4}], [%5];"
                 ::"r"(dst), "l"(m), "r"(c0), "r"(c1), "r"(c2), "r"(bar) : "memory");
}
__device__ __forceinline__ void tma3d_mc(uint32_t dst, const CUtensorMap* m, int c0, int c1, int c2, uint32_t bar, uint16_t mask) {
    asm volatile("cp.async.bulk.tensor.3d.shared::cluster.global.mbarrier::complete_tx::bytes.multicast::cluster [%0], [%1, {%2,%3,%4}], [%5], %6;"
                 ::"r"(dst), "l"(m), "r"(c0), "r"(c1), "r"(c2), "r"(bar), "h"(mask) : "memory");
}
__device__ __forceinline__ void bulk_g2s_mc(uint32_t dst, const void* src, uint32_t bytes, uint32_t bar, uint16_t mask) {
    asm volatile("cp.async.bulk.shared::cluster.global.mbarrier::complete_tx::bytes.multicast::cluster [%0], [%1], %2, [%3], %4;"
                 ::"r"(dst), "l"(src), "r"(bytes), "r"(bar), "h"(mask) : "memory");
}
__device__ __forceinline__ void tma2d_prefetch(const CUtensorMap* m, int c0, int c1) {
    asm volatile("cp.async.bulk.prefetch.tensor.2d.L2.global [%0, {%1,%2}];" ::"l"(m), "r"(c0), "r"(c1) : "memory");
}
__device__ __forceinline__ void bulk_s2c(uint32_t dst, uint32_t src, uint32_t bytes, uint32_t bar) {
    asm volatile("cp.async.bulk.shared::cluster.shared::cta.mbarrier::complete_tx::bytes [%0], [%1], %2, [%3];" ::"r"(dst), "r"(src), "r"(bytes), "r"(bar) : "memory");
}
__device__ __forceinline__ void bulk_s2g(void* dst, uint32_t src, uint32_t bytes) {
    asm volatile("cp.async.bulk.global.shared::cta.bulk_group [%0], [%1], %2;" ::"l"(dst), "r"(src), "r"(bytes) : "memory");
}
__device__ __forceinline__ void bulk_commit() { asm volatile("cp.async.bulk.commit_group;" ::: "memory"); }
__device__ __forceinline__ void bulk_wait0() { asm volatile("cp.async.bulk.wait_group 0;" ::: "memory"); }
__device__ __forceinline__ uint4 ld_poll(const void* p) {
    uint4 v;
    asm volatile("ld.relaxed.gpu.global.v4.u32 {%0,%1,%2,%3},[%4];" : "=r"(v.x), "=r"(v.y), "=r"(v.z), "=r"(v.w) : "l"(p) : "memory");
    return v;
}
template <int IMM>
__device__ __forceinline__ void ld_poll_at(uint4& v, const void* p) {
    asm volatile("ld.relaxed.gpu.global.v4.u32 {%0,%1,%2,%3},[%4+%5];" : "=r"(v.x), "=r"(v.y), "=r"(v.z), "=r"(v.w) : "l"(p), "n"(IMM) : "memory");
}
__device__ __forceinline__ void look(uint4 (&v)[6], const void* p) {
    ld_poll_at<0>(v[0], p); ld_poll_at<16384>(v[1], p); ld_poll_at<64>(v[2], p);
    ld_poll_at<16384 + 64>(v[3], p); ld_poll_at<128>(v[4], p); ld_poll_at<16384 + 128>(v[5], p);
}
__device__ __forceinline__ unsigned ld_acquire(const unsigned* p) { unsigned v; asm volatile("ld.acquire.gpu.global.u32 %0,[%1];" : "=r"(v) : "l"(p) : "memory"); return v; }
__device__ __forceinline__ void red_release(unsigned* p, unsigned v) { asm volatile("red.release.gpu.global.add.u32 [%0], %1;" ::"l"(p), "r"(v) : "memory"); }

template <int ID, int N> __device__ __forceinline__ void bar_sync() { asm volatile("bar.sync %0, %1;" ::"n"(ID), "n"(N) : "memory"); }
template <int ID, int N> __device__ __forceinline__ void bar_arrive() { asm volatile("bar.arrive %0, %1;" ::"n"(ID), "n"(N) : "memory"); }
__device__ __forceinline__ void cluster_arrive() { asm volatile("barrier.cluster.arrive.relaxed.aligned;" ::: "memory"); }
__device__ __forceinline__ void cluster_wait() { asm volatile("barrier.cluster.wait.aligned;" ::: "memory"); }

constexpr uint32_t XB_BYTES = 36864;
constexpr uint32_t S_XB = 0;
constexpr uint32_t S_QM = 73728;
constexpr uint32_t S_KM = 74752;
constexpr uint32_t S_OM = 75776;
constexpr uint32_t S_SP = 77824;
constexpr uint32_t S_SUM = 80384;
constexpr uint32_t S_TGT = 81408;
constexpr uint32_t S_VM = 147456;
constexpr uint32_t S_QX = 86016;
constexpr uint32_t S_PX = S_QX;
constexpr uint32_t S_KX = 94208;
constexpr uint32_t S_VX = 102400;
constexpr uint32_t S_SX = 135168;
constexpr uint32_t S_OX = 155648;
constexpr uint32_t S_MEM = 172032;
constexpr uint32_t S_WO = 181248;
constexpr uint32_t S_BAR = 230400;
constexpr uint32_t A_SMEM = S_BAR + 128;
__host__ __device__ constexpr uint32_t s_w(int c) { return c == 0 ? S_WO : 73728 + (c - 1) * 49152; }
constexpr uint32_t B_W = S_BAR, B_WO = S_BAR + 24, B_X = S_BAR + 32, B_S = S_BAR + 48, B_VX = S_BAR + 56, B_SX = S_BAR + 72, B_M = S_BAR + 88, B_T = S_BAR + 112;
constexpr int NB_QK = 1, NB_O = 2, NB_RED = 3, NB_P = 4, NB_AUX = 5, NB_PRO = 6, NB_X = 7, NB_GO = 8, NB_L = 9, NB_PV = 10;

constexpr float SM_SCALE = 0.08838834764831845f * 1.4426950408889634f;
constexpr uint32_t ONES = 0x3F803F80u;
constexpr uint32_t FULL_COUNT = 0x4200u;
#define XLIM NSEG
#define TGT_NS 1088
#define LOOK_NS 100
#define RCP_AT 2
#define NCH 2
#define XTMA_NS 50
#define REG_MAIN0 232
#define REG_MAIN1 232
#define REG_AUX 40

#define HAND_AT 26
#define VX_AT 0
#define PV_MODE 2
#define FLAG_NS 40
static_assert(REG_MAIN0 + REG_MAIN1 + REG_AUX <= 504, "the three warpgroups share 3 x 168 registers");
#define HSTAMP(i) do {} while (0)
#define HSTAMP2(i) do {} while (0)
#define TSTAMP(i, e) do {} while (0)

__device__ __forceinline__ void load_scores(uint32_t a, __half2 (&hs)[5]) {
    uint32_t r[10];
    ldsm4(r, a);
    ldsm4(r + 4, a + 512);
    ldsm2(r + 8, a + 1024);
    const __half2 hf = as_h2(0x38003800u);
#pragma unroll
    for (int T = 0; T < 5; T++) hs[T] = __hfma2(as_h2(r[2 * T]), hf, __hmul2(as_h2(r[2 * T + 1]), hf));
}
__device__ __forceinline__ void softmax_exp(const __half2 (&hs)[5], float (&ev)[10]) {
    __half2 m = __hmax2(__hmax2(__hmax2(hs[0], hs[1]), __hmax2(hs[2], hs[3])), hs[4]);
    const uint32_t mu = as_u32(m);
    const uint32_t m1 = __shfl_xor_sync(0xffffffffu, mu, 1), m2 = __shfl_xor_sync(0xffffffffu, mu, 2), m3 = __shfl_xor_sync(0xffffffffu, mu, 3);
    m = __hmax2(__hmax2(m, as_h2(m1)), __hmax2(as_h2(m2), as_h2(m3)));
    const float mc = -fmaxf(__low2float(m), __high2float(m)) * (2.f * SM_SCALE);
#pragma unroll
    for (int T = 0; T < 5; T++) {
        ev[2 * T] = ex2(fmaf(__low2float(hs[T]), 2.f * SM_SCALE, mc));
        ev[2 * T + 1] = ex2(fmaf(__high2float(hs[T]), 2.f * SM_SCALE, mc));
    }
}

__device__ __forceinline__ void x_scores(uint32_t sb, int seg, int wq, uint32_t L16, float (&ev)[10]) {
    __half2 hs[5];
    load_scores(sb + S_SX + (seg & 1) * 5120 + wq * 1280 + L16, hs);
    const int dg = (int)(L16 >> 6) - (int)((L16 >> 3) & 6) + 8 * wq;
#pragma unroll
    for (int T = 0; T < 4; T++) {
        uint32_t u = as_u32(hs[T]);
        if (dg < 8 * T + 1) u = (u & 0xFFFFu) | 0xFC000000u;
        if (dg < 8 * T) u = 0xFC00FC00u;
        hs[T] = as_h2(u);
    }
    softmax_exp(hs, ev);
}
__device__ __forceinline__ void x_probs(uint32_t sb, int seg, int wq, uint32_t L16, const float (&ev)[10]) {
    float l = ((ev[0] + ev[1]) + (ev[2] + ev[3])) + ((ev[4] + ev[5]) + (ev[6] + ev[7])) + (ev[8] + ev[9]);
    const float l1 = __shfl_xor_sync(0xffffffffu, l, 1), l2 = __shfl_xor_sync(0xffffffffu, l, 2), l3 = __shfl_xor_sync(0xffffffffu, l, 3);
    const float r = rcp((l + l1) + (l2 + l3));
    const uint32_t a = sb + S_PX + (seg & 1) * 4096 + wq * 640 + (L16 >> 2);
#pragma unroll
    for (int i = 0; i < 5; i++) sts32(a + i * 128, pack_bf16(ev[2 * i] * r, ev[2 * i + 1] * r));
}
__device__ __forceinline__ void x_pv_load(uint32_t sb, int seg, int w, uint32_t L16, uint32_t (&a)[3][4]) {
    lds128(a[0], sb + S_VX + (seg & 3) * 8192 + w * 1024 + L16);
    lds128(a[1], sb + S_VX + (seg & 3) * 8192 + w * 1024 + 512 + L16);
    lds64(a[2], sb + S_VM + (seg & 3) * 2048 + w * 256 + (L16 >> 1));
    a[2][2] = 0; a[2][3] = 0;
}
__device__ __forceinline__ void x_pv_run(uint32_t sb, int seg, const uint32_t (&a)[3][4], uint32_t (&pk)[8]) {
    const uint32_t d = ((sb + S_PX + (seg & 1) * 4096) & 0x3FFFF) >> 4;
    float o[16];
    wg_fence();
    wg_rs_n32<0, 40>(o, a[0], d | (8u << 16));
    wg_rs_n32<1, 40>(o, a[1], (d + 16) | (8u << 16));
    wg_rs_n32<1, 40>(o, a[2], d + 32);
    wg_commit();
    wg_wait<0>();
#pragma unroll
    for (int i = 0; i < 8; i++) pk[i] = pack_bf16(o[2 * i], o[2 * i + 1]);
}
__device__ __forceinline__ void x_pv_store(uint32_t sb, int seg, int w, uint32_t L16, const uint32_t (&pk)[8]) {
    const uint32_t a = sb + S_OX + (seg & 1) * 8192 + w * 1024 + L16;
    stsm4(a, pk[0], pk[1], pk[2], pk[3]);
    stsm4(a + 512, pk[4], pk[5], pk[6], pk[7]);
}
__device__ __forceinline__ void ox_store(uint32_t sb, int seg, uint32_t h) {
    fence_async_smem();
    bulk_s2g(g_ox + (seg * NH + h) * 512, sb + S_OX + (seg & 1) * 8192, 8192);
    bulk_commit();
}
__device__ __forceinline__ void ox_publish(int seg, uint32_t h) {
    bulk_wait0();
    asm volatile("fence.proxy.async.global;" ::: "memory");
    asm volatile("red.relaxed.gpu.global.add.u32 [%0], 1;" ::"l"(&g_flag[seg * 4 + (h >> 3)]) : "memory");
}
__device__ __forceinline__ void vx_store(uint32_t sb, int seg, uint32_t h) {
    fence_async_smem();
    bulk_s2g(g_vx + (h * 2 + (seg & 1)) * 512, sb + S_VX + (seg & 3) * 8192, 8192);
    bulk_commit();
}
__device__ __forceinline__ void vx_fetch(uint32_t sb, int seg, uint32_t h) {
    bulk_wait0();
    bulk_g2s_mc(sb + S_VX + (seg & 3) * 8192, g_vx + (h * 2 + (seg & 1)) * 512, 8192, sb + B_VX + (seg & 1) * 8, 3);
}

__device__ __forceinline__ void x_pack(const float (&d)[16], uint32_t (&pk)[8]) {
#pragma unroll
    for (int i = 0; i < 8; i++) pk[i] = pack_bf16(d[2 * i], d[2 * i + 1]);
}
__device__ __forceinline__ void x_write(uint32_t sb, const uint32_t (&pk)[8], int seg, bool isv, int w, uint32_t L16) {
    if (!isv) {
        const uint32_t a = sb + S_QX + (w >> 2) * 8192 + (seg & 1) * 4096 + (w & 3) * 256 + (L16 & 0xF0) + (L16 & 0x100) * 4;
        stsm4t(a, pk[0], pk[1], pk[2], pk[3]);
        stsm4t(a + 2048, pk[4], pk[5], pk[6], pk[7]);
    } else {
        const uint32_t a = sb + S_VX + (seg & 3) * 8192 + w * 1024 + L16;
        sts128(a, pk[0], pk[1], pk[2], pk[3]);
        sts128(a + 512, pk[4], pk[5], pk[6], pk[7]);
    }
}

template <int K0, int K1>
__device__ __forceinline__ void x_project(float (&d)[16], const uint32_t (&wA)[36][4], uint32_t desc) {
#pragma unroll
    for (int i = K0; i < K1; i++) {
        const uint32_t db = desc + (((i >> 2) * 4096 + (i & 3) * 32) >> 4);
        if (i == 0) wg_rs_n32<0>(d, wA[i], db); else wg_rs_n32<1>(d, wA[i], db);
    }
}

__device__ __forceinline__ void mem_scores(uint32_t sb, uint32_t peerA, uint32_t peerB, uint32_t off, const uint32_t (&q0)[4], const uint32_t (&q1)[4],
                                           const uint32_t (&k0)[4], const uint32_t (&k1)[4]) {
    float e0[4], o0[4], e1[4], o1[4];
    mma16z(e0, q0, k0[0], k0[1]);
    mma16z(o0, q0, k0[2], k0[3]);
    mma16z(e1, q1, k1[0], k1[1]);
    mma16z(o1, q1, k1[2], k1[3]);
    const uint32_t sc = pack_f16_sat((e0[0] + o0[2]) + (e1[0] + o1[2]), (e0[1] + o0[3]) + (e1[1] + o1[3]));
    st_async32(peerB + off, sc, peerB + B_S);
    st_async32(peerA + off, sc, peerA + B_S);
    sts32(sb + off, sc);
    __syncwarp();
}

__device__ __forceinline__ unsigned post_time(int s, uint32_t L16) {
    delay(1);
    const unsigned t = gtime() | 1;
    if (L16 == 0) asm volatile("st.relaxed.gpu.global.u32 [%0], %1;" ::"l"(g_time + s * 96 + blockIdx.x), "r"(t) : "memory");
    return t;
}
__device__ __forceinline__ void plan_look(uint32_t sb, int s, uint32_t L16, unsigned t) {
    const char* p = reinterpret_cast<const char*>(g_time) + s * 384 + (L16 < 384 ? L16 : 0);
    uint4 v;
    unsigned c = 0;
    do { v = ld_poll(p); } while (__any_sync(0xffffffffu, (v.x & v.y & v.z & v.w & 1) == 0) && ++c < SPIN_LIM);
    const int d = max(max((int)(v.x - t), (int)(v.y - t)), max((int)(v.z - t), (int)(v.w - t)));
    const unsigned tgt = t + min(__reduce_max_sync(0xffffffffu, d), 20000) + TGT_NS;
    if (L16 < 48) { const uint32_t r = mapa(sb, L16 >> 4); st_async32(r + S_TGT, tgt, r + B_T); }
}

template <int ROLE>
__device__ __forceinline__ void chain_main(const uint32_t sb, const uint32_t lane16, const int wq, const uint32_t j, const uint32_t h,
                                           const uint32_t peerA, const uint32_t peerB, char* const acc) {
    uint32_t L16 = lane16;
    constexpr bool isv = ROLE >= 2;
    constexpr int wg = ROLE & 1;
    const int w = wg * 4 + wq;
    const uint32_t xdesc = desc_lo(sb + S_XB);
    const uint32_t zero = h >> 20;
    uint32_t wA[36][4], woA[8][4], woB[4][4];
    float xd[16];
    {
        const int m = L16 >> 7, r = (L16 >> 4) & 7;
        const int blk = (ROLE == 1) ? ((wq & 2) * 2 + (wq & 1) + (m & 1) * 2) : (2 * wq + (m & 1));
        const uint32_t a = sb + wg * 24576 + ((m >> 1) * 8 + r) * 128 + ((blk ^ r) << 4);
        mbar_wait(sb + B_X, 0);
#pragma unroll
        for (int c = 0; c < 3; c++) {
            mbar_wait(sb + B_W + 8 * c, 0);
#pragma unroll
            for (int i = 0; i < 12; i++) ldsm4t(wA[12 * c + i], a + s_w(c) + i * 2048);
            if (c == 0) bar_arrive<NB_PRO, 384>();
            if (c == 2) { bar_sync<NB_O, 256>(); cluster_arrive(); }
            wg_fence();
            if (c == 0) x_project<0, 12>(xd, wA, xdesc);
            if (c == 1) x_project<12, 24>(xd, wA, xdesc);
            if (c == 2) x_project<24, 36>(xd, wA, xdesc);
            wg_commit();
            wg_wait<0>();
        }
        uint32_t pk[8];
        x_pack(xd, pk);
        x_write(sb, pk, 0, isv, w, L16);
        bar_arrive<NB_RED, 384>();
        mbar_wait(sb + B_WO, 0);
        const int ca = 3 * w + (m & 1), cb = 3 * w + 2;
        const uint32_t aA = sb + S_WO + (ca >> 3) * 16384 + ((m >> 1) * 8 + r) * 128 + (((ca & 7) ^ r) << 4);
        const int eB = ((m & 2) + ((r >> 1) & 1)) * 8 + 4 * (m & 1) + 2 * (r >> 2) + (r & 1);
        const uint32_t aB = sb + S_WO + (cb >> 3) * 16384 + eB * 128 + (((cb & 7) ^ (eB & 7)) << 4);
#pragma unroll
        for (int i = 0; i < 8; i++) ldsm4t(woA[i], aA + i * 2048);
#pragma unroll
        for (int i = 0; i < 4; i++) ldsm4t(woB[i], aB + i * 4096);
        mbar_wait(sb + B_X + 8, 0);
        cluster_wait();
        bar_sync<NB_O, 256>();
        wg_fence();
        x_project<0, 36>(xd, wA, xdesc + (XB_BYTES >> 4));
        wg_commit();
    }
    int s = 0;
#pragma unroll 1
    while (true) {
        const uint32_t par = s & 1;
        const uint32_t kx = sb + S_KX + par * 4096;
        asm volatile("" : "+r"(L16));
        uint32_t pk[8];
        if (wg == 0) { wg_wait<0>(); x_pack(xd, pk); x_write(sb, pk, s + 1, isv, w, L16); }
        float c0[4], c1[4];
        uint32_t k0[4], k1[4];
        {
            const uint32_t a = sb + S_MEM + L16;
            constexpr int CH = 18 / NCH;
            uint32_t b[3][4];
            bool ready = true;
            mbar_wait(sb + B_M, par);
            ldsm4(b[0], a);
            ldsm4(b[1], a + 512);
            if (wg == 1) { wg_wait<0>(); x_pack(xd, pk); }
            bar_arrive<NB_GO, 288>();
#pragma unroll
            for (int i = 0; i < 18; i++) {
                if ((i + 4) % CH == 0 && i + 4 < 18) ready = mbar_test(sb + B_M + ((i + 4) / CH) * 8, par);
                if ((i + 2) % CH == 0 && i + 2 < 18) { if (__builtin_expect(!ready, 0)) mbar_wait(sb + B_M + ((i + 2) / CH) * 8, par); }
                if (i + 2 < 18) ldsm4(b[(i + 2) % 3], a + (i + 2) * 512);
                if (ROLE == 0 && i == 16) ldsm4(k0, kx + wq * 1024 + L16);
                if (ROLE == 0 && i == 17) ldsm4(k1, kx + wq * 1024 + 512 + L16);
                if (i == 0) { mma16z(c0, wA[0], b[0][0], b[0][1]); mma16z(c1, wA[1], b[0][2], b[0][3]); }
                else { mma16(c0, wA[2 * i], b[i % 3][0], b[i % 3][1]); mma16(c1, wA[2 * i + 1], b[i % 3][2], b[i % 3][3]); }
            }
        }
        const uint32_t p0 = pack_bf16(c0[0] + c1[0], c0[1] + c1[1]), p1 = pack_bf16(c0[2] + c1[2], c0[3] + c1[3]);
        if (!isv) {
            stsm2t(sb + S_QM + w * 256 + L16, p0, p1);
            bar_sync<NB_QK, 384>();
            if (ROLE == 0) {
                uint32_t q0[4], q1[4];
                ldsm4(q0, sb + S_QM + L16);
                ldsm4(q1, sb + S_QM + 512 + L16);
                mem_scores(sb, peerA, peerB, S_SP + j * 128 + wq * 256 + (L16 >> 2), q0, q1, k0, k1);
                mbar_arrive_if0(sb + B_S, L16);
            } else {
                if (s + 2 < XLIM) mbar_wait(sb + B_X + par * 8, ((s + 2) >> 1) & 1);
                x_write(sb, pk, s + 1, isv, w, L16);
                if (wq != 0) {
                    const int rt = (wq == 3) ? 0 : 1;
                    const uint32_t qa = sb + S_QX + par * 4096 + rt * 2048 + (L16 & 0x80) * 8 + (L16 & 0x170);
                    const uint32_t kb0 = (wq == 2 ? kx + 2048 : sb + S_KM) + L16;
                    const uint32_t kb1 = (wq == 2 ? kx + 3072 : kx) + L16;
                    const uint32_t kb2 = kx + 1024 + L16;
                    float a0[4], a1[4], a2[4];
#pragma unroll
                    for (int hf = 0; hf < 2; hf++) {
                        uint32_t qa0[4], qa1[4], b[4];
                        ldsm4(qa0, qa + hf * 512);
                        ldsm4(qa1, qa + hf * 512 + 128);
                        ldsm4(b, kb0 + hf * 512);
                        if (hf == 0) mma16z(a0, qa0, b[0], b[1]); else mma16(a0, qa0, b[0], b[1]);
                        mma16(a0, qa1, b[2], b[3]);
                        ldsm4(b, kb1 + hf * 512);
                        if (hf == 0) mma16z(a1, qa0, b[0], b[1]); else mma16(a1, qa0, b[0], b[1]);
                        mma16(a1, qa1, b[2], b[3]);
                        ldsm4(b, kb2 + hf * 512);
                        if (hf == 0) mma16z(a2, qa0, b[0], b[1]); else mma16(a2, qa0, b[0], b[1]);
                        mma16(a2, qa1, b[2], b[3]);
                    }
                    mbar_wait(sb + B_S, par);
                    const uint32_t dst = peerB + S_SX + par * 5120 + j * 128 + rt * 2560 + (L16 >> 2);
                    const uint32_t bar = peerB + B_SX + par * 8;
                    const uint32_t T0 = (wq == 2 ? 2 : 4) * 256, T1 = (wq == 2 ? 3 : 0) * 256;
                    st_async32(dst + T0, pack_f16_sat(a0[0], a0[1]), bar);
                    st_async32(dst + 1280 + T0, pack_f16_sat(a0[2], a0[3]), bar);
                    if (wq != 2) st_async32(dst + T1, pack_f16_sat(a1[0], a1[1]), bar);
                    st_async32(dst + 1280 + T1, pack_f16_sat(a1[2], a1[3]), bar);
                    if (wq == 1) st_async32(dst + 256, pack_f16_sat(a2[0], a2[1]), bar);
                    if (wq != 2) st_async32(dst + 1280 + 256, pack_f16_sat(a2[2], a2[3]), bar);
                }
            }
        } else {
            const uint32_t off = S_VM + (s & 3) * 2048 + w * 256 + (L16 >> 1);
            st_async64(peerA + off, p0, p1, peerA + B_S);
            st_async64(peerB + off, p0, p1, peerB + B_S);
            sts64(sb + off, p0, p1);
            __syncwarp();
            mbar_expect_if0(sb + B_S, 160, L16);
            if (ROLE == 3) x_write(sb, pk, s + 1, isv, w, L16);
            if (PV_MODE == 2 && ROLE == 2) { bar_arrive<NB_P, 384>(); bar_arrive<NB_PV, 288>(); }
            else {
                uint32_t pva[3][4];
                x_pv_load(sb, s + 2, w, L16, pva);
                bar_sync<NB_P, 384>();
                x_pv_run(sb, s, pva, pk);
                if (PV_MODE == 2) x_pv_load(sb, s + 2, wq, L16, pva);
                x_pv_store(sb, s, w, L16, pk);
                if (PV_MODE == 2) { x_pv_run(sb, s, pva, pk); x_pv_store(sb, s, wq, L16, pk); }
                bar_arrive<NB_PV, 288>();
            }
            if (ROLE == 3 && s + 2 < XLIM) mbar_wait(sb + B_X + par * 8, ((s + 2) >> 1) & 1);
        }
        if (s == NSEG - 1) break;
        if (wg == 0) {
            if (!isv) mbar_wait(sb + B_VX + par * 8, (s >> 1) & 1);
            uint32_t va[4][4];
            const uint32_t vx = sb + S_VX + (s & 3) * 8192 + wq * 2048 + L16;
            const uint32_t vm = sb + S_VM + (s & 3) * 2048 + wq * 512 + (L16 >> 1);
            lds128(va[0], vx);
            lds128(va[2], vx + 1024);
            mbar_wait(sb + B_S, par);
            __half2 hs[5];
            load_scores(sb + S_SP + L16, hs);
            float ev[10];
            softmax_exp(hs, ev);
            lds128(va[1], vx + 512);
            lds128(va[3], vx + 1536);
            uint32_t p[5];
#pragma unroll
            for (int i = 0; i < 5; i++) p[i] = pack_bf16(ev[2 * i], ev[2 * i + 1]);
            uint32_t vm0[2], vm1[2];
            const uint32_t ones[4] = {ONES, ONES, ONES, ONES};
            float sum[4], o0[4], o1[4];
            mma16z(o0, va[0], p[0], p[1]);
            mma16z(o1, va[2], p[0], p[1]);
            mma16z(sum, ones, p[0], p[1]);
            lds64(vm0, vm);
            lds64(vm1, vm + 256);
            mma16(o0, va[1], p[2], p[3]);
            mma16(o1, va[3], p[2], p[3]);
            mma16(sum, ones, p[2], p[3]);
            mma8(o0, vm0[0], vm0[1], p[4]);
            mma8(o1, vm1[0], vm1[1], p[4]);
            mma8(sum, ONES, ONES, p[4]);
            stsm4t(sb + S_OM + wq * 512 + L16, pack_bf16(o0[0], o0[1]), pack_bf16(o0[2], o0[3]), pack_bf16(o1[0], o1[1]), pack_bf16(o1[2], o1[3]));
            sts64(sb + S_SUM + wq * 256 + (L16 >> 1), __float_as_uint(sum[0]), __float_as_uint(sum[1]));
        }
        bar_sync<NB_O, 256>();
        {
            float a0[4], a1[4], e[4];
            float2 sc;
            float sr, r0, r1, rr;
#pragma unroll
            for (int i = 0; i < 4; i++) {
                uint32_t b[4];
                ldsm4(b, sb + S_OM + i * 512 + L16);
                if (i == 0) {
                    mma16z(a0, woA[0], b[0], b[1]); mma16z(a1, woA[1], b[2], b[3]);
                    mma_sp<0>(e, b, woB[0]);
                } else {
                    if (i == 1) { sc = lds64f(sb + S_SUM + (L16 >> 1)); sr = lds32f(sb + S_SUM + ((L16 >> 4) & 0x1C)); }
                    const uint32_t z = __float_as_uint(a0[0]) & zero;
                    mma16(a0, woA[2 * i], b[0], b[1]); mma16(a1, woA[2 * i + 1], b[2], b[3]);
                    mma_sp<1>(e, b, woB[i]);
                    if (i == RCP_AT) {
                        r0 = rcp(__uint_as_float(__float_as_uint(sc.x) | z));
                        r1 = rcp(__uint_as_float(__float_as_uint(sc.y) | z));
                        rr = rcp(__uint_as_float(__float_as_uint(sr) | z));
                    }
                }
            }
            asm volatile("" : "+r"(L16));
            char* const rslot = acc + (slot_off(s + 1) + j * 64 + w * 4096) + lane_off(L16);
            asm volatile("red.relaxed.gpu.global.add.noftz.v4.bf16x2 [%0], {%1,%2,%3,%4};"
                         ::"l"(rslot), "r"(pack_bf16((a0[0] + a1[0]) * r0, (a0[1] + a1[1]) * r1)), "r"(pack_bf16((a0[2] + a1[2]) * r0, (a0[3] + a1[3]) * r1)),
                           "r"(pack_bf16((e[0] + e[2]) * rr, (e[1] + e[3]) * rr)), "r"(0x3F80u) : "memory");
        }
        bar_arrive<NB_RED, 384>();
        if (wg == 0) {
            bar_sync<NB_X, 256>();
            wg_fence();
            x_project<0, HAND_AT>(xd, wA, xdesc + par * (XB_BYTES >> 4));
            bar_arrive<NB_L, 256>();
            x_project<HAND_AT, 36>(xd, wA, xdesc + par * (XB_BYTES >> 4));
        } else {
            bar_arrive<NB_X, 256>();
            bar_sync<NB_L, 256>();
            wg_fence();
            x_project<0, 36>(xd, wA, xdesc + par * (XB_BYTES >> 4));
        }
        wg_commit();
        s++;
    }
    if (isv) {
#pragma unroll 1
        for (int seg = NSEG - 2; seg < NSEG; seg++) {
            uint32_t pva[3][4], pk[8];
            x_pv_load(sb, seg, w, L16, pva);
            bar_sync<NB_RED, 384>();
            x_pv_run(sb, seg, pva, pk);
            x_pv_store(sb, seg, w, L16, pk);
            bar_arrive<NB_QK, 384>();
        }
    }
}

template <bool isv>
__device__ __forceinline__ void chain_aux(const uint32_t sb, const uint32_t lane16, const int wq, const uint32_t j, const uint32_t h,
                                          const uint32_t peerA, const uint32_t peerB, const CUtensorMap* tmWo, const CUtensorMap* tmX,
                                          const bf16* __restrict__ mem0, char* const acc) {
    const int t = wq * 32 + (lane16 >> 4);
    TSTAMP(64, 0);
    cluster_arrive();
    {
        char* z = acc + h * 32768 + j * 64 + (t >> 2) * 256 + (t & 3) * 16;
#pragma unroll
        for (int i = 0; i < 4; i++) *reinterpret_cast<uint4*>(z + i * 8192) = make_uint4(0, 0, 0, 0);
        if (t < 64) g_time[blockIdx.x * 64 + t] = 0;
        if (blockIdx.x == 0) { g_flag[t] = 0; g_flag[128 + t] = 0; }
        for (int i = t; i < 576; i += 128) {
            const uint4 v = *reinterpret_cast<const uint4*>(mem0 + (i & 7) * DM + (i >> 3) * 8);
            sts128(sb + S_MEM + i * 16, v.x, v.y, v.z, v.w);
        }
        __threadfence();
        bar_sync<NB_AUX, 128>();
        if (t == 0) red_release(&g_zero_cnt, 1);
        asm volatile("griddepcontrol.launch_dependents;" ::: "memory");
        bar_sync<NB_PRO, 384>();
        if (t == 0) {
            fence_async_smem();
            mbar_expect(sb + B_WO, 49152);
            for (int b = 0; b < 3; b++) tma2d(sb + S_WO + b * 16384, tmWo, 192 * j + 64 * b, h * 128, sb + B_WO);
        }
        unsigned c = 0;
        while (ld_acquire(&g_zero_cnt) < 96 && ++c < SPIN_LIM) {}
        __syncwarp();
        for (int c2 = 0; c2 < 3; c2++) mbar_arrive_if0(sb + B_M + c2 * 8, lane16);
        cluster_wait();
        bar_sync<NB_RED, 384>();
        if (t == 0) {
            fence_async_smem();
            if (!isv) mbar_expect(sb + B_VX, 8192);
            else {
                bulk_s2c(peerA + S_VX, sb + S_VX, 8192, peerA + B_VX);
                bulk_s2c(peerB + S_VX, sb + S_VX, 8192, peerB + B_VX);
            }
            mbar_expect(sb + B_X, XB_BYTES);
            tma3d(sb + S_XB, tmX, 0, 64, 0, sb + B_X);
        }
        __syncwarp();
    }
    TSTAMP(0, 0);
    uint32_t L16 = lane16;
    const char* slot = acc + wq * 4096 + lane_off(L16);
    float ev[10];
    int s = 0;
#pragma unroll 1
    while (true) {
        const uint32_t par = s & 1;
        asm volatile("" : "+r"(L16));
        if (!isv) {
            if (wq == 0) {
                bar_sync<NB_QK, 384>();
                uint32_t q0[4], q1[4], k0[4], k1[4];
                ldsm4(q0, sb + S_QM + L16);
                ldsm4(k0, sb + S_KM + L16);
                ldsm4(q1, sb + S_QM + 512 + L16);
                ldsm4(k1, sb + S_KM + 512 + L16);
                mem_scores(sb, peerA, peerB, S_SP + j * 128 + 1024 + (L16 >> 2), q0, q1, k0, k1);
                mbar_expect_if0(sb + B_S, 640 + 2048, L16);
            } else if (wq == 3) {
                bar_sync<NB_GO, 288>();
                const unsigned t = post_time(s, L16);
                bar_sync<NB_QK, 384>();
                if (j == 0 && s < NSEG - 1) {
                    if (LOOK_NS) __nanosleep(LOOK_NS);
                    plan_look(sb, s, L16, t);
                }
            } else {
                bar_arrive<NB_QK, 384>();
                if (wq == 2) {
                    if (L16 == 0) {
                        if (s + 3 < XLIM) mbar_expect(sb + B_X + (par ^ 1) * 8, XB_BYTES);
                        mbar_expect(sb + B_VX + (par ^ 1) * 8, 8192);
                        mbar_expect(sb + B_T, 4);
                        if (s == 2 && h == 0 && j == 0) g_zero_cnt = 0;
                    }
                } else if (s + 3 < XLIM && j == 1) {
                    mbar_wait(sb + B_S, par);
                    if (XTMA_NS) __nanosleep(XTMA_NS);
                    if (L16 == 0) tma3d_mc(sb + S_XB + (par ^ 1) * XB_BYTES, tmX, 0, (s + 3) * SEG, 0, sb + B_X + (par ^ 1) * 8, 7);
                }
                __syncwarp();
            }
        } else {
            if (wq == 3) {
                bar_sync<NB_GO, 288>();
                post_time(s, L16);
            } else if (L16 == 0) {
                if (wq == 0) {
                    if (s >= 1) vx_fetch(sb, s, h);
                } else if (wq == 1) {
                    if (s >= 3) ox_publish(s - 3, h);
                } else {
                    mbar_expect(sb + B_SX + par * 8, 3584);
                    mbar_expect(sb + B_T, 4);
                    if (s + 3 < XLIM) mbar_expect(sb + B_X + (par ^ 1) * 8, XB_BYTES);
                }
            }
            __syncwarp();
            if (s >= 1) mbar_wait(sb + B_SX + (par ^ 1) * 8, ((s - 1) >> 1) & 1);
            fence_async_smem();
            bar_sync<NB_P, 384>();
            if (VX_AT == 0 && wq == 0) { if (L16 == 0 && s + 1 < NSEG) vx_store(sb, s + 1, h); __syncwarp(); }
            x_scores(sb, s + 1, wq, L16, ev);
            if (VX_AT == 1 && wq == 0) { if (L16 == 0 && s + 1 < NSEG) vx_store(sb, s + 1, h); __syncwarp(); }
            if (wq == 1) {
                bar_sync<NB_PV, 288>();
                if (L16 == 0 && s >= 2) ox_store(sb, s - 2, h);
                __syncwarp();
            }
            x_probs(sb, s + 1, wq, L16, ev);
        }
        if (s == NSEG - 1) break;
        mbar_wait(sb + B_T, par);
        const unsigned tgt = __float_as_uint(lds32f(sb + S_TGT));
        bar_sync<NB_RED, 384>();
        asm volatile("" : "+r"(L16));
        slot += par ? 32768 - 512 : 512;
        while ((int)(gtime() - tgt) < 0) {}
        uint4 v[6];
        look(v, slot);
        s++;
        const uint32_t ma = sb + S_MEM + wq * 384 + L16;
        unsigned c = 0;
        constexpr int CW = 6 / NCH;
        int done = NCH;
#pragma unroll
        for (int k = 0; k < NCH; k++) {
            uint32_t bad = 0;
#pragma unroll
            for (int i = CW * k; i < CW * k + CW; i++) { stsm2t(ma + i * 1536, v[i].x, v[i].y); stsm1(ma + i * 1536 + 256, v[i].z); bad |= v[i].w ^ FULL_COUNT; }
            const bool again = __any_sync(0xffffffffu, bad != 0);
            mbar_arrive_if0(sb + B_M + k * 8, L16 | (uint32_t)again);
            if (again) { done = k; break; }
        }
        if (done < NCH) {
            uint32_t bad;
            do {
                look(v, slot);
                bad = 0;
#pragma unroll
                for (int i = 0; i < 6; i++) { stsm2t(ma + i * 1536, v[i].x, v[i].y); stsm1(ma + i * 1536 + 256, v[i].z); bad |= v[i].w ^ FULL_COUNT; }
            } while (++c < SPIN_LIM && __any_sync(0xffffffffu, bad != 0));
            __syncwarp();
#pragma unroll
            for (int k = 0; k < NCH; k++) if (k >= done) mbar_arrive_if0(sb + B_M + k * 8, L16);
        }
        TSTAMP(s, c | t_pack);
    }
    if (!isv) {
        mbar_wait(sb + B_VX + 8, ((NSEG - 1) >> 1) & 1);
        mbar_wait(sb + B_S, 1);
    } else {
        fence_async_smem();
        bar_arrive<NB_RED, 384>();
        mbar_wait(sb + B_S, 1);
        mbar_wait(sb + B_SX + 8, ((NSEG - 1) >> 1) & 1);
        x_scores(sb, NSEG - 1, wq, L16, ev);
        bar_sync<NB_QK, 384>();
        if (wq == 2 && L16 == 0) ox_store(sb, NSEG - 2, h);
        if (wq == 1 && L16 == 0) ox_publish(NSEG - 3, h);
        __syncwarp();
        x_probs(sb, NSEG - 1, wq, L16, ev);
        fence_async_smem();
        bar_arrive<NB_RED, 384>();
        if (wq == 2) { if (L16 == 0) ox_publish(NSEG - 2, h); __syncwarp(); bar_arrive<NB_QK, 384>(); }
        else bar_sync<NB_QK, 384>();
        if (wq == 3 && L16 == 0) { ox_store(sb, NSEG - 1, h); ox_publish(NSEG - 1, h); }
    }
}

__global__ void __launch_bounds__(384, 1)
chain_kernel(const __grid_constant__ CUtensorMap tmWq, const __grid_constant__ CUtensorMap tmWk, const __grid_constant__ CUtensorMap tmWv,
             const __grid_constant__ CUtensorMap tmWo, const __grid_constant__ CUtensorMap tmX, const bf16* __restrict__ mem0, char* const acc) {
    extern __shared__ __align__(1024) uint8_t smem[];
    const uint32_t sb = smem_u32(smem);
    const int tid = threadIdx.x;
    const uint32_t L16 = __shfl_sync(0xffffffffu, (tid & 31) * 16, tid & 31);
    const int w = __shfl_sync(0xffffffffu, tid >> 5, 0), wg = w >> 2, wq = w & 3;
    uint32_t j, h;
    asm("mov.u32 %0, %%cluster_ctarank;" : "=r"(j));
    asm("mov.u32 %0, %%clusterid.x;" : "=r"(h));
    const bool isv = (j == 2);
    const uint32_t peerA = mapa(sb, isv ? 0 : (j ^ 1)), peerB = mapa(sb, isv ? 1 : 2);
    if (tid == 256) {
        for (int c = 0; c < 3; c++) { mbar_init(sb + B_W + 8 * c, 1); mbar_init(sb + B_M + 8 * c, 4); }
        mbar_init(sb + B_WO, 1); mbar_init(sb + B_T, 1);
        mbar_init(sb + B_X, 1); mbar_init(sb + B_X + 8, 1);
        mbar_init(sb + B_S, isv ? 8 : 5);
        mbar_init(sb + B_VX, 1); mbar_init(sb + B_VX + 8, 1);
        mbar_init(sb + B_SX, 1); mbar_init(sb + B_SX + 8, 1);
        asm volatile("fence.mbarrier_init.release.cluster;" ::: "memory");
        const CUtensorMap* m0 = isv ? &tmWv : &tmWq;
        const CUtensorMap* m1 = isv ? &tmWv : &tmWk;
        const int c0 = h * 128 + (isv ? 0 : 64 * j), c1 = h * 128 + (isv ? 64 : 64 * j);
        mbar_expect(sb + B_X, XB_BYTES);
        tma3d(sb + S_XB, &tmX, 0, 0, 0, sb + B_X);
#pragma unroll
        for (int c = 0; c < 3; c++) {
            mbar_expect(sb + B_W + 8 * c, 49152);
            tma2d(sb + s_w(c), m0, c0, c * 192, sb + B_W + 8 * c);
            tma2d(sb + s_w(c) + 24576, m1, c1, c * 192, sb + B_W + 8 * c);
        }
        mbar_expect(sb + B_X + 8, XB_BYTES);
        tma3d(sb + S_XB + XB_BYTES, &tmX, 0, 32, 0, sb + B_X + 8);
    }
    __syncthreads();
    if (wg == 2) {
        asm volatile("setmaxnreg.dec.sync.aligned.u32 %0;" ::"n"(REG_AUX));
        if (!isv) chain_aux<false>(sb, L16, wq, j, h, peerA, peerB, &tmWo, &tmX, mem0, acc);
        else chain_aux<true>(sb, L16, wq, j, h, peerA, peerB, &tmWo, &tmX, mem0, acc);
        __syncwarp();
        cluster_arrive(); cluster_wait();
        TSTAMP(65, 0);
    } else if (wg == 0) {
        asm volatile("setmaxnreg.inc.sync.aligned.u32 %0;" ::"n"(REG_MAIN0));
        if (!isv) chain_main<0>(sb, L16, wq, j, h, peerA, peerB, acc);
        else chain_main<2>(sb, L16, wq, j, h, peerA, peerB, acc);
        cluster_arrive(); cluster_wait();
    } else {
        asm volatile("setmaxnreg.inc.sync.aligned.u32 %0;" ::"n"(REG_MAIN1));
        if (!isv) chain_main<1>(sb, L16, wq, j, h, peerA, peerB, acc);
        else chain_main<3>(sb, L16, wq, j, h, peerA, peerB, acc);
        cluster_arrive(); cluster_wait();
    }
}

constexpr int NHELP = 36;
constexpr uint32_t H_U = 0;
constexpr uint32_t UT_PITCH = 4368;
constexpr uint32_t H_UT = 65536;
constexpr uint32_t KW_BYTES = 8320;
constexpr uint32_t H_KW = 135424;
constexpr uint32_t H_PAR = 201984;
constexpr uint32_t H_KD = 218368;
constexpr uint32_t H_STAGE = 0;
constexpr uint32_t H_RED = 196608;
constexpr uint32_t H_FIN = 212992;
constexpr uint32_t H_BAR = 229376;
constexpr uint32_t B_SMEM = H_BAR + 256;
constexpr uint32_t HB_U = H_BAR, HB_WO = H_BAR + 8, HB_FULL = H_BAR + 16, HB_EMPTY = H_BAR + 64, HB_RFULL = H_BAR + 112, HB_REMPTY = H_BAR + 128, HB_FIN = H_BAR + 144;
__device__ __align__(1024) uint4 g_part[4 * 9 * 4 * 4 * 128];

__device__ __forceinline__ float2 cmul(float2 a, float2 b) { return make_float2(fmaf(a.x, b.x, -a.y * b.y), fmaf(a.x, b.y, a.y * b.x)); }
__device__ __forceinline__ float2 csqr(float2 a) { return make_float2(fmaf(a.x, a.x, -a.y * a.y), (a.x + a.x) * a.y); }
__device__ __forceinline__ float2 cexp(float zr, float zi, float p) {
    const float m = ex2(zr * p);
    const float r = zi * p;
    const float a = (r - rintf(r)) * 6.283185307179586f;
    return make_float2(m * __cosf(a), m * __sinf(a));
}
__device__ __forceinline__ uint32_t pack_f16(float lo, float hi) { uint32_t r; asm("cvt.rn.f16x2.f32 %0, %1, %2;" : "=r"(r) : "f"(hi), "f"(lo)); return r; }
__device__ __forceinline__ void mma16h(float* d, const uint32_t* a, uint32_t b0, uint32_t b1) {
    asm volatile("mma.sync.aligned.m16n8k16.row.col.f32.f16.f16.f32 {%0,%1,%2,%3},{%4,%5,%6,%7},{%8,%9},{%0,%1,%2,%3};"
                 : "+f"(d[0]), "+f"(d[1]), "+f"(d[2]), "+f"(d[3]) : "r"(a[0]), "r"(a[1]), "r"(a[2]), "r"(a[3]), "r"(b0), "r"(b1));
}
__device__ __forceinline__ float bf_round(float x) { return __bfloat162float(__float2bfloat16_rn(x)); }
__device__ __forceinline__ uint32_t lds32(uint32_t a) { uint32_t v; asm volatile("ld.shared.b32 %0,[%1];" : "=r"(v) : "r"(a) : "memory"); return v; }
__device__ __forceinline__ uint32_t lds16(uint32_t a) { uint16_t v; asm volatile("ld.shared.u16 %0,[%1];" : "=h"(v) : "r"(a) : "memory"); return v; }

__device__ __forceinline__ void s4d_kernel(uint32_t par, uint32_t kd, uint32_t kw, int d, int lane, const bf16* __restrict__ logA, const bf16* __restrict__ Aim,
                                           const bf16* __restrict__ Cre, const bf16* __restrict__ Cim, const bf16* __restrict__ logdt) {
    const float dt = bf_round(expf(__bfloat162float(logdt[d])));
    float4 q[4];
    float cmax = 0.f, last = 0.f;
#pragma unroll
    for (int i = 0; i < 4; i++) {
        const int n = d * NST + i * 32 + lane;
        q[i].x = -bf_round(expf(__bfloat162float(logA[n]))) * dt * 1.4426950408889634f;
        q[i].y = __bfloat162float(Aim[n]) * dt * 0.15915494309189535f;
        q[i].z = 2.f * (__bfloat162float(Cre[n]) * dt);
        q[i].w = 2.f * (__bfloat162float(Cim[n]) * dt);
        cmax = fmaxf(cmax, fmaxf(fabsf(q[i].z), fabsf(q[i].w)));
        const float2 e = cexp(q[i].x, q[i].y, 2048.f);
        last += q[i].z * e.x - q[i].w * e.y;
    }
#pragma unroll
    for (int o = 16; o; o >>= 1) { cmax = fmaxf(cmax, __shfl_xor_sync(0xffffffffu, cmax, o)); last += __shfl_xor_sync(0xffffffffu, last, o); }
    const float cs = __uint_as_float(max(__float_as_uint(cmax) & 0x7F800000u, 0x00800000u));
    const float ci = 1.f / cs;
#pragma unroll
    for (int i = 0; i < 4; i++) sts128(par + (i * 32 + lane) * 16, __float_as_uint(q[i].x), __float_as_uint(q[i].y), __float_as_uint(q[i].z * ci), __float_as_uint(q[i].w * ci));
    __syncwarp();
    float acc[5][4];
#pragma unroll
    for (int i = 0; i < 5; i++) acc[i][0] = acc[i][1] = acc[i][2] = acc[i][3] = 0.f;
    const float g = (float)(lane >> 2);
#pragma unroll 1
    for (int ks = 0; ks < 16; ks++) {
        uint32_t A[5][4], B[4][2];
#pragma unroll
        for (int hf = 0; hf < 2; hf++) {
            uint32_t r[4];
            lds128(r, par + (ks * 8 + hf * 4 + (lane & 3)) * 16);
            const float zr = __uint_as_float(r[0]), zi = __uint_as_float(r[1]);
            const float2 c = make_float2(__uint_as_float(r[2]), __uint_as_float(r[3]));
            float2 y = cexp(zr, zi, g), x0 = cexp(zr, zi, 8.f * g + 128.f), x1 = cexp(zr, zi, 8.f * g + 192.f);
            const float2 xl = cexp(zr, zi, 8.f * g + 64.f);
#pragma unroll
            for (int k = 0; k < 4; k++) {
                const float2 cy = cmul(c, y);
                B[k][hf] = pack_f16(cy.x, -cy.y);
                A[k + 1][2 * hf] = pack_f16(x0.x, x0.y);
                A[k + 1][2 * hf + 1] = pack_f16(x1.x, x1.y);
                if (k < 3) { y = csqr(y); x0 = csqr(x0); x1 = csqr(x1); }
            }
            A[0][2 * hf] = pack_f16(y.x, y.y);
            A[0][2 * hf + 1] = pack_f16(xl.x, xl.y);
        }
        mma16h(acc[0], A[0], B[0][0], B[0][1]);
#pragma unroll
        for (int k = 0; k < 4; k++) mma16h(acc[k + 1], A[k + 1], B[k][0], B[k][1]);
    }
#pragma unroll
    for (int i = 0; i < 5; i++) {
        sts32(kd + i * 256 + lane * 4, pack_bf16(acc[i][0] * cs, acc[i][1] * cs));
        sts32(kd + i * 256 + 128 + lane * 4, pack_bf16(acc[i][2] * cs, acc[i][3] * cs));
    }
    if (lane == 0) sts32(kd + 1280, pack_bf16(last, 0.f));
    if (lane < 16) sts32(kw + lane * 4, 0);
    __syncwarp();
    uint32_t carry = 0;
#pragma unroll 4
    for (int it = 0; it < 64; it++) {
        const int l = it * 32 + lane;
        const int jx = l < 128 ? l : (int)__bfloat16_as_ushort(__float2bfloat16_rn((float)l)) - (133 << 7);
        const uint32_t v = lds16(kd + jx * 2);
        uint32_t pv = __shfl_up_sync(0xffffffffu, v, 1);
        if (lane == 0) pv = carry;
        carry = __shfl_sync(0xffffffffu, v, 31);
        sts32(kw + 64 + l * 4, v | (pv << 16));
    }
    __syncwarp();
}

__device__ __forceinline__ void s4d_conv(uint32_t ut, uint32_t kw, int lane) {
    float acc[16][4];
#pragma unroll
    for (int i = 0; i < 16; i++) acc[i][0] = acc[i][1] = acc[i][2] = acc[i][3] = 0.f;
    const uint32_t ka = kw + 64 + ((lane >> 2) - 2 * (lane & 3)) * 4;
    const uint32_t ua = ut + 256 + lane * 8;
#pragma unroll 1
    for (int rho = 0; rho < 8; rho++) {
        uint32_t B[16][2];
#pragma unroll
        for (int q = 0; q < 16; q++) lds64(B[q], ua + q * 256 - rho * 32);
#pragma unroll
        for (int m = 0; m < 16; m++) {
            uint32_t A[4];
            const uint32_t x = ka + m * 512 + rho * 64;
            A[0] = lds32(x); A[1] = lds32(x + 32); A[2] = lds32(x - 32); A[3] = A[0];
#pragma unroll
            for (int i = m; i < 16; i++) mma16(acc[i], A, B[i - m][0], B[i - m][1]);
        }
    }
    __syncwarp();
    const uint32_t ya = ut + 256 + (lane & 7) * 32 + ((lane >> 3) & 1) * 16 + (lane >> 4) * 256;
#pragma unroll
    for (int i = 0; i < 16; i += 2)
        stsm4t(ya + i * 256, pack_bf16(acc[i][0], acc[i][1]), pack_bf16(acc[i][2], acc[i][3]),
               pack_bf16(acc[i + 1][0], acc[i + 1][1]), pack_bf16(acc[i + 1][2], acc[i + 1][3]));
}

__global__ void __launch_bounds__(384, 1)
helper_kernel(const __grid_constant__ CUtensorMap tmU, const __grid_constant__ CUtensorMap tmY, const __grid_constant__ CUtensorMap tmWo,
              const bf16* __restrict__ logA, const bf16* __restrict__ Aim, const bf16* __restrict__ Cre, const bf16* __restrict__ Cim,
              const bf16* __restrict__ logdt, const bf16* __restrict__ Dskip, bf16* __restrict__ out) {
    extern __shared__ __align__(1024) uint8_t smem[];
    const uint32_t sb = smem_u32(smem);
    const int tid = threadIdx.x, lane = tid & 31;
    const int w = __shfl_sync(0xffffffffu, tid >> 5, 0);
    const int d0 = blockIdx.x * 16;
    HSTAMP(0);
    if (tid == 0) {
        mbar_init(sb + HB_U, 1); mbar_init(sb + HB_WO, 1);
        for (int i = 0; i < 6; i++) { mbar_init(sb + HB_FULL + 8 * i, 1); mbar_init(sb + HB_EMPTY + 8 * i, 4); }
        for (int i = 0; i < 2; i++) { mbar_init(sb + HB_RFULL + 8 * i, 4); mbar_init(sb + HB_REMPTY + 8 * i, 4); mbar_init(sb + HB_FIN + 8 * i, 2); }
        fence_async_smem();
        mbar_expect(sb + HB_U, 65536);
        for (int i = 0; i < 8; i++) tma2d(sb + H_U + i * 8192, &tmU, d0, i * 256, sb + HB_U);
    }
    __syncthreads();
    const int m = lane >> 3, r = lane & 7;
    if (w < 8) {
        s4d_kernel(sb + H_PAR + w * 2048, sb + H_KD + w * 1296, sb + H_KW + w * KW_BYTES, d0 + w, lane, logA, Aim, Cre, Cim, logdt);
    } else {
        for (int i = tid - 256; i < 256; i += 128) sts128(sb + H_UT + (i >> 4) * UT_PITCH + (i & 15) * 16, 0, 0, 0, 0);
        mbar_wait(sb + HB_U, 0);
        const uint32_t src = sb + H_U + ((m & 1) * 8 + r) * 32 + (((m >> 1) ^ (r >> 2)) << 4);
        const uint32_t dst = sb + H_UT + 256 + (lane >> 2) * UT_PITCH + (lane & 3) * 8;
#pragma unroll 4
        for (int grp = w - 8; grp < 128; grp += 4) {
            uint32_t v[4];
            ldsm4t(v, src + grp * 512);
            sts64(dst + grp * 32, v[0], v[1]);
            sts64(dst + 8 * UT_PITCH + grp * 32, v[2], v[3]);
        }
    }
    __syncthreads();
    HSTAMP(1);
    if (w < 8) {
        s4d_conv(sb + H_UT + w * UT_PITCH, sb + H_KW + w * KW_BYTES, lane);
        s4d_kernel(sb + H_PAR + w * 2048, sb + H_KD + w * 1296, sb + H_KW + w * KW_BYTES, d0 + 8 + w, lane, logA, Aim, Cre, Cim, logdt);
        s4d_conv(sb + H_UT + (8 + w) * UT_PITCH, sb + H_KW + w * KW_BYTES, lane);
    }
    __syncthreads();
    HSTAMP(2);
    const int cc = blockIdx.x % 9, kq = blockIdx.x / 9;
    {
        const __nv_bfloat162 D0 = *reinterpret_cast<const __nv_bfloat162*>(Dskip + d0 + (lane & 3) * 2);
        const __nv_bfloat162 D1 = *reinterpret_cast<const __nv_bfloat162*>(Dskip + d0 + 8 + (lane & 3) * 2);
        const uint32_t ua = sb + H_U + ((m & 1) * 8 + r) * 32 + (((m >> 1) ^ (r >> 2)) << 4);
        const uint32_t ya = sb + H_UT + 256 + ((m >> 1) * 8 + r) * UT_PITCH + (m & 1) * 16;
        for (int grp = w; grp < 128; grp += 12) {
            uint32_t u[4], y[4];
            ldsm4(u, ua + grp * 512);
            ldsm4t(y, ya + grp * 32);
#pragma unroll
            for (int i = 0; i < 4; i++) {
                const __nv_bfloat162 o = __hadd2_rn(*reinterpret_cast<__nv_bfloat162*>(&y[i]), __hmul2_rn(*reinterpret_cast<__nv_bfloat162*>(&u[i]), i < 2 ? D0 : D1));
                y[i] = *reinterpret_cast<const uint32_t*>(&o);
            }
            stsm4(ua + grp * 512, y[0], y[1], y[2], y[3]);
        }
        fence_async_smem();
        __syncthreads();
        if (tid == 0) {
            for (int i = 0; i < 8; i++)
                asm volatile("cp.async.bulk.tensor.2d.global.shared::cta.bulk_group [%0, {%1,%2}], [%3];" ::"l"(&tmY), "r"(DM + d0), "r"(i * 256), "r"(sb + H_U + i * 8192) : "memory");
            bulk_commit();
            mbar_expect(sb + HB_WO, 131072);
            for (int i = 0; i < 8; i++) tma2d(sb + 65536 + i * 16384, &tmWo, cc * 64, (kq * 8 + i) * 128, sb + HB_WO);
            asm volatile("cp.async.bulk.wait_group.read 0;" ::: "memory");
        }
    }
    __syncwarp();
    if (w < 8) {
        asm volatile("setmaxnreg.inc.sync.aligned.u32 208;");
        const int wg = w >> 2;
        uint32_t wo[32][4];
        mbar_wait(sb + HB_WO, 0);
        const uint32_t a = sb + 65536 + wg * 65536 + ((m >> 1) * 8 + r) * 128 + (((2 * (w & 3) + (m & 1)) ^ r) << 4);
#pragma unroll
        for (int i = 0; i < 32; i++) ldsm4t(wo[i], a + i * 2048);
        __syncthreads();
        HSTAMP(3);
        const int t = tid & 127;
        int st = 0, ph = 0;
#pragma unroll 1
        for (int s = 0; s < NSEG; s++) {
            mbar_wait_long(sb + HB_FULL + (st * 2 + wg) * 8, ph);
            const uint32_t desc = (((sb + H_STAGE + st * 65536 + wg * 32768) & 0x3FFFF) >> 4) | (8u << 16);
            float d[16];
            wg_fence();
#pragma unroll
            for (int i = 0; i < 32; i++) {
                if (i == 0) wg_rs_n32<0, 16, 1>(d, wo[i], desc); else wg_rs_n32<1, 16, 1>(d, wo[i], desc + i * 64);
            }
            wg_commit();
            wg_wait<0>();
            mbar_arrive_if0(sb + HB_EMPTY + (st * 2 + wg) * 8, lane);
            if (++st == 3) { st = 0; ph ^= 1; }
            const uint32_t ra = sb + H_RED + (s & 1) * 8192 + t * 16;
            if (wg == 0) {
                if (s >= 2) mbar_wait_long(sb + HB_REMPTY + (s & 1) * 8, ((s - 2) >> 1) & 1);
#pragma unroll
                for (int i = 0; i < 4; i++) sts128(ra + i * 2048, __float_as_uint(d[4 * i]), __float_as_uint(d[4 * i + 1]), __float_as_uint(d[4 * i + 2]), __float_as_uint(d[4 * i + 3]));
                __syncwarp();
                mbar_arrive_if0(sb + HB_RFULL + (s & 1) * 8, lane);
            } else {
                mbar_wait_long(sb + HB_RFULL + (s & 1) * 8, (s >> 1) & 1);
                if (s >= 2) mbar_wait_long(sb + HB_FIN + (s & 1) * 8, ((s - 2) >> 1) & 1);
                uint4* dst = g_part + (((s & 3) * 9 + cc) * 16 + kq) * 128 + t;
#pragma unroll
                for (int i = 0; i < 4; i++) {
                    uint32_t p[4];
                    lds128(p, ra + i * 2048);
#pragma unroll
                    for (int k = 0; k < 4; k++) p[k] = ((__float_as_uint(__uint_as_float(p[k]) + d[4 * i + k]) + 64) & ~127u) | (s + 1);
                    asm volatile("st.relaxed.gpu.global.v4.u32 [%0], {%1,%2,%3,%4};" ::"l"(dst + i * 512), "r"(p[0]), "r"(p[1]), "r"(p[2]), "r"(p[3]) : "memory");
                }
                __syncwarp();
                mbar_arrive_if0(sb + HB_REMPTY + (s & 1) * 8, lane);
            }
        }
        if (tid == 0) bulk_wait0();
    } else {
        asm volatile("setmaxnreg.dec.sync.aligned.u32 88;");
        __syncthreads();
        if (w == 8) {
            if (lane == 0) {
                int st = 0, ph = 1;
                for (int s = 0; s < NSEG; s++) {
                    unsigned c = 0;
                    while (ld_acquire(&g_flag[s * 4 + kq]) < 8 && ++c < LONG_LIM) __nanosleep(FLAG_NS);
                    asm volatile("fence.proxy.async;" ::: "memory");
                    for (int g = 0; g < 2; g++) {
                        const uint32_t bar = sb + HB_FULL + (st * 2 + g) * 8;
                        mbar_wait_long(sb + HB_EMPTY + (st * 2 + g) * 8, ph);
                        mbar_expect(bar, 32768);
                        asm volatile("cp.async.bulk.shared::cluster.global.mbarrier::complete_tx::bytes [%0], [%1], %2, [%3];"
                                     ::"r"(sb + H_STAGE + st * 65536 + g * 32768), "l"(g_ox + (s * NH + kq * 8 + g * 4) * 512), "r"(32768), "r"(bar) : "memory");
                    }
                    if (++st == 3) { st = 0; ph ^= 1; }
                }
            }
        } else if (w < 11) {
            const int f = w - 9;
            const uint32_t fa = sb + H_FIN + f * 512;
            for (int s = 0; s < NSEG; s++) {
                mbar_wait_long(sb + HB_REMPTY + (s & 1) * 8, (s >> 1) & 1);
                const uint4* src = g_part + (((s & 3) * 9 + cc) * 16 + kq * 4) * 128 + f * 64 + lane;
                uint4 v[8];
                unsigned c = 0;
                while (true) {
                    uint32_t bad = 0;
#pragma unroll
                    for (int i = 0; i < 8; i++) v[i] = ld_poll(src + (i >> 1) * 128 + (i & 1) * 32);
#pragma unroll
                    for (int i = 0; i < 8; i++) bad |= (v[i].x ^ (s + 1)) | (v[i].y ^ (s + 1)) | (v[i].z ^ (s + 1)) | (v[i].w ^ (s + 1));
                    if (!__any_sync(0xffffffffu, (bad & 127) != 0) || ++c >= LONG_LIM) break;
                    __nanosleep(FLAG_NS);
                }
                mbar_arrive_if0(sb + HB_FIN + (s & 1) * 8, lane);
                uint32_t pk[4];
#pragma unroll
                for (int u = 0; u < 2; u++) {
                    float o[4] = {0.f, 0.f, 0.f, 0.f};
#pragma unroll
                    for (int k = 0; k < 4; k++) {
                        o[0] += __uint_as_float(v[2 * k + u].x & ~127u); o[1] += __uint_as_float(v[2 * k + u].y & ~127u);
                        o[2] += __uint_as_float(v[2 * k + u].z & ~127u); o[3] += __uint_as_float(v[2 * k + u].w & ~127u);
                    }
                    pk[2 * u] = pack_bf16(o[0], o[1]); pk[2 * u + 1] = pack_bf16(o[2], o[3]);
                }
                stsm4t(fa + r * 64 + ((m ^ (r >> 1)) << 4), pk[0], pk[1], pk[2], pk[3]);
                __syncwarp();
                uint32_t o4[4];
                lds128(o4, fa + (lane >> 2) * 64 + (((lane & 3) ^ (lane >> 3)) << 4));
                *reinterpret_cast<uint4*>(out + (s * SEG + kq * 8 + (lane >> 2)) * OUTW + cc * 64 + f * 32 + (lane & 3) * 8) = make_uint4(o4[0], o4[1], o4[2], o4[3]);
                __syncwarp();
                HSTAMP2(s);
            }
            asm volatile("griddepcontrol.wait;" ::: "memory");
        }
    }
}

typedef CUresult (*EncodeFn)(CUtensorMap*, CUtensorMapDataType, cuuint32_t, void*, const cuuint64_t*, const cuuint64_t*, const cuuint32_t*,
                             const cuuint32_t*, CUtensorMapInterleave, CUtensorMapSwizzle, CUtensorMapL2promotion, CUtensorMapFloatOOBfill);

void make_map(EncodeFn fn, CUtensorMap* m, const void* p, int rank, const cuuint64_t* dims, const cuuint64_t* strides, const cuuint32_t* box,
              CUtensorMapSwizzle sw = CU_TENSOR_MAP_SWIZZLE_128B, CUtensorMapL2promotion pr = CU_TENSOR_MAP_L2_PROMOTION_L2_128B) {
    const cuuint32_t es[3] = {1, 1, 1};
    fn(m, CU_TENSOR_MAP_DATA_TYPE_BFLOAT16, rank, const_cast<void*>(p), dims, strides, box, es, CU_TENSOR_MAP_INTERLEAVE_NONE,
       sw, pr, CU_TENSOR_MAP_FLOAT_OOB_FILL_NONE);
}

}

extern "C" void kernel_launch(void* const* d_in, const int* in_sizes, int n_in, void* d_out, int out_size) {
    const bf16* x = (const bf16*)d_in[0];
    const bf16* mem0 = (const bf16*)d_in[1];
    const bf16* Wo = (const bf16*)d_in[5];
    bf16* out = (bf16*)d_out;

    static EncodeFn enc = nullptr;
    static char* acc = nullptr;
    if (!enc) {
        void* p = nullptr;
        cudaGetSymbolAddress(&p, g_acc);
        acc = reinterpret_cast<char*>((reinterpret_cast<uintptr_t>(p) + 32767) & ~(uintptr_t)32767);
        void* fn = nullptr;
        cudaDriverEntryPointQueryResult st;
        cudaGetDriverEntryPoint("cuTensorMapEncodeTiled", &fn, cudaEnableDefault, &st);
        enc = (EncodeFn)fn;
        cudaFuncSetAttribute(chain_kernel, cudaFuncAttributeMaxDynamicSharedMemorySize, A_SMEM);
        cudaFuncSetAttribute(helper_kernel, cudaFuncAttributeMaxDynamicSharedMemorySize, B_SMEM);
    }
    CUtensorMap tmW[3], tmWo, tmX;
    {
        const cuuint64_t dims[2] = {4096, 576}, str[1] = {8192};
        const cuuint32_t box[2] = {64, 192};
        for (int i = 0; i < 3; i++) make_map(enc, &tmW[i], d_in[2 + i], 2, dims, str, box);
    }
    {
        const cuuint64_t dims[2] = {576, 4096}, str[1] = {1152};
        const cuuint32_t box[2] = {64, 128};
        make_map(enc, &tmWo, Wo, 2, dims, str, box);
    }
    {
        const cuuint64_t dims[3] = {64, 2048, 9}, str[2] = {1152, 128};
        const cuuint32_t box[3] = {64, 32, 9};
        make_map(enc, &tmX, x, 3, dims, str, box);
    }
    CUtensorMap tmU, tmY;
    {
        const cuuint64_t dimsU[2] = {576, 2048}, strU[1] = {1152}, dimsY[2] = {1152, 2048}, strY[1] = {2304};
        const cuuint32_t box[2] = {16, 256};
        make_map(enc, &tmU, d_in[7], 2, dimsU, strU, box, CU_TENSOR_MAP_SWIZZLE_32B);
        make_map(enc, &tmY, out, 2, dimsY, strY, box, CU_TENSOR_MAP_SWIZZLE_32B, CU_TENSOR_MAP_L2_PROMOTION_NONE);
    }
    cudaStream_t st = cudaStreamPerThread;
    {
        cudaLaunchConfig_t cfg = {};
        cfg.gridDim = dim3(96); cfg.blockDim = dim3(384); cfg.dynamicSmemBytes = A_SMEM; cfg.stream = st;
        cudaLaunchAttribute at[1];
        at[0].id = cudaLaunchAttributeClusterDimension;
        at[0].val.clusterDim.x = 3; at[0].val.clusterDim.y = 1; at[0].val.clusterDim.z = 1;
        cfg.attrs = at; cfg.numAttrs = 1;
        cudaLaunchKernelEx(&cfg, chain_kernel, tmW[0], tmW[1], tmW[2], tmWo, tmX, mem0, acc);
    }
    {
        cudaLaunchConfig_t cfg = {};
        cfg.gridDim = dim3(NHELP); cfg.blockDim = dim3(384); cfg.dynamicSmemBytes = B_SMEM; cfg.stream = st;
        cudaLaunchAttribute at[1];
        at[0].id = cudaLaunchAttributeProgrammaticStreamSerialization;
        at[0].val.programmaticStreamSerializationAllowed = 1;
        cfg.attrs = at; cfg.numAttrs = 1;
        cudaLaunchKernelEx(&cfg, helper_kernel, tmU, tmY, tmWo, (const bf16*)d_in[8], (const bf16*)d_in[9], (const bf16*)d_in[10],
                           (const bf16*)d_in[11], (const bf16*)d_in[12], (const bf16*)d_in[13], out);
    }
}
```

```cpp
#include <cuda_runtime.h>
#include <cuda_bf16.h>
#include <cuda_fp16.h>
#include <cuda.h>
#include <stdint.h>

typedef __nv_bfloat16 bf16;

namespace {

constexpr int DM = 576, NH = 32, DH = 128, SEG = 32, NSEG = 64, SEQ = 2048, NST = 128;
constexpr int OUTW = 2 * DM;
constexpr unsigned SPIN_LIM = 1u << 15;

__device__ __align__(1024) uint4 g_acc[33 * 2048];
__device__ __align__(128) unsigned g_time[NSEG * 96];
__device__ __align__(1024) uint4 g_ox[NSEG * NH * 512];
__device__ __align__(1024) uint4 g_vx[NH * 2 * 512];
__device__ __align__(128) unsigned g_flag[NSEG * 4];
__device__ unsigned g_zero_cnt;

__device__ __forceinline__ uint32_t smem_u32(const void* p) { return (uint32_t)__cvta_generic_to_shared(p); }
__device__ __forceinline__ unsigned clk() { unsigned c; asm volatile("mov.u32 %0, %%clock;" : "=r"(c)::"memory"); return c; }
__device__ __forceinline__ unsigned gtime() { unsigned t; asm volatile("mov.u32 %0, %%globaltimer_lo;" : "=r"(t)::"memory"); return t; }
__device__ __forceinline__ uint32_t slot_off(int s) { return (s >> 1) * 32768 + (s & 1) * 512; }
__device__ __forceinline__ uint32_t lane_off(uint32_t L16) { return (L16 & 0x180) * 8 + (L16 & 0x40) * 4 + (L16 & 0x30); }
__device__ __forceinline__ uint32_t mapa(uint32_t a, uint32_t r) { uint32_t o; asm("mapa.shared::cluster.u32 %0, %1, %2;" : "=r"(o) : "r"(a), "r"(r)); return o; }
__device__ __forceinline__ void mbar_init(uint32_t b, uint32_t n) { asm volatile("mbarrier.init.shared::cta.b64 [%0], %1;" ::"r"(b), "r"(n) : "memory"); }
__device__ __forceinline__ void mbar_arrive(uint32_t b) { asm volatile("mbarrier.arrive.shared::cta.b64 _, [%0];" ::"r"(b) : "memory"); }
__device__ __forceinline__ void mbar_expect(uint32_t b, uint32_t tx) { asm volatile("mbarrier.arrive.expect_tx.shared::cta.b64 _, [%0], %1;" ::"r"(b), "r"(tx) : "memory"); }
__device__ __forceinline__ bool mbar_try(uint32_t b, uint32_t par) {
    uint32_t ok;
    asm volatile("{.reg .pred p; mbarrier.try_wait.parity.shared::cta.b64 p, [%1], %2; selp.u32 %0, 1, 0, p;}" : "=r"(ok) : "r"(b), "r"(par) : "memory");
    return ok;
}
__device__ __forceinline__ bool mbar_test(uint32_t b, uint32_t par) {
    uint32_t ok;
    asm volatile("{.reg .pred p; mbarrier.test_wait.parity.shared::cta.b64 p, [%1], %2; selp.u32 %0, 1, 0, p;}" : "=r"(ok) : "r"(b), "r"(par) : "memory");
    return ok;
}
__device__ __forceinline__ void mbar_wait(uint32_t b, uint32_t par) {
    asm volatile("{.reg .pred p, q; .reg .u32 c; mov.u32 c, 0;\n"
                 "W: mbarrier.try_wait.parity.shared::cta.b64 p, [%0], %1;\n"
                 "@p bra D;\n add.u32 c, c, 1; setp.lt.u32 q, c, %2;\n @q bra W;\n D:\n}" ::"r"(b), "r"(par), "n"(SPIN_LIM) : "memory");
}
constexpr unsigned LONG_LIM = 1u << 17;
__device__ __forceinline__ void mbar_wait_long(uint32_t b, uint32_t par) {
    asm volatile("{.reg .pred p, q; .reg .u32 c; mov.u32 c, 0;\n"
                 "W: mbarrier.try_wait.parity.shared::cta.b64 p, [%0], %1;\n"
                 "@p bra D;\n add.u32 c, c, 1; setp.lt.u32 q, c, %2;\n @q bra W;\n D:\n}" ::"r"(b), "r"(par), "n"(LONG_LIM) : "memory");
}
__device__ __forceinline__ void cluster_sync() { asm volatile("barrier.cluster.arrive.aligned; barrier.cluster.wait.aligned;" ::: "memory"); }
__device__ __forceinline__ void fence_async_smem() { asm volatile("fence.proxy.async.shared::cta;" ::: "memory"); }
__device__ __forceinline__ void ldsm4(uint32_t* r, uint32_t a) { asm volatile("ldmatrix.sync.aligned.m8n8.x4.shared.b16 {%0,%1,%2,%3},[%4];" : "=r"(r[0]), "=r"(r[1]), "=r"(r[2]), "=r"(r[3]) : "r"(a) : "memory"); }
__device__ __forceinline__ void ldsm4t(uint32_t* r, uint32_t a) { asm volatile("ldmatrix.sync.aligned.m8n8.x4.trans.shared.b16 {%0,%1,%2,%3},[%4];" : "=r"(r[0]), "=r"(r[1]), "=r"(r[2]), "=r"(r[3]) : "r"(a) : "memory"); }
__device__ __forceinline__ void stsm1(uint32_t a, uint32_t r0) { asm volatile("stmatrix.sync.aligned.m8n8.x1.shared.b16 [%0],{%1};" ::"r"(a), "r"(r0) : "memory"); }
__device__ __forceinline__ void stsm2t(uint32_t a, uint32_t r0, uint32_t r1) { asm volatile("stmatrix.sync.aligned.m8n8.x2.trans.shared.b16 [%0],{%1,%2};" ::"r"(a), "r"(r0), "r"(r1) : "memory"); }
__device__ __forceinline__ void stsm4t(uint32_t a, uint32_t r0, uint32_t r1, uint32_t r2, uint32_t r3) { asm volatile("stmatrix.sync.aligned.m8n8.x4.trans.shared.b16 [%0],{%1,%2,%3,%4};" ::"r"(a), "r"(r0), "r"(r1), "r"(r2), "r"(r3) : "memory"); }
__device__ __forceinline__ void stsm4(uint32_t a, uint32_t r0, uint32_t r1, uint32_t r2, uint32_t r3) { asm volatile("stmatrix.sync.aligned.m8n8.x4.shared.b16 [%0],{%1,%2,%3,%4};" ::"r"(a), "r"(r0), "r"(r1), "r"(r2), "r"(r3) : "memory"); }
__device__ __forceinline__ void sts32(uint32_t a, uint32_t v) { asm volatile("st.shared.b32 [%0], %1;" ::"r"(a), "r"(v) : "memory"); }
__device__ __forceinline__ void sts64(uint32_t a, uint32_t x, uint32_t y) { asm volatile("st.shared.v2.b32 [%0], {%1,%2};" ::"r"(a), "r"(x), "r"(y) : "memory"); }
__device__ __forceinline__ void sts128(uint32_t a, uint32_t x, uint32_t y, uint32_t z, uint32_t w) { asm volatile("st.shared.v4.b32 [%0], {%1,%2,%3,%4};" ::"r"(a), "r"(x), "r"(y), "r"(z), "r"(w) : "memory"); }
__device__ __forceinline__ void lds64(uint32_t* r, uint32_t a) { asm volatile("ld.shared.v2.b32 {%0,%1},[%2];" : "=r"(r[0]), "=r"(r[1]) : "r"(a) : "memory"); }
__device__ __forceinline__ float2 lds64f(uint32_t a) { float2 v; asm volatile("ld.shared.v2.f32 {%0,%1},[%2];" : "=f"(v.x), "=f"(v.y) : "r"(a) : "memory"); return v; }
__device__ __forceinline__ void lds128(uint32_t* r, uint32_t a) { asm volatile("ld.shared.v4.b32 {%0,%1,%2,%3},[%4];" : "=r"(r[0]), "=r"(r[1]), "=r"(r[2]), "=r"(r[3]) : "r"(a) : "memory"); }
__device__ __forceinline__ void st_async64(uint32_t a, uint32_t x, uint32_t y, uint32_t bar) {
    asm volatile("st.async.weak.shared::cluster.mbarrier::complete_tx::bytes.v2.b32 [%0], {%1,%2}, [%3];" ::"r"(a), "r"(x), "r"(y), "r"(bar) : "memory");
}
__device__ __forceinline__ void st_async32(uint32_t a, uint32_t x, uint32_t bar) {
    asm volatile("st.async.weak.shared::cluster.mbarrier::complete_tx::bytes.b32 [%0], %1, [%2];" ::"r"(a), "r"(x), "r"(bar) : "memory");
}
__device__ __forceinline__ void ldsm2(uint32_t* r, uint32_t a) { asm volatile("ldmatrix.sync.aligned.m8n8.x2.shared.b16 {%0,%1},[%2];" : "=r"(r[0]), "=r"(r[1]) : "r"(a) : "memory"); }
__device__ __forceinline__ uint32_t pack_f16_sat(float lo, float hi) { uint32_t r; asm("cvt.rn.satfinite.f16x2.f32 %0, %1, %2;" : "=r"(r) : "f"(hi), "f"(lo)); return r; }
__device__ __forceinline__ __half2 as_h2(uint32_t x) { return *reinterpret_cast<__half2*>(&x); }
__device__ __forceinline__ uint32_t as_u32(__half2 x) { return *reinterpret_cast<uint32_t*>(&x); }
__device__ __forceinline__ uint32_t pack_bf16(float lo, float hi) { uint32_t r; asm("cvt.rn.bf16x2.f32 %0, %1, %2;" : "=r"(r) : "f"(hi), "f"(lo)); return r; }
__device__ __forceinline__ float ex2(float x) { float r; asm("ex2.approx.ftz.f32 %0, %1;" : "=f"(r) : "f"(x)); return r; }
__device__ __forceinline__ float rcp(float x) { float r; asm("rcp.approx.ftz.f32 %0, %1;" : "=f"(r) : "f"(x)); return r; }
__device__ __forceinline__ void mma16(float* d, const uint32_t* a, uint32_t b0, uint32_t b1) {
    asm volatile("mma.sync.aligned.m16n8k16.row.col.f32.bf16.bf16.f32 {%0,%1,%2,%3},{%4,%5,%6,%7},{%8,%9},{%0,%1,%2,%3};"
                 : "+f"(d[0]), "+f"(d[1]), "+f"(d[2]), "+f"(d[3]) : "r"(a[0]), "r"(a[1]), "r"(a[2]), "r"(a[3]), "r"(b0), "r"(b1));
}
__device__ __forceinline__ void mma16z(float* d, const uint32_t* a, uint32_t b0, uint32_t b1) {
    asm volatile("mma.sync.aligned.m16n8k16.row.col.f32.bf16.bf16.f32 {%0,%1,%2,%3},{%4,%5,%6,%7},{%8,%9},{%10,%10,%10,%10};"
                 : "=f"(d[0]), "=f"(d[1]), "=f"(d[2]), "=f"(d[3]) : "r"(a[0]), "r"(a[1]), "r"(a[2]), "r"(a[3]), "r"(b0), "r"(b1), "f"(0.f));
}
__device__ __forceinline__ void mma8(float* d, uint32_t a0, uint32_t a1, uint32_t b0) {
    asm volatile("mma.sync.aligned.m16n8k8.row.col.f32.bf16.bf16.f32 {%0,%1,%2,%3},{%4,%5},{%6},{%0,%1,%2,%3};"
                 : "+f"(d[0]), "+f"(d[1]), "+f"(d[2]), "+f"(d[3]) : "r"(a0), "r"(a1), "r"(b0));
}
template <int ACC>
__device__ __forceinline__ void mma_sp(float* d, const uint32_t* a, const uint32_t* b) {
    if (ACC)
        asm volatile("mma.sp::ordered_metadata.sync.aligned.m16n8k32.row.col.f32.bf16.bf16.f32 {%0,%1,%2,%3},{%4,%5,%6,%7},{%8,%9,%10,%11},{%0,%1,%2,%3},%12,0x0;"
                     : "+f"(d[0]), "+f"(d[1]), "+f"(d[2]), "+f"(d[3])
                     : "r"(a[0]), "r"(a[1]), "r"(a[2]), "r"(a[3]), "r"(b[0]), "r"(b[1]), "r"(b[2]), "r"(b[3]), "r"(0xEEEE4444u));
    else
        asm volatile("mma.sp::ordered_metadata.sync.aligned.m16n8k32.row.col.f32.bf16.bf16.f32 {%0,%1,%2,%3},{%4,%5,%6,%7},{%8,%9,%10,%11},{%13,%13,%13,%13},%12,0x0;"
                     : "=f"(d[0]), "=f"(d[1]), "=f"(d[2]), "=f"(d[3])
                     : "r"(a[0]), "r"(a[1]), "r"(a[2]), "r"(a[3]), "r"(b[0]), "r"(b[1]), "r"(b[2]), "r"(b[3]), "r"(0xEEEE4444u), "f"(0.f));
}
__device__ __forceinline__ void mbar_arrive_if0(uint32_t b, uint32_t z) { asm volatile("{.reg .pred p; setp.eq.u32 p, %1, 0; @p mbarrier.arrive.shared::cta.b64 _, [%0];}" ::"r"(b), "r"(z) : "memory"); }
__device__ __forceinline__ void mbar_expect_if0(uint32_t b, uint32_t tx, uint32_t z) { asm volatile("{.reg .pred p; setp.eq.u32 p, %2, 0; @p mbarrier.arrive.expect_tx.shared::cta.b64 _, [%0], %1;}" ::"r"(b), "r"(tx), "r"(z) : "memory"); }
__device__ __forceinline__ float lds32f(uint32_t a) { float v; asm volatile("ld.shared.f32 %0,[%1];" : "=f"(v) : "r"(a) : "memory"); return v; }
__device__ __forceinline__ void wg_fence() { asm volatile("wgmma.fence.sync.aligned;" ::: "memory"); }
__device__ __forceinline__ void wg_commit() { asm volatile("wgmma.commit_group.sync.aligned;" ::: "memory"); }
template <int N> __device__ __forceinline__ void wg_wait() { asm volatile("wgmma.wait_group.sync.aligned %0;" ::"n"(N) : "memory"); }
__device__ __forceinline__ void delay(unsigned n) { if (n) { const unsigned t0 = clk(); while (clk() - t0 < n) {} } }
template <int ACC, uint32_t DHI = 0x40000040u, int TB = 0>
__device__ __forceinline__ void wg_rs_n32(float* d, const uint32_t* a, uint32_t dlo) {
    if (ACC)
        asm volatile("{.reg .b64 db; mov.b64 db, {%20, %21};\n"
                     "wgmma.mma_async.sync.aligned.m64n32k16.f32.bf16.bf16 {%0,%1,%2,%3,%4,%5,%6,%7,%8,%9,%10,%11,%12,%13,%14,%15},{%16,%17,%18,%19},db,1,1,1,%22;}"
                     : "+f"(d[0]), "+f"(d[1]), "+f"(d[2]), "+f"(d[3]), "+f"(d[4]), "+f"(d[5]), "+f"(d[6]), "+f"(d[7]),
                       "+f"(d[8]), "+f"(d[9]), "+f"(d[10]), "+f"(d[11]), "+f"(d[12]), "+f"(d[13]), "+f"(d[14]), "+f"(d[15])
                     : "r"(a[0]), "r"(a[1]), "r"(a[2]), "r"(a[3]), "r"(dlo), "r"(DHI), "n"(TB));
    else
        asm volatile("{.reg .b64 db; mov.b64 db, {%20, %21};\n"
                     "wgmma.mma_async.sync.aligned.m64n32k16.f32.bf16.bf16 {%0,%1,%2,%3,%4,%5,%6,%7,%8,%9,%10,%11,%12,%13,%14,%15},{%16,%17,%18,%19},db,0,1,1,%22;}"
                     : "=f"(d[0]), "=f"(d[1]), "=f"(d[2]), "=f"(d[3]), "=f"(d[4]), "=f"(d[5]), "=f"(d[6]), "=f"(d[7]),
                       "=f"(d[8]), "=f"(d[9]), "=f"(d[10]), "=f"(d[11]), "=f"(d[12]), "=f"(d[13]), "=f"(d[14]), "=f"(d[15])
                     : "r"(a[0]), "r"(a[1]), "r"(a[2]), "r"(a[3]), "r"(dlo), "r"(DHI), "n"(TB));
}
__device__ __forceinline__ uint32_t desc_lo(uint32_t addr) { return ((addr & 0x3FFFF) >> 4) | (1u << 16); }
__device__ __forceinline__ void tma2d(uint32_t dst, const CUtensorMap* m, int c0, int c1, uint32_t bar) {
    asm volatile("cp.async.bulk.tensor.2d.shared::cluster.global.mbarrier::complete_tx::bytes [%0], [%1, {%2,%3}], [%4];"
                 ::"r"(dst), "l"(m), "r"(c0), "r"(c1), "r"(bar) : "memory");
}
__device__ __forceinline__ void tma3d(uint32_t dst, const CUtensorMap* m, int c0, int c1, int c2, uint32_t bar) {
    asm volatile("cp.async.bulk.tensor.3d.shared::cluster.global.mbarrier::complete_tx::bytes [%0], [%1, {%2,%3,%4}], [%5];"
                 ::"r"(dst), "l"(m), "r"(c0), "r"(c1), "r"(c2), "r"(bar) : "memory");
}
__device__ __forceinline__ void tma3d_mc(uint32_t dst, const CUtensorMap* m, int c0, int c1, int c2, uint32_t bar, uint16_t mask) {
    asm volatile("cp.async.bulk.tensor.3d.shared::cluster.global.mbarrier::complete_tx::bytes.multicast::cluster [%0], [%1, {%2,%3,%4}], [%5], %6;"
                 ::"r"(dst), "l"(m), "r"(c0), "r"(c1), "r"(c2), "r"(bar), "h"(mask) : "memory");
}
__device__ __forceinline__ void bulk_g2s_mc(uint32_t dst, const void* src, uint32_t bytes, uint32_t bar, uint16_t mask) {
    asm volatile("cp.async.bulk.shared::cluster.global.mbarrier::complete_tx::bytes.multicast::cluster [%0], [%1], %2, [%3], %4;"
                 ::"r"(dst), "l"(src), "r"(bytes), "r"(bar), "h"(mask) : "memory");
}
__device__ __forceinline__ void tma2d_prefetch(const CUtensorMap* m, int c0, int c1) {
    asm volatile("cp.async.bulk.prefetch.tensor.2d.L2.global [%0, {%1,%2}];" ::"l"(m), "r"(c0), "r"(c1) : "memory");
}
__device__ __forceinline__ void bulk_s2c(uint32_t dst, uint32_t src, uint32_t bytes, uint32_t bar) {
    asm volatile("cp.async.bulk.shared::cluster.shared::cta.mbarrier::complete_tx::bytes [%0], [%1], %2, [%3];" ::"r"(dst), "r"(src), "r"(bytes), "r"(bar) : "memory");
}
__device__ __forceinline__ void bulk_s2g(void* dst, uint32_t src, uint32_t bytes) {
    asm volatile("cp.async.bulk.global.shared::cta.bulk_group [%0], [%1], %2;" ::"l"(dst), "r"(src), "r"(bytes) : "memory");
}
__device__ __forceinline__ void bulk_commit() { asm volatile("cp.async.bulk.commit_group;" ::: "memory"); }
__device__ __forceinline__ void bulk_wait0() { asm volatile("cp.async.bulk.wait_group 0;" ::: "memory"); }
__device__ __forceinline__ uint4 ld_poll(const void* p) {
    uint4 v;
    asm volatile("ld.relaxed.gpu.global.v4.u32 {%0,%1,%2,%3},[%4];" : "=r"(v.x), "=r"(v.y), "=r"(v.z), "=r"(v.w) : "l"(p) : "memory");
    return v;
}
template <int IMM>
__device__ __forceinline__ void ld_poll_at(uint4& v, const void* p) {
    asm volatile("ld.relaxed.gpu.global.v4.u32 {%0,%1,%2,%3},[%4+%5];" : "=r"(v.x), "=r"(v.y), "=r"(v.z), "=r"(v.w) : "l"(p), "n"(IMM) : "memory");
}
__device__ __forceinline__ void look(uint4 (&v)[6], const void* p) {
    ld_poll_at<0>(v[0], p); ld_poll_at<16384>(v[1], p); ld_poll_at<64>(v[2], p);
    ld_poll_at<16384 + 64>(v[3], p); ld_poll_at<128>(v[4], p); ld_poll_at<16384 + 128>(v[5], p);
}
__device__ __forceinline__ unsigned ld_acquire(const unsigned* p) { unsigned v; asm volatile("ld.acquire.gpu.global.u32 %0,[%1];" : "=r"(v) : "l"(p) : "memory"); return v; }
__device__ __forceinline__ void red_release(unsigned* p, unsigned v) { asm volatile("red.release.gpu.global.add.u32 [%0], %1;" ::"l"(p), "r"(v) : "memory"); }

template <int ID, int N> __device__ __forceinline__ void bar_sync() { asm volatile("bar.sync %0, %1;" ::"n"(ID), "n"(N) : "memory"); }
template <int ID, int N> __device__ __forceinline__ void bar_arrive() { asm volatile("bar.arrive %0, %1;" ::"n"(ID), "n"(N) : "memory"); }
__device__ __forceinline__ void cluster_arrive() { asm volatile("barrier.cluster.arrive.relaxed.aligned;" ::: "memory"); }
__device__ __forceinline__ void cluster_wait() { asm volatile("barrier.cluster.wait.aligned;" ::: "memory"); }

constexpr uint32_t XB_BYTES = 36864;
constexpr uint32_t S_XB = 0;
constexpr uint32_t S_QM = 73728;
constexpr uint32_t S_KM = 74752;
constexpr uint32_t S_OM = 75776;
constexpr uint32_t S_SP = 77824;
constexpr uint32_t S_SUM = 80384;
constexpr uint32_t S_TGT = 81408;
constexpr uint32_t S_VM = 147456;
constexpr uint32_t S_QX = 86016;
constexpr uint32_t S_PX = S_QX;
constexpr uint32_t S_KX = 94208;
constexpr uint32_t S_VX = 102400;
constexpr uint32_t S_SX = 135168;
constexpr uint32_t S_OX = 155648;
constexpr uint32_t S_MEM = 172032;
constexpr uint32_t S_WO = 181248;
constexpr uint32_t S_BAR = 230400;
constexpr uint32_t S_ZERO = S_BAR + 128;
constexpr uint32_t A_SMEM = S_ZERO + 1024;
__host__ __device__ constexpr uint32_t s_w(int c) { return c == 0 ? S_WO : 73728 + (c - 1) * 49152; }
constexpr uint32_t B_W = S_BAR, B_WO = S_BAR + 24, B_X = S_BAR + 32, B_S = S_BAR + 48, B_VX = S_BAR + 56, B_SX = S_BAR + 72, B_M = S_BAR + 88, B_T = S_BAR + 112;
constexpr int NB_QK = 1, NB_O = 2, NB_RED = 3, NB_P = 4, NB_AUX = 5, NB_PRO = 6, NB_X = 7, NB_GO = 8, NB_L = 9, NB_PV = 10, NB_P2 = 11;

constexpr float SM_SCALE = 0.08838834764831845f * 1.4426950408889634f;
constexpr uint32_t ONES = 0x3F803F80u;
constexpr uint32_t FULL_COUNT = 0x4200u;
#define XLIM NSEG
#define TGT_NS 1088
#define LOOK_NS 100
#define RCP_AT 2
#define NCH 2
#define XTMA_NS 50
#define REG_MAIN0 232
#define REG_MAIN1 232
#define REG_AUX 40

#define HAND_AT 26
#define VX_AT 0
#define PV_MODE 2
#define W_PROMO CU_TENSOR_MAP_L2_PROMOTION_L2_128B
#define DESCPF 1
#define WO_AFTER 2
#define FIRST_NS 450
#define PACE 1
#define DEP_LATE 1
#define HSPLIT 2
#define FIN_NS 40
#define WO_LOOP 1
#define FLAG_NS 40
static_assert(REG_MAIN0 + REG_MAIN1 + REG_AUX <= 504, "the three warpgroups share 3 x 168 registers");
#define HSTAMP(i) do {} while (0)
#define HSTAMP2(i) do {} while (0)
#define HSTAMP3(i) do {} while (0)
#define HSTAMP4(i) do {} while (0)
#define TSTAMP(i, e) do {} while (0)

__device__ __forceinline__ void load_scores(uint32_t a, __half2 (&hs)[5]) {
    uint32_t r[10];
    ldsm4(r, a);
    ldsm4(r + 4, a + 512);
    ldsm2(r + 8, a + 1024);
    const __half2 hf = as_h2(0x38003800u);
#pragma unroll
    for (int T = 0; T < 5; T++) hs[T] = __hfma2(as_h2(r[2 * T]), hf, __hmul2(as_h2(r[2 * T + 1]), hf));
}
__device__ __forceinline__ void softmax_exp(const __half2 (&hs)[5], float (&ev)[10]) {
    __half2 m = __hmax2(__hmax2(__hmax2(hs[0], hs[1]), __hmax2(hs[2], hs[3])), hs[4]);
    const uint32_t mu = as_u32(m);
    const uint32_t m1 = __shfl_xor_sync(0xffffffffu, mu, 1), m2 = __shfl_xor_sync(0xffffffffu, mu, 2), m3 = __shfl_xor_sync(0xffffffffu, mu, 3);
    m = __hmax2(__hmax2(m, as_h2(m1)), __hmax2(as_h2(m2), as_h2(m3)));
    const float mc = -fmaxf(__low2float(m), __high2float(m)) * (2.f * SM_SCALE);
#pragma unroll
    for (int T = 0; T < 5; T++) {
        ev[2 * T] = ex2(fmaf(__low2float(hs[T]), 2.f * SM_SCALE, mc));
        ev[2 * T + 1] = ex2(fmaf(__high2float(hs[T]), 2.f * SM_SCALE, mc));
    }
}

__device__ __forceinline__ void x_scores(uint32_t sb, int seg, int wq, uint32_t L16, float (&ev)[10]) {
    __half2 hs[5];
    load_scores(sb + S_SX + (seg & 1) * 5120 + wq * 1280 + L16, hs);
    const int dg = (int)(L16 >> 6) - (int)((L16 >> 3) & 6) + 8 * wq;
#pragma unroll
    for (int T = 0; T < 4; T++) {
        uint32_t u = as_u32(hs[T]);
        if (dg < 8 * T + 1) u = (u & 0xFFFFu) | 0xFC000000u;
        if (dg < 8 * T) u = 0xFC00FC00u;
        hs[T] = as_h2(u);
    }
    softmax_exp(hs, ev);
}
__device__ __forceinline__ void x_probs(uint32_t sb, int seg, int wq, uint32_t L16, const float (&ev)[10]) {
    float l = ((ev[0] + ev[1]) + (ev[2] + ev[3])) + ((ev[4] + ev[5]) + (ev[6] + ev[7])) + (ev[8] + ev[9]);
    const float l1 = __shfl_xor_sync(0xffffffffu, l, 1), l2 = __shfl_xor_sync(0xffffffffu, l, 2), l3 = __shfl_xor_sync(0xffffffffu, l, 3);
    const float r = rcp((l + l1) + (l2 + l3));
    const uint32_t a = sb + S_PX + (seg & 1) * 4096 + wq * 640 + (L16 >> 2);
#pragma unroll
    for (int i = 0; i < 5; i++) sts32(a + i * 128, pack_bf16(ev[2 * i] * r, ev[2 * i + 1] * r));
}
__device__ __forceinline__ void x_pv_load(uint32_t sb, int seg, int w, uint32_t L16, uint32_t (&a)[3][4]) {
    lds128(a[0], sb + S_VX + (seg & 3) * 8192 + w * 1024 + L16);
    lds128(a[1], sb + S_VX + (seg & 3) * 8192 + w * 1024 + 512 + L16);
    lds64(a[2], sb + S_VM + (seg & 3) * 2048 + w * 256 + (L16 >> 1));
    a[2][2] = 0; a[2][3] = 0;
}
__device__ __forceinline__ void x_pv_run(uint32_t sb, int seg, const uint32_t (&a)[3][4], uint32_t (&pk)[8]) {
    const uint32_t d = ((sb + S_PX + (seg & 1) * 4096) & 0x3FFFF) >> 4;
    float o[16];
    wg_fence();
    wg_rs_n32<0, 40>(o, a[0], d | (8u << 16));
    wg_rs_n32<1, 40>(o, a[1], (d + 16) | (8u << 16));
    wg_rs_n32<1, 40>(o, a[2], d + 32);
    wg_commit();
    wg_wait<0>();
#pragma unroll
    for (int i = 0; i < 8; i++) pk[i] = pack_bf16(o[2 * i], o[2 * i + 1]);
}
__device__ __forceinline__ void x_pv_store(uint32_t sb, int seg, int w, uint32_t L16, const uint32_t (&pk)[8]) {
    const uint32_t a = sb + S_OX + (seg & 1) * 8192 + w * 1024 + L16;
    stsm4(a, pk[0], pk[1], pk[2], pk[3]);
    stsm4(a + 512, pk[4], pk[5], pk[6], pk[7]);
}
__device__ __forceinline__ void ox_store(uint32_t sb, int seg, uint32_t h) {
    fence_async_smem();
    bulk_s2g(g_ox + (seg * NH + h) * 512, sb + S_OX + (seg & 1) * 8192, 8192);
    bulk_commit();
}
__device__ __forceinline__ void ox_publish(int seg, uint32_t h) {
    bulk_wait0();
    asm volatile("fence.proxy.async.global;" ::: "memory");
    asm volatile("red.relaxed.gpu.global.add.u32 [%0], 1;" ::"l"(&g_flag[(h >> 3) * NSEG + seg]) : "memory");
}
__device__ __forceinline__ void vx_store(uint32_t sb, int seg, uint32_t h) {
    fence_async_smem();
    bulk_s2g(g_vx + (h * 2 + (seg & 1)) * 512, sb + S_VX + (seg & 3) * 8192, 8192);
    bulk_commit();
}
__device__ __forceinline__ void vx_fetch(uint32_t sb, int seg, uint32_t h) {
    bulk_wait0();
    bulk_g2s_mc(sb + S_VX + (seg & 3) * 8192, g_vx + (h * 2 + (seg & 1)) * 512, 8192, sb + B_VX + (seg & 1) * 8, 3);
}

__device__ __forceinline__ void x_pack(const float (&d)[16], uint32_t (&pk)[8]) {
#pragma unroll
    for (int i = 0; i < 8; i++) pk[i] = pack_bf16(d[2 * i], d[2 * i + 1]);
}
__device__ __forceinline__ void x_write(uint32_t sb, const uint32_t (&pk)[8], int seg, bool isv, int w, uint32_t L16) {
    if (!isv) {
        const uint32_t a = sb + S_QX + (w >> 2) * 8192 + (seg & 1) * 4096 + (w & 3) * 256 + (L16 & 0xF0) + (L16 & 0x100) * 4;
        stsm4t(a, pk[0], pk[1], pk[2], pk[3]);
        stsm4t(a + 2048, pk[4], pk[5], pk[6], pk[7]);
    } else {
        const uint32_t a = sb + S_VX + (seg & 3) * 8192 + w * 1024 + L16;
        sts128(a, pk[0], pk[1], pk[2], pk[3]);
        sts128(a + 512, pk[4], pk[5], pk[6], pk[7]);
    }
}

template <int K0, int K1>
__device__ __forceinline__ void x_project(float (&d)[16], const uint32_t (&wA)[36][4], uint32_t desc) {
#pragma unroll
    for (int i = K0; i < K1; i++) {
        const uint32_t db = desc + (((i >> 2) * 4096 + (i & 3) * 32) >> 4);
        if (i == 0) wg_rs_n32<0>(d, wA[i], db); else wg_rs_n32<1>(d, wA[i], db);
    }
}

__device__ __forceinline__ void mem_scores(uint32_t sb, uint32_t peerA, uint32_t peerB, uint32_t off, const uint32_t (&q0)[4], const uint32_t (&q1)[4],
                                           const uint32_t (&k0)[4], const uint32_t (&k1)[4]) {
    float e0[4], o0[4], e1[4], o1[4];
    mma16z(e0, q0, k0[0], k0[1]);
    mma16z(o0, q0, k0[2], k0[3]);
    mma16z(e1, q1, k1[0], k1[1]);
    mma16z(o1, q1, k1[2], k1[3]);
    const uint32_t sc = pack_f16_sat((e0[0] + o0[2]) + (e1[0] + o1[2]), (e0[1] + o0[3]) + (e1[1] + o1[3]));
    st_async32(peerB + off, sc, peerB + B_S);
    st_async32(peerA + off, sc, peerA + B_S);
    sts32(sb + off, sc);
    __syncwarp();
}

__device__ __forceinline__ unsigned post_time(int s, uint32_t L16) {
    delay(1);
    const unsigned t = gtime() | 1;
    if (L16 == 0) asm volatile("st.relaxed.gpu.global.u32 [%0], %1;" ::"l"(g_time + s * 96 + blockIdx.x), "r"(t) : "memory");
    return t;
}
__device__ __forceinline__ void plan_look(uint32_t sb, int s, uint32_t L16, unsigned t) {
    const char* p = reinterpret_cast<const char*>(g_time) + s * 384 + (L16 < 384 ? L16 : 0);
    uint4 v;
    unsigned c = 0;
    do { v = ld_poll(p); } while (__any_sync(0xffffffffu, (v.x & v.y & v.z & v.w & 1) == 0) && ++c < SPIN_LIM);
    const int d = max(max((int)(v.x - t), (int)(v.y - t)), max((int)(v.z - t), (int)(v.w - t))) + (s == 0 ? FIRST_NS : 0);
    const unsigned tgt = t + min(__reduce_max_sync(0xffffffffu, d), 20000) + TGT_NS;
    if (L16 < 48) { const uint32_t r = mapa(sb, L16 >> 4); st_async32(r + S_TGT, tgt, r + B_T); }
}

__device__ __forceinline__ void load_wo(uint32_t sb, int w, uint32_t L16, uint32_t (&woA)[8][4], uint32_t (&woB)[4][4]) {
    mbar_wait(sb + B_WO, 0);
    if (w < 4) TSTAMP(73, 0);
    const int m = L16 >> 7, r = (L16 >> 4) & 7;
    const int ca = 3 * w + (m & 1), cb = 3 * w + 2;
    const uint32_t aA = sb + S_WO + (ca >> 3) * 16384 + ((m >> 1) * 8 + r) * 128 + (((ca & 7) ^ r) << 4);
    const int eB = ((m & 2) + ((r >> 1) & 1)) * 8 + 4 * (m & 1) + 2 * (r >> 2) + (r & 1);
    const uint32_t aB = sb + S_WO + (cb >> 3) * 16384 + eB * 128 + (((cb & 7) ^ (eB & 7)) << 4);
#pragma unroll
    for (int i = 0; i < 8; i++) ldsm4t(woA[i], aA + i * 2048);
#pragma unroll
    for (int i = 0; i < 4; i++) ldsm4t(woB[i], aB + i * 4096);
}

template <int ROLE>
__device__ __forceinline__ void chain_main(const uint32_t sb, const uint32_t lane16, const int wq, const uint32_t j, const uint32_t h,
                                           const uint32_t peerA, const uint32_t peerB, char* const acc) {
    uint32_t L16 = lane16;
    constexpr bool isv = ROLE >= 2;
    constexpr int wg = ROLE & 1;
    const int w = wg * 4 + wq;
    const uint32_t xdesc = desc_lo(sb + S_XB);
    const uint32_t zero = h >> 20;
    uint32_t wA[36][4], woA[8][4], woB[4][4];
    float xd[16];
    {
        const int m = L16 >> 7, r = (L16 >> 4) & 7;
        const int blk = (ROLE == 1) ? ((wq & 2) * 2 + (wq & 1) + (m & 1) * 2) : (2 * wq + (m & 1));
        const uint32_t a = sb + wg * 24576 + ((m >> 1) * 8 + r) * 128 + ((blk ^ r) << 4);
        float x0[16];
#pragma unroll
        for (int c = 0; c < 3; c++) {
            mbar_wait(sb + B_W + 8 * c, 0);
            if (wg == 0) TSTAMP(70 + c, 0);
#pragma unroll
            for (int i = 0; i < 12; i++) ldsm4t(wA[12 * c + i], a + s_w(c) + i * 2048);
            if (c == WO_AFTER) bar_arrive<NB_PRO, 288>();
            if (c == 0) { mbar_wait(sb + B_X, 0); mbar_wait(sb + B_X + 8, 0); }
            if (c == 2) { bar_sync<NB_O, 256>(); cluster_arrive(); }
            wg_fence();
            if (c == 0) { x_project<0, 12>(x0, wA, xdesc); x_project<0, 12>(xd, wA, xdesc + (XB_BYTES >> 4)); wg_commit(); wg_wait<0>(); }
            if (c == 1) { x_project<12, 24>(x0, wA, xdesc); x_project<12, 24>(xd, wA, xdesc + (XB_BYTES >> 4)); wg_commit(); wg_wait<0>(); }
            if (c == 2) { x_project<24, 36>(x0, wA, xdesc); wg_commit(); wg_wait<0>(); }
        }
        uint32_t pk[8];
        x_pack(x0, pk);
        x_write(sb, pk, 0, isv, w, L16);
        bar_arrive<NB_AUX, 288>();
        wg_fence();
        x_project<24, 36>(xd, wA, xdesc + (XB_BYTES >> 4));
        wg_commit();
        cluster_wait();
        bar_sync<NB_O, 256>();
        if (wg == 0) TSTAMP(74, 0);
        if (WO_LOOP) {
#pragma unroll
            for (int i = 0; i < 8; i++) woA[i][0] = woA[i][1] = woA[i][2] = woA[i][3] = 0;
#pragma unroll
            for (int i = 0; i < 4; i++) woB[i][0] = woB[i][1] = woB[i][2] = woB[i][3] = 0;
        } else load_wo(sb, w, L16, woA, woB);
    }
    int s = 0;
#pragma unroll 1
    while (true) {
        const uint32_t par = s & 1;
        const uint32_t kx = sb + S_KX + par * 4096;
        asm volatile("" : "+r"(L16));
        uint32_t pk[8];
        if (wg == 0) { wg_wait<0>(); x_pack(xd, pk); x_write(sb, pk, s + 1, isv, w, L16); }
        float c0[4], c1[4];
        uint32_t k0[4], k1[4];
        {
            const uint32_t a = sb + S_MEM + L16;
            constexpr int CH = 18 / NCH;
            uint32_t b[3][4];
            bool ready = true;
            mbar_wait(sb + B_M, par);
            ldsm4(b[0], a);
            ldsm4(b[1], a + 512);
            if (wg == 1) { wg_wait<0>(); x_pack(xd, pk); }
            bar_arrive<NB_GO, 288>();
#pragma unroll
            for (int i = 0; i < 18; i++) {
                if ((i + 4) % CH == 0 && i + 4 < 18) ready = mbar_test(sb + B_M + ((i + 4) / CH) * 8, par);
                if ((i + 2) % CH == 0 && i + 2 < 18) { if (__builtin_expect(!ready, 0)) mbar_wait(sb + B_M + ((i + 2) / CH) * 8, par); }
                if (i + 2 < 18) ldsm4(b[(i + 2) % 3], a + (i + 2) * 512);
                if (ROLE == 0 && i == 16) ldsm4(k0, kx + wq * 1024 + L16);
                if (ROLE == 0 && i == 17) ldsm4(k1, kx + wq * 1024 + 512 + L16);
                if (i == 0) { mma16z(c0, wA[0], b[0][0], b[0][1]); mma16z(c1, wA[1], b[0][2], b[0][3]); }
                else { mma16(c0, wA[2 * i], b[i % 3][0], b[i % 3][1]); mma16(c1, wA[2 * i + 1], b[i % 3][2], b[i % 3][3]); }
            }
        }
        const uint32_t p0 = pack_bf16(c0[0] + c1[0], c0[1] + c1[1]), p1 = pack_bf16(c0[2] + c1[2], c0[3] + c1[3]);
        if (!isv) {
            stsm2t(sb + S_QM + w * 256 + L16, p0, p1);
            bar_sync<NB_QK, 384>();
            if (ROLE == 0) {
                uint32_t q0[4], q1[4];
                ldsm4(q0, sb + S_QM + L16);
                ldsm4(q1, sb + S_QM + 512 + L16);
                mem_scores(sb, peerA, peerB, S_SP + j * 128 + wq * 256 + (L16 >> 2), q0, q1, k0, k1);
                mbar_arrive_if0(sb + B_S, L16);
            } else {
                if (s + 2 < XLIM) mbar_wait(sb + B_X + par * 8, ((s + 2) >> 1) & 1);
                x_write(sb, pk, s + 1, isv, w, L16);
                if (wq != 0) {
                    const int rt = (wq == 3) ? 0 : 1;
                    const uint32_t qa = sb + S_QX + par * 4096 + rt * 2048 + (L16 & 0x80) * 8 + (L16 & 0x170);
                    const uint32_t kb0 = (wq == 2 ? kx + 2048 : sb + S_KM) + L16;
                    const uint32_t kb1 = (wq == 2 ? kx + 3072 : kx) + L16;
                    const uint32_t kb2 = kx + 1024 + L16;
                    float a0[4], a1[4], a2[4];
#pragma unroll
                    for (int hf = 0; hf < 2; hf++) {
                        uint32_t qa0[4], qa1[4], b[4];
                        ldsm4(qa0, qa + hf * 512);
                        ldsm4(qa1, qa + hf * 512 + 128);
                        ldsm4(b, kb0 + hf * 512);
                        if (hf == 0) mma16z(a0, qa0, b[0], b[1]); else mma16(a0, qa0, b[0], b[1]);
                        mma16(a0, qa1, b[2], b[3]);
                        ldsm4(b, kb1 + hf * 512);
                        if (hf == 0) mma16z(a1, qa0, b[0], b[1]); else mma16(a1, qa0, b[0], b[1]);
                        mma16(a1, qa1, b[2], b[3]);
                        ldsm4(b, kb2 + hf * 512);
                        if (hf == 0) mma16z(a2, qa0, b[0], b[1]); else mma16(a2, qa0, b[0], b[1]);
                        mma16(a2, qa1, b[2], b[3]);
                    }
                    mbar_wait(sb + B_S, par);
                    const uint32_t dst = peerB + S_SX + par * 5120 + j * 128 + rt * 2560 + (L16 >> 2);
                    const uint32_t bar = peerB + B_SX + par * 8;
                    const uint32_t T0 = (wq == 2 ? 2 : 4) * 256, T1 = (wq == 2 ? 3 : 0) * 256;
                    st_async32(dst + T0, pack_f16_sat(a0[0], a0[1]), bar);
                    st_async32(dst + 1280 + T0, pack_f16_sat(a0[2], a0[3]), bar);
                    if (wq != 2) st_async32(dst + T1, pack_f16_sat(a1[0], a1[1]), bar);
                    st_async32(dst + 1280 + T1, pack_f16_sat(a1[2], a1[3]), bar);
                    if (wq == 1) st_async32(dst + 256, pack_f16_sat(a2[0], a2[1]), bar);
                    if (wq != 2) st_async32(dst + 1280 + 256, pack_f16_sat(a2[2], a2[3]), bar);
                }
            }
        } else {
            const uint32_t off = S_VM + (s & 3) * 2048 + w * 256 + (L16 >> 1);
            st_async64(peerA + off, p0, p1, peerA + B_S);
            st_async64(peerB + off, p0, p1, peerB + B_S);
            sts64(sb + off, p0, p1);
            __syncwarp();
            mbar_expect_if0(sb + B_S, 160, L16);
            if (ROLE == 3) x_write(sb, pk, s + 1, isv, w, L16);
            if (PV_MODE >= 2 && ROLE == 2) { bar_arrive<NB_P, 384>(); bar_arrive<NB_PV, 288>(); }
            else {
                uint32_t pva[3][4];
                x_pv_load(sb, s + 2, w, L16, pva);
                bar_sync<NB_P, 384>();
                x_pv_run(sb, s, pva, pk);
                if (PV_MODE == 2) x_pv_load(sb, s + 2, wq, L16, pva);
                x_pv_store(sb, s, w, L16, pk);
                if (PV_MODE == 2) { x_pv_run(sb, s, pva, pk); x_pv_store(sb, s, wq, L16, pk); }
                bar_arrive<NB_PV, 288>();
            }
            if (ROLE == 3 && s + 2 < XLIM) mbar_wait(sb + B_X + par * 8, ((s + 2) >> 1) & 1);
        }
        if (WO_LOOP == 0 && s == NSEG - 1) break;
        if (WO_LOOP && ((s + 1) & (NSEG - 1)) <= 1) {
            if (s) break;
            load_wo(sb, w, L16, woA, woB);
        }
        if (wg == 0) {
            if (!isv) mbar_wait(sb + B_VX + par * 8, (s >> 1) & 1);
            uint32_t va[4][4];
            const uint32_t vx = sb + S_VX + (s & 3) * 8192 + wq * 2048 + L16;
            const uint32_t vm = sb + S_VM + (s & 3) * 2048 + wq * 512 + (L16 >> 1);
            lds128(va[0], vx);
            lds128(va[2], vx + 1024);
            mbar_wait(sb + B_S, par);
            __half2 hs[5];
            load_scores(sb + S_SP + L16, hs);
            float ev[10];
            softmax_exp(hs, ev);
            lds128(va[1], vx + 512);
            lds128(va[3], vx + 1536);
            uint32_t p[5];
#pragma unroll
            for (int i = 0; i < 5; i++) p[i] = pack_bf16(ev[2 * i], ev[2 * i + 1]);
            uint32_t vm0[2], vm1[2];
            const uint32_t ones[4] = {ONES, ONES, ONES, ONES};
            float sum[4], o0[4], o1[4];
            mma16z(o0, va[0], p[0], p[1]);
            mma16z(o1, va[2], p[0], p[1]);
            mma16z(sum, ones, p[0], p[1]);
            lds64(vm0, vm);
            lds64(vm1, vm + 256);
            mma16(o0, va[1], p[2], p[3]);
            mma16(o1, va[3], p[2], p[3]);
            mma16(sum, ones, p[2], p[3]);
            mma8(o0, vm0[0], vm0[1], p[4]);
            mma8(o1, vm1[0], vm1[1], p[4]);
            mma8(sum, ONES, ONES, p[4]);
            stsm4t(sb + S_OM + wq * 512 + L16, pack_bf16(o0[0], o0[1]), pack_bf16(o0[2], o0[3]), pack_bf16(o1[0], o1[1]), pack_bf16(o1[2], o1[3]));
            sts64(sb + S_SUM + wq * 256 + (L16 >> 1), __float_as_uint(sum[0]), __float_as_uint(sum[1]));
        }
        bar_sync<NB_O, 256>();
        {
            float a0[4], a1[4], e[4];
            float2 sc;
            float sr, r0, r1, rr;
#pragma unroll
            for (int i = 0; i < 4; i++) {
                uint32_t b[4];
                ldsm4(b, sb + S_OM + i * 512 + L16);
                if (i == 0) {
                    mma16z(a0, woA[0], b[0], b[1]); mma16z(a1, woA[1], b[2], b[3]);
                    mma_sp<0>(e, b, woB[0]);
                } else {
                    if (i == 1) { sc = lds64f(sb + S_SUM + (L16 >> 1)); sr = lds32f(sb + S_SUM + ((L16 >> 4) & 0x1C)); }
                    const uint32_t z = __float_as_uint(a0[0]) & zero;
                    mma16(a0, woA[2 * i], b[0], b[1]); mma16(a1, woA[2 * i + 1], b[2], b[3]);
                    mma_sp<1>(e, b, woB[i]);
                    if (i == RCP_AT) {
                        r0 = rcp(__uint_as_float(__float_as_uint(sc.x) | z));
                        r1 = rcp(__uint_as_float(__float_as_uint(sc.y) | z));
                        rr = rcp(__uint_as_float(__float_as_uint(sr) | z));
                    }
                }
            }
            asm volatile("" : "+r"(L16));
            char* const rslot = acc + (slot_off(s + 1) + j * 64 + w * 4096) + lane_off(L16);
            asm volatile("red.relaxed.gpu.global.add.noftz.v4.bf16x2 [%0], {%1,%2,%3,%4};"
                         ::"l"(rslot), "r"(pack_bf16((a0[0] + a1[0]) * r0, (a0[1] + a1[1]) * r1)), "r"(pack_bf16((a0[2] + a1[2]) * r0, (a0[3] + a1[3]) * r1)),
                           "r"(pack_bf16((e[0] + e[2]) * rr, (e[1] + e[3]) * rr)), "r"(0x3F80u) : "memory");
        }
        bar_arrive<NB_RED, 384>();
        if (wg == 0) {
            if (PV_MODE == 3 && isv) bar_arrive<NB_P2, 384>();
            bar_sync<NB_X, 256>();
            wg_fence();
            x_project<0, HAND_AT>(xd, wA, xdesc + par * (XB_BYTES >> 4));
            bar_arrive<NB_L, 256>();
            x_project<HAND_AT, 36>(xd, wA, xdesc + par * (XB_BYTES >> 4));
        } else {
            bar_arrive<NB_X, 256>();
            if (PV_MODE == 3 && isv) {
                uint32_t pva[3][4];
                asm volatile("" : "+r"(L16));
                x_pv_load(sb, s + 3, wq, L16, pva);
                bar_sync<NB_P2, 384>();
                x_pv_run(sb, s + 1, pva, pk);
                x_pv_store(sb, s + 1, wq, L16, pk);
            }
            bar_sync<NB_L, 256>();
            wg_fence();
            x_project<0, 36>(xd, wA, xdesc + par * (XB_BYTES >> 4));
        }
        wg_commit();
        s++;
    }
    if (isv) {
#pragma unroll 1
        for (int seg = NSEG - 2; seg < NSEG; seg++) {
            uint32_t pva[3][4], pk[8];
            x_pv_load(sb, seg, w, L16, pva);
            bar_sync<NB_RED, 384>();
            x_pv_run(sb, seg, pva, pk);
            x_pv_store(sb, seg, w, L16, pk);
            bar_arrive<NB_QK, 384>();
        }
    }
}

template <bool isv>
__device__ __forceinline__ void chain_aux(const uint32_t sb, const uint32_t lane16, const int wq, const uint32_t j, const uint32_t h,
                                          const uint32_t peerA, const uint32_t peerB, const CUtensorMap* tmWo, const CUtensorMap* tmX,
                                          char* const acc, const CUtensorMap* m0, const CUtensorMap* m1) {
    const int t = wq * 32 + (lane16 >> 4);
    cluster_arrive();
    {
        for (int c2 = 0; c2 < 3; c2++) mbar_arrive_if0(sb + B_M + c2 * 8, lane16);
        if (wq == 0) {
            if (PACE) {
                mbar_wait(sb + B_W, 0);
                if (t == 0) {
                    mbar_expect(sb + B_W + 16, 49152);
                    tma2d(sb + s_w(2), m0, h * 128 + (isv ? 0 : 64 * j), 384, sb + B_W + 16);
                    tma2d(sb + s_w(2) + 24576, m1, h * 128 + (isv ? 64 : 64 * j), 384, sb + B_W + 16);
                }
                __syncwarp();
            }
            bar_sync<NB_PRO, 288>();
            if (t == 0) {
                fence_async_smem();
                mbar_expect(sb + B_WO, 49152);
                for (int b = 0; b < 3; b++) tma2d(sb + S_WO + b * 16384, tmWo, 192 * j + 64 * b, h * 128, sb + B_WO);
            }
        } else if (wq == 3) {
            bulk_wait0();
            asm volatile("fence.proxy.async.global;" ::: "memory");
            __syncwarp();
            if (lane16 == 0) {
                if (h == 0) asm volatile("red.relaxed.gpu.global.add.u32 [%0], 1;" ::"l"(&g_zero_cnt) : "memory");
            }
            __syncwarp();
            unsigned c = 0;
            while (ld_acquire(&g_zero_cnt) < 3 && ++c < SPIN_LIM) __nanosleep(100);
            TSTAMP(76, 0);
            if (DEP_LATE) mbar_wait(sb + B_W + 16, 0);
            asm volatile("griddepcontrol.launch_dependents;" ::: "memory");
        }
        __syncwarp();
        cluster_wait();
        if (wq == 0) bar_sync<NB_AUX, 288>();
        if (t == 0) {
            fence_async_smem();
            if (!isv) mbar_expect(sb + B_VX, 8192);
            else {
                bulk_s2c(peerA + S_VX, sb + S_VX, 8192, peerA + B_VX);
                bulk_s2c(peerB + S_VX, sb + S_VX, 8192, peerB + B_VX);
            }
            mbar_expect(sb + B_X, XB_BYTES);
            tma3d(sb + S_XB, tmX, 0, 64, 0, sb + B_X);
        }
        __syncwarp();
    }
    TSTAMP(0, 0);
    uint32_t L16 = lane16;
    const char* slot = acc + wq * 4096 + lane_off(L16);
    float ev[10];
    int s = 0;
#pragma unroll 1
    while (true) {
        const uint32_t par = s & 1;
        asm volatile("" : "+r"(L16));
        if (!isv) {
            if (wq == 0) {
                bar_sync<NB_QK, 384>();
                uint32_t q0[4], q1[4], k0[4], k1[4];
                ldsm4(q0, sb + S_QM + L16);
                ldsm4(k0, sb + S_KM + L16);
                ldsm4(q1, sb + S_QM + 512 + L16);
                ldsm4(k1, sb + S_KM + 512 + L16);
                mem_scores(sb, peerA, peerB, S_SP + j * 128 + 1024 + (L16 >> 2), q0, q1, k0, k1);
                mbar_expect_if0(sb + B_S, 640 + 2048, L16);
            } else if (wq == 3) {
                bar_sync<NB_GO, 288>();
                const unsigned t = post_time(s, L16);
                bar_sync<NB_QK, 384>();
                if (j == 0 && s < NSEG - 1) {
                    if (LOOK_NS) __nanosleep(LOOK_NS);
                    plan_look(sb, s, L16, t);
                }
            } else {
                bar_arrive<NB_QK, 384>();
                if (wq == 2) {
                    if (L16 == 0) {
                        if (s + 3 < XLIM) mbar_expect(sb + B_X + (par ^ 1) * 8, XB_BYTES);
                        mbar_expect(sb + B_VX + (par ^ 1) * 8, 8192);
                        mbar_expect(sb + B_T, 4);
                        if (s == 2 && h == 0 && j == 0) g_zero_cnt = 0;
                    }
                } else if (s + 3 < XLIM && j == 1) {
                    mbar_wait(sb + B_S, par);
                    if (XTMA_NS) __nanosleep(XTMA_NS);
                    if (L16 == 0) tma3d_mc(sb + S_XB + (par ^ 1) * XB_BYTES, tmX, 0, (s + 3) * SEG, 0, sb + B_X + (par ^ 1) * 8, 7);
                }
                __syncwarp();
            }
        } else {
            if (wq == 3) {
                bar_sync<NB_GO, 288>();
                post_time(s, L16);
            } else if (L16 == 0) {
                if (wq == 0) {
                    if (s >= 1) vx_fetch(sb, s, h);
                } else if (wq == 1) {
                    if (s >= 3) ox_publish(s - 3, h);
                } else {
                    mbar_expect(sb + B_SX + par * 8, 3584);
                    mbar_expect(sb + B_T, 4);
                    if (s + 3 < XLIM) mbar_expect(sb + B_X + (par ^ 1) * 8, XB_BYTES);
                }
            }
            __syncwarp();
            if (s >= 1) mbar_wait(sb + B_SX + (par ^ 1) * 8, ((s - 1) >> 1) & 1);
            if (PV_MODE != 3) fence_async_smem();
            bar_sync<NB_P, 384>();
            if (VX_AT == 0 && wq == 0) { if (L16 == 0 && s + 1 < NSEG) vx_store(sb, s + 1, h); __syncwarp(); }
            x_scores(sb, s + 1, wq, L16, ev);
            if (VX_AT == 1 && wq == 0) { if (L16 == 0 && s + 1 < NSEG) vx_store(sb, s + 1, h); __syncwarp(); }
            if (wq == 1) {
                bar_sync<NB_PV, 288>();
                if (L16 == 0 && s >= 2) ox_store(sb, s - 2, h);
                __syncwarp();
            }
            x_probs(sb, s + 1, wq, L16, ev);
            if (PV_MODE == 3 && s < NSEG - 1) { fence_async_smem(); bar_arrive<NB_P2, 384>(); }
        }
        if (s == NSEG - 1) break;
        mbar_wait(sb + B_T, par);
        const unsigned tgt = __float_as_uint(lds32f(sb + S_TGT));
        bar_sync<NB_RED, 384>();
        asm volatile("" : "+r"(L16));
        slot += par ? 32768 - 512 : 512;
        while ((int)(gtime() - tgt) < 0) {}
        uint4 v[6];
        look(v, slot);
        s++;
        const uint32_t ma = sb + S_MEM + wq * 384 + L16;
        unsigned c = 0;
        constexpr int CW = 6 / NCH;
        int done = NCH;
#pragma unroll
        for (int k = 0; k < NCH; k++) {
            uint32_t bad = 0;
#pragma unroll
            for (int i = CW * k; i < CW * k + CW; i++) { stsm2t(ma + i * 1536, v[i].x, v[i].y); stsm1(ma + i * 1536 + 256, v[i].z); bad |= v[i].w ^ FULL_COUNT; }
            const bool again = __any_sync(0xffffffffu, bad != 0);
            mbar_arrive_if0(sb + B_M + k * 8, L16 | (uint32_t)again);
            if (again) { done = k; break; }
        }
        if (done < NCH) {
            uint32_t bad;
            do {
                look(v, slot);
                bad = 0;
#pragma unroll
                for (int i = 0; i < 6; i++) { stsm2t(ma + i * 1536, v[i].x, v[i].y); stsm1(ma + i * 1536 + 256, v[i].z); bad |= v[i].w ^ FULL_COUNT; }
            } while (++c < SPIN_LIM && __any_sync(0xffffffffu, bad != 0));
            __syncwarp();
#pragma unroll
            for (int k = 0; k < NCH; k++) if (k >= done) mbar_arrive_if0(sb + B_M + k * 8, L16);
        }
        TSTAMP(s, c | t_pack);
    }
    if (!isv) {
        mbar_wait(sb + B_VX + 8, ((NSEG - 1) >> 1) & 1);
        mbar_wait(sb + B_S, 1);
    } else {
        fence_async_smem();
        bar_arrive<NB_RED, 384>();
        mbar_wait(sb + B_S, 1);
        mbar_wait(sb + B_SX + 8, ((NSEG - 1) >> 1) & 1);
        x_scores(sb, NSEG - 1, wq, L16, ev);
        bar_sync<NB_QK, 384>();
        if (wq == 2 && L16 == 0) ox_store(sb, NSEG - 2, h);
        if (wq == 1 && L16 == 0) ox_publish(NSEG - 3, h);
        __syncwarp();
        x_probs(sb, NSEG - 1, wq, L16, ev);
        fence_async_smem();
        bar_arrive<NB_RED, 384>();
        if (wq == 2) { if (L16 == 0) ox_publish(NSEG - 2, h); __syncwarp(); bar_arrive<NB_QK, 384>(); }
        else bar_sync<NB_QK, 384>();
        if (wq == 3 && L16 == 0) { ox_store(sb, NSEG - 1, h); ox_publish(NSEG - 1, h); }
    }
}

__global__ void __launch_bounds__(384, 1)
chain_kernel(const __grid_constant__ CUtensorMap tmWq, const __grid_constant__ CUtensorMap tmWk, const __grid_constant__ CUtensorMap tmWv,
             const __grid_constant__ CUtensorMap tmWo, const __grid_constant__ CUtensorMap tmX, const bf16* __restrict__ mem0, char* const acc) {
    extern __shared__ __align__(1024) uint8_t smem[];
    const uint32_t sb = smem_u32(smem);
    const int tid = threadIdx.x;
    const uint32_t L16 = __shfl_sync(0xffffffffu, (tid & 31) * 16, tid & 31);
    const int w = __shfl_sync(0xffffffffu, tid >> 5, 0), wg = w >> 2, wq = w & 3;
    uint32_t j, h;
    asm("mov.u32 %0, %%cluster_ctarank;" : "=r"(j));
    asm("mov.u32 %0, %%clusterid.x;" : "=r"(h));
    const bool isv = (j == 2);
    const uint32_t peerA = mapa(sb, isv ? 0 : (j ^ 1)), peerB = mapa(sb, isv ? 1 : 2);
    if (DESCPF && w == 10 && L16 < 64) {
        const CUtensorMap* m = L16 == 0 ? &tmX : L16 == 16 ? (isv ? &tmWv : &tmWq) : L16 == 32 ? &tmWk : &tmWo;
        asm volatile("prefetch.tensormap [%0];" ::"l"(m) : "memory");
    }
    if (w == 11) {
        sts128(sb + S_ZERO + L16, 0, 0, 0, 0);
        sts128(sb + S_ZERO + 512 + L16, 0, 0, 0, 0);
        fence_async_smem();
        __syncwarp();
        const int i = L16 >> 4, kb = j * 11 + i;
        if (i < 11 && kb < 32) bulk_s2g(acc + h * 32768 + kb * 1024, sb + S_ZERO, 1024);
        if (i == 11) bulk_s2g(g_time + blockIdx.x * 64, sb + S_ZERO, 256);
        if (i == 12 && blockIdx.x == 0) bulk_s2g(g_flag, sb + S_ZERO, 1024);
        bulk_commit();
    }
    if (tid == 256) {
        for (int c = 0; c < 3; c++) { mbar_init(sb + B_W + 8 * c, 1); mbar_init(sb + B_M + 8 * c, 4); }
        mbar_init(sb + B_WO, 1); mbar_init(sb + B_T, 1);
        mbar_init(sb + B_X, 1); mbar_init(sb + B_X + 8, 1);
        mbar_init(sb + B_S, isv ? 8 : 5);
        mbar_init(sb + B_VX, 1); mbar_init(sb + B_VX + 8, 1);
        mbar_init(sb + B_SX, 1); mbar_init(sb + B_SX + 8, 1);
        asm volatile("fence.mbarrier_init.release.cluster;" ::: "memory");
        const CUtensorMap* m0 = isv ? &tmWv : &tmWq;
        const CUtensorMap* m1 = isv ? &tmWv : &tmWk;
        const int c0 = h * 128 + (isv ? 0 : 64 * j), c1 = h * 128 + (isv ? 64 : 64 * j);
        mbar_expect(sb + B_X, XB_BYTES);
        tma3d(sb + S_XB, &tmX, 0, 0, 0, sb + B_X);
        mbar_expect(sb + B_X + 8, XB_BYTES);
        tma3d(sb + S_XB + XB_BYTES, &tmX, 0, 32, 0, sb + B_X + 8);
#pragma unroll 1
        for (int c = 0; c < (PACE ? 2 : 3); c++) {
            mbar_expect(sb + B_W + 8 * c, 49152);
            tma2d(sb + s_w(c), m0, c0, c * 192, sb + B_W + 8 * c);
            tma2d(sb + s_w(c) + 24576, m1, c1, c * 192, sb + B_W + 8 * c);
        }
    } else if (tid < 256) {
        uint4 v0, v1, v2;
        v0 = *reinterpret_cast<const uint4*>(mem0 + (tid & 7) * DM + (tid >> 3) * 8);
        v1 = *reinterpret_cast<const uint4*>(mem0 + (tid & 7) * DM + (tid >> 3) * 8 + 256);
        if (tid < 64) v2 = *reinterpret_cast<const uint4*>(mem0 + (tid & 7) * DM + (tid >> 3) * 8 + 512);
        sts128(sb + S_MEM + tid * 16, v0.x, v0.y, v0.z, v0.w);
        sts128(sb + S_MEM + 4096 + tid * 16, v1.x, v1.y, v1.z, v1.w);
        if (tid < 64) sts128(sb + S_MEM + 8192 + tid * 16, v2.x, v2.y, v2.z, v2.w);
    }
    __syncthreads();
    if (wg == 2) {
        asm volatile("setmaxnreg.dec.sync.aligned.u32 %0;" ::"n"(REG_AUX));
        if (!isv) chain_aux<false>(sb, L16, wq, j, h, peerA, peerB, &tmWo, &tmX, acc, &tmWq, &tmWk);
        else chain_aux<true>(sb, L16, wq, j, h, peerA, peerB, &tmWo, &tmX, acc, &tmWv, &tmWv);
        __syncwarp();
        cluster_arrive(); cluster_wait();
        TSTAMP(65, 0);
    } else if (wg == 0) {
        asm volatile("setmaxnreg.inc.sync.aligned.u32 %0;" ::"n"(REG_MAIN0));
        if (!isv) chain_main<0>(sb, L16, wq, j, h, peerA, peerB, acc);
        else chain_main<2>(sb, L16, wq, j, h, peerA, peerB, acc);
        cluster_arrive(); cluster_wait();
    } else {
        asm volatile("setmaxnreg.inc.sync.aligned.u32 %0;" ::"n"(REG_MAIN1));
        if (!isv) chain_main<1>(sb, L16, wq, j, h, peerA, peerB, acc);
        else chain_main<3>(sb, L16, wq, j, h, peerA, peerB, acc);
        cluster_arrive(); cluster_wait();
    }
}

constexpr int NHELP = 36;
constexpr uint32_t H_U = 0;
constexpr uint32_t UT_PITCH = 4368;
constexpr uint32_t H_UT = 65536;
constexpr uint32_t KW_BYTES = 8320;
constexpr uint32_t H_KW = 135424;
constexpr uint32_t H_PAR = 201984;
constexpr uint32_t H_KD = 218368;
constexpr uint32_t H_STAGE = 0;
constexpr uint32_t H_RED = 196608;
constexpr uint32_t H_FIN = 212992;
constexpr uint32_t H_BAR = 229376;
constexpr uint32_t B_SMEM = H_BAR + 384;
constexpr uint32_t HB_U = H_BAR, HB_WO = H_BAR + 8, HB_EMPTY = H_BAR + 16, HB_RFULL = H_BAR + 64, HB_REMPTY = H_BAR + 80, HB_FIN = H_BAR + 96, HB_FULL = H_BAR + 128;
__device__ __align__(1024) uint4 g_part[4 * 9 * 4 * 4 * 128];

__device__ __forceinline__ float2 cmul(float2 a, float2 b) { return make_float2(fmaf(a.x, b.x, -a.y * b.y), fmaf(a.x, b.y, a.y * b.x)); }
__device__ __forceinline__ float2 csqr(float2 a) { return make_float2(fmaf(a.x, a.x, -a.y * a.y), (a.x + a.x) * a.y); }
__device__ __forceinline__ float2 cexp(float zr, float zi, float p) {
    const float m = ex2(zr * p);
    const float r = zi * p;
    const float a = (r - rintf(r)) * 6.283185307179586f;
    return make_float2(m * __cosf(a), m * __sinf(a));
}
__device__ __forceinline__ uint32_t pack_f16(float lo, float hi) { uint32_t r; asm("cvt.rn.f16x2.f32 %0, %1, %2;" : "=r"(r) : "f"(hi), "f"(lo)); return r; }
__device__ __forceinline__ void mma16h(float* d, const uint32_t* a, uint32_t b0, uint32_t b1) {
    asm volatile("mma.sync.aligned.m16n8k16.row.col.f32.f16.f16.f32 {%0,%1,%2,%3},{%4,%5,%6,%7},{%8,%9},{%0,%1,%2,%3};"
                 : "+f"(d[0]), "+f"(d[1]), "+f"(d[2]), "+f"(d[3]) : "r"(a[0]), "r"(a[1]), "r"(a[2]), "r"(a[3]), "r"(b0), "r"(b1));
}
__device__ __forceinline__ float bf_round(float x) { return __bfloat162float(__float2bfloat16_rn(x)); }
__device__ __forceinline__ uint32_t lds32(uint32_t a) { uint32_t v; asm volatile("ld.shared.b32 %0,[%1];" : "=r"(v) : "r"(a) : "memory"); return v; }
__device__ __forceinline__ uint32_t lds16(uint32_t a) { uint16_t v; asm volatile("ld.shared.u16 %0,[%1];" : "=h"(v) : "r"(a) : "memory"); return v; }

__device__ __forceinline__ void s4d_kernel(uint32_t par, uint32_t kd, uint32_t kw, int d, int lane, const bf16* __restrict__ logA, const bf16* __restrict__ Aim,
                                           const bf16* __restrict__ Cre, const bf16* __restrict__ Cim, const bf16* __restrict__ logdt) {
    const float dt = bf_round(expf(__bfloat162float(logdt[d])));
    float4 q[4];
    float cmax = 0.f, last = 0.f;
#pragma unroll
    for (int i = 0; i < 4; i++) {
        const int n = d * NST + i * 32 + lane;
        q[i].x = -bf_round(expf(__bfloat162float(logA[n]))) * dt * 1.4426950408889634f;
        q[i].y = __bfloat162float(Aim[n]) * dt * 0.15915494309189535f;
        q[i].z = 2.f * (__bfloat162float(Cre[n]) * dt);
        q[i].w = 2.f * (__bfloat162float(Cim[n]) * dt);
        cmax = fmaxf(cmax, fmaxf(fabsf(q[i].z), fabsf(q[i].w)));
        const float2 e = cexp(q[i].x, q[i].y, 2048.f);
        last += q[i].z * e.x - q[i].w * e.y;
    }
#pragma unroll
    for (int o = 16; o; o >>= 1) { cmax = fmaxf(cmax, __shfl_xor_sync(0xffffffffu, cmax, o)); last += __shfl_xor_sync(0xffffffffu, last, o); }
    const float cs = __uint_as_float(max(__float_as_uint(cmax) & 0x7F800000u, 0x00800000u));
    const float ci = 1.f / cs;
#pragma unroll
    for (int i = 0; i < 4; i++) sts128(par + (i * 32 + lane) * 16, __float_as_uint(q[i].x), __float_as_uint(q[i].y), __float_as_uint(q[i].z * ci), __float_as_uint(q[i].w * ci));
    __syncwarp();
    float acc[5][4];
#pragma unroll
    for (int i = 0; i < 5; i++) acc[i][0] = acc[i][1] = acc[i][2] = acc[i][3] = 0.f;
    const float g = (float)(lane >> 2);
#pragma unroll 1
    for (int ks = 0; ks < 16; ks++) {
        uint32_t A[5][4], B[4][2];
#pragma unroll
        for (int hf = 0; hf < 2; hf++) {
            uint32_t r[4];
            lds128(r, par + (ks * 8 + hf * 4 + (lane & 3)) * 16);
            const float zr = __uint_as_float(r[0]), zi = __uint_as_float(r[1]);
            const float2 c = make_float2(__uint_as_float(r[2]), __uint_as_float(r[3]));
            float2 y = cexp(zr, zi, g), x0 = cexp(zr, zi, 8.f * g + 128.f), x1 = cexp(zr, zi, 8.f * g + 192.f);
            const float2 xl = cexp(zr, zi, 8.f * g + 64.f);
#pragma unroll
            for (int k = 0; k < 4; k++) {
                const float2 cy = cmul(c, y);
                B[k][hf] = pack_f16(cy.x, -cy.y);
                A[k + 1][2 * hf] = pack_f16(x0.x, x0.y);
                A[k + 1][2 * hf + 1] = pack_f16(x1.x, x1.y);
                if (k < 3) { y = csqr(y); x0 = csqr(x0); x1 = csqr(x1); }
            }
            A[0][2 * hf] = pack_f16(y.x, y.y);
            A[0][2 * hf + 1] = pack_f16(xl.x, xl.y);
        }
        mma16h(acc[0], A[0], B[0][0], B[0][1]);
#pragma unroll
        for (int k = 0; k < 4; k++) mma16h(acc[k + 1], A[k + 1], B[k][0], B[k][1]);
    }
#pragma unroll
    for (int i = 0; i < 5; i++) {
        sts32(kd + i * 256 + lane * 4, pack_bf16(acc[i][0] * cs, acc[i][1] * cs));
        sts32(kd + i * 256 + 128 + lane * 4, pack_bf16(acc[i][2] * cs, acc[i][3] * cs));
    }
    if (lane == 0) sts32(kd + 1280, pack_bf16(last, 0.f));
    if (lane < 16) sts32(kw + lane * 4, 0);
    __syncwarp();
    uint32_t carry = 0;
#pragma unroll 4
    for (int it = 0; it < 64; it++) {
        const int l = it * 32 + lane;
        const int jx = l < 128 ? l : (int)__bfloat16_as_ushort(__float2bfloat16_rn((float)l)) - (133 << 7);
        const uint32_t v = lds16(kd + jx * 2);
        uint32_t pv = __shfl_up_sync(0xffffffffu, v, 1);
        if (lane == 0) pv = carry;
        carry = __shfl_sync(0xffffffffu, v, 31);
        sts32(kw + 64 + l * 4, v | (pv << 16));
    }
    __syncwarp();
}

__device__ __forceinline__ void s4d_conv(uint32_t ut, uint32_t kw, int lane) {
    float acc[16][4];
#pragma unroll
    for (int i = 0; i < 16; i++) acc[i][0] = acc[i][1] = acc[i][2] = acc[i][3] = 0.f;
    const uint32_t ka = kw + 64 + ((lane >> 2) - 2 * (lane & 3)) * 4;
    const uint32_t ua = ut + 256 + lane * 8;
#pragma unroll 1
    for (int rho = 0; rho < 8; rho++) {
        uint32_t B[16][2];
#pragma unroll
        for (int q = 0; q < 16; q++) lds64(B[q], ua + q * 256 - rho * 32);
#pragma unroll
        for (int m = 0; m < 16; m++) {
            uint32_t A[4];
            const uint32_t x = ka + m * 512 + rho * 64;
            A[0] = lds32(x); A[1] = lds32(x + 32); A[2] = lds32(x - 32); A[3] = A[0];
#pragma unroll
            for (int i = m; i < 16; i++) mma16(acc[i], A, B[i - m][0], B[i - m][1]);
        }
    }
    __syncwarp();
    const uint32_t ya = ut + 256 + (lane & 7) * 32 + ((lane >> 3) & 1) * 16 + (lane >> 4) * 256;
#pragma unroll
    for (int i = 0; i < 16; i += 2)
        stsm4t(ya + i * 256, pack_bf16(acc[i][0], acc[i][1]), pack_bf16(acc[i][2], acc[i][3]),
               pack_bf16(acc[i + 1][0], acc[i + 1][1]), pack_bf16(acc[i + 1][2], acc[i + 1][3]));
}

__global__ void __launch_bounds__(384, 1)
helper_kernel(const __grid_constant__ CUtensorMap tmU, const __grid_constant__ CUtensorMap tmY, const __grid_constant__ CUtensorMap tmWo,
              const bf16* __restrict__ logA, const bf16* __restrict__ Aim, const bf16* __restrict__ Cre, const bf16* __restrict__ Cim,
              const bf16* __restrict__ logdt, const bf16* __restrict__ Dskip, bf16* __restrict__ out) {
    extern __shared__ __align__(1024) uint8_t smem[];
    const uint32_t sb = smem_u32(smem);
    const int tid = threadIdx.x, lane = tid & 31;
    const int w = __shfl_sync(0xffffffffu, tid >> 5, 0);
    const int d0 = blockIdx.x * 16;
    HSTAMP(0);
    if (tid == 0) {
        mbar_init(sb + HB_U, 1); mbar_init(sb + HB_WO, 1);
        for (int i = 0; i < 6; i++) mbar_init(sb + HB_EMPTY + 8 * i, 4);
        for (int i = 0; i < 24; i++) mbar_init(sb + HB_FULL + 8 * i, 1);
        for (int i = 0; i < 2; i++) { mbar_init(sb + HB_RFULL + 8 * i, 4); mbar_init(sb + HB_REMPTY + 8 * i, 4); mbar_init(sb + HB_FIN + 8 * i, 2); }
        fence_async_smem();
        mbar_expect(sb + HB_U, 65536);
        for (int i = 0; i < 8; i++) tma2d(sb + H_U + i * 8192, &tmU, d0, i * 256, sb + HB_U);
    }
    __syncthreads();
    const int m = lane >> 3, r = lane & 7;
    if (w < 8) {
        s4d_kernel(sb + H_PAR + w * 2048, sb + H_KD + w * 1296, sb + H_KW + w * KW_BYTES, d0 + w, lane, logA, Aim, Cre, Cim, logdt);
    } else {
        for (int i = tid - 256; i < 256; i += 128) sts128(sb + H_UT + (i >> 4) * UT_PITCH + (i & 15) * 16, 0, 0, 0, 0);
        mbar_wait(sb + HB_U, 0);
        const uint32_t src = sb + H_U + ((m & 1) * 8 + r) * 32 + (((m >> 1) ^ (r >> 2)) << 4);
        const uint32_t dst = sb + H_UT + 256 + (lane >> 2) * UT_PITCH + (lane & 3) * 8;
#pragma unroll 4
        for (int grp = w - 8; grp < 128; grp += 4) {
            uint32_t v[4];
            ldsm4t(v, src + grp * 512);
            sts64(dst + grp * 32, v[0], v[1]);
            sts64(dst + 8 * UT_PITCH + grp * 32, v[2], v[3]);
        }
    }
    __syncthreads();
    HSTAMP(1);
    if (w < 8) {
        s4d_conv(sb + H_UT + w * UT_PITCH, sb + H_KW + w * KW_BYTES, lane);
        s4d_kernel(sb + H_PAR + w * 2048, sb + H_KD + w * 1296, sb + H_KW + w * KW_BYTES, d0 + 8 + w, lane, logA, Aim, Cre, Cim, logdt);
        s4d_conv(sb + H_UT + (8 + w) * UT_PITCH, sb + H_KW + w * KW_BYTES, lane);
    }
    __syncthreads();
    HSTAMP(2);
    const int cc = blockIdx.x % 9, kq = blockIdx.x / 9;
    {
        const __nv_bfloat162 D0 = *reinterpret_cast<const __nv_bfloat162*>(Dskip + d0 + (lane & 3) * 2);
        const __nv_bfloat162 D1 = *reinterpret_cast<const __nv_bfloat162*>(Dskip + d0 + 8 + (lane & 3) * 2);
        const uint32_t ua = sb + H_U + ((m & 1) * 8 + r) * 32 + (((m >> 1) ^ (r >> 2)) << 4);
        const uint32_t ya = sb + H_UT + 256 + ((m >> 1) * 8 + r) * UT_PITCH + (m & 1) * 16;
        for (int grp = w; grp < 128; grp += 12) {
            uint32_t u[4], y[4];
            ldsm4(u, ua + grp * 512);
            ldsm4t(y, ya + grp * 32);
#pragma unroll
            for (int i = 0; i < 4; i++) {
                const __nv_bfloat162 o = __hadd2_rn(*reinterpret_cast<__nv_bfloat162*>(&y[i]), __hmul2_rn(*reinterpret_cast<__nv_bfloat162*>(&u[i]), i < 2 ? D0 : D1));
                y[i] = *reinterpret_cast<const uint32_t*>(&o);
            }
            stsm4(ua + grp * 512, y[0], y[1], y[2], y[3]);
        }
        fence_async_smem();
        __syncthreads();
        if (tid == 0) {
            for (int i = 0; i < 8; i++)
                asm volatile("cp.async.bulk.tensor.2d.global.shared::cta.bulk_group [%0, {%1,%2}], [%3];" ::"l"(&tmY), "r"(DM + d0), "r"(i * 256), "r"(sb + H_U + i * 8192) : "memory");
            bulk_commit();
            mbar_expect(sb + HB_WO, 131072);
            for (int i = 0; i < 8; i++) tma2d(sb + 65536 + i * 16384, &tmWo, cc * 64, (kq * 8 + i) * 128, sb + HB_WO);
            asm volatile("cp.async.bulk.wait_group.read 0;" ::: "memory");
        }
    }
    __syncwarp();
    if (w < 8) {
        asm volatile("setmaxnreg.inc.sync.aligned.u32 208;");
        const int wg = w >> 2;
        uint32_t wo[32][4];
        mbar_wait(sb + HB_WO, 0);
        const uint32_t a = sb + 65536 + wg * 65536 + ((m >> 1) * 8 + r) * 128 + (((2 * (w & 3) + (m & 1)) ^ r) << 4);
#pragma unroll
        for (int i = 0; i < 32; i++) ldsm4t(wo[i], a + i * 2048);
        __syncthreads();
        HSTAMP(3);
        const int t = tid & 127;
        int st = 0, ph = 0;
#pragma unroll 1
        for (int s = 0; s < NSEG; s++) {
            const uint32_t desc = (((sb + H_STAGE + st * 65536 + wg * 32768) & 0x3FFFF) >> 4) | (8u << 16);
            float d[16];
#pragma unroll
            for (int q = 0; q < HSPLIT; q++) {
                mbar_wait_long(sb + HB_FULL + ((st * 2 + wg) * 4 + q) * 8, ph);
                wg_fence();
#pragma unroll
                for (int i = q * (32 / HSPLIT); i < (q + 1) * (32 / HSPLIT); i++) {
                    if (i == 0) wg_rs_n32<0, 16, 1>(d, wo[i], desc); else wg_rs_n32<1, 16, 1>(d, wo[i], desc + i * 64);
                }
                wg_commit();
            }
            wg_wait<0>();
            mbar_arrive_if0(sb + HB_EMPTY + (st * 2 + wg) * 8, lane);
            if (++st == 3) { st = 0; ph ^= 1; }
            const uint32_t ra = sb + H_RED + (s & 1) * 8192 + t * 16;
            if (wg == 0) {
                if (s >= 2) mbar_wait_long(sb + HB_REMPTY + (s & 1) * 8, ((s - 2) >> 1) & 1);
#pragma unroll
                for (int i = 0; i < 4; i++) sts128(ra + i * 2048, __float_as_uint(d[4 * i]), __float_as_uint(d[4 * i + 1]), __float_as_uint(d[4 * i + 2]), __float_as_uint(d[4 * i + 3]));
                __syncwarp();
                mbar_arrive_if0(sb + HB_RFULL + (s & 1) * 8, lane);
            } else {
                mbar_wait_long(sb + HB_RFULL + (s & 1) * 8, (s >> 1) & 1);
                if (s >= 2) mbar_wait_long(sb + HB_FIN + (s & 1) * 8, ((s - 2) >> 1) & 1);
                uint4* dst = g_part + (((s & 3) * 9 + cc) * 16 + kq) * 128 + t;
#pragma unroll
                for (int i = 0; i < 4; i++) {
                    uint32_t p[4];
                    lds128(p, ra + i * 2048);
#pragma unroll
                    for (int k = 0; k < 4; k++) p[k] = ((__float_as_uint(__uint_as_float(p[k]) + d[4 * i + k]) + 64) & ~127u) | (s + 1);
                    asm volatile("st.relaxed.gpu.global.v4.u32 [%0], {%1,%2,%3,%4};" ::"l"(dst + i * 512), "r"(p[0]), "r"(p[1]), "r"(p[2]), "r"(p[3]) : "memory");
                }
                __syncwarp();
                mbar_arrive_if0(sb + HB_REMPTY + (s & 1) * 8, lane);
                HSTAMP4(s);
            }
        }
        if (tid == 0) bulk_wait0();
    } else {
        asm volatile("setmaxnreg.dec.sync.aligned.u32 88;");
        __syncthreads();
        if (w == 8) {
            int st = 0, ph = 1, ready = 0;
            for (int s = 0; s < NSEG; s++) {
                unsigned c = 0;
                while (ready <= s) {
                    const unsigned f = ld_acquire(&g_flag[kq * NSEG + min(s + (lane & 3), NSEG - 1)]);
                    ready = s + __ffs(~(__ballot_sync(0xffffffffu, f >= 8) & 15)) - 1;
                    if (++c >= LONG_LIM) break;
                    if (ready <= s && FLAG_NS) __nanosleep(FLAG_NS);
                }
                __syncwarp();
                if (lane == 0) {
                    asm volatile("fence.proxy.async.global;" ::: "memory");
                    HSTAMP3(s);
                    mbar_wait_long(sb + HB_EMPTY + st * 16, ph);
                    mbar_wait_long(sb + HB_EMPTY + st * 16 + 8, ph);
#pragma unroll
                    for (int k = 0; k < 2 * HSPLIT; k++) {
                        const int g = k & 1, q = k >> 1;
                        constexpr uint32_t bytes = 32768 / HSPLIT;
                        const uint32_t bar = sb + HB_FULL + ((st * 2 + g) * 4 + q) * 8;
                        mbar_expect(bar, bytes);
                        asm volatile("cp.async.bulk.shared::cluster.global.mbarrier::complete_tx::bytes [%0], [%1], %2, [%3];"
                                     ::"r"(sb + H_STAGE + st * 65536 + g * 32768 + q * bytes), "l"(g_ox + (s * NH + kq * 8 + g * 4) * 512 + q * (bytes / 16)), "r"(bytes), "r"(bar) : "memory");
                    }
                }
                __syncwarp();
                if (++st == 3) { st = 0; ph ^= 1; }
            }
        } else if (w < 11) {
            const int f = w - 9;
            const uint32_t fa = sb + H_FIN + f * 512;
            for (int s = 0; s < NSEG; s++) {
                mbar_wait_long(sb + HB_REMPTY + (s & 1) * 8, (s >> 1) & 1);
                const uint4* src = g_part + (((s & 3) * 9 + cc) * 16 + kq * 4) * 128 + f * 64 + lane;
                uint4 v[8];
                unsigned c = 0;
                while (true) {
                    uint32_t bad = 0;
#pragma unroll
                    for (int i = 0; i < 8; i++) v[i] = ld_poll(src + (i >> 1) * 128 + (i & 1) * 32);
#pragma unroll
                    for (int i = 0; i < 8; i++) bad |= (v[i].x ^ (s + 1)) | (v[i].y ^ (s + 1)) | (v[i].z ^ (s + 1)) | (v[i].w ^ (s + 1));
                    if (!__any_sync(0xffffffffu, (bad & 127) != 0) || ++c >= LONG_LIM) break;
                    if (FIN_NS) __nanosleep(FIN_NS);
                }
                mbar_arrive_if0(sb + HB_FIN + (s & 1) * 8, lane);
                uint32_t pk[4];
#pragma unroll
                for (int u = 0; u < 2; u++) {
                    float o[4] = {0.f, 0.f, 0.f, 0.f};
#pragma unroll
                    for (int k = 0; k < 4; k++) {
                        o[0] += __uint_as_float(v[2 * k + u].x & ~127u); o[1] += __uint_as_float(v[2 * k + u].y & ~127u);
                        o[2] += __uint_as_float(v[2 * k + u].z & ~127u); o[3] += __uint_as_float(v[2 * k + u].w & ~127u);
                    }
                    pk[2 * u] = pack_bf16(o[0], o[1]); pk[2 * u + 1] = pack_bf16(o[2], o[3]);
                }
                stsm4t(fa + r * 64 + ((m ^ (r >> 1)) << 4), pk[0], pk[1], pk[2], pk[3]);
                __syncwarp();
                uint32_t o4[4];
                lds128(o4, fa + (lane >> 2) * 64 + (((lane & 3) ^ (lane >> 3)) << 4));
                *reinterpret_cast<uint4*>(out + (s * SEG + kq * 8 + (lane >> 2)) * OUTW + cc * 64 + f * 32 + (lane & 3) * 8) = make_uint4(o4[0], o4[1], o4[2], o4[3]);
                __syncwarp();
                HSTAMP2(s);
            }
            asm volatile("griddepcontrol.wait;" ::: "memory");
        }
    }
}

typedef CUresult (*EncodeFn)(CUtensorMap*, CUtensorMapDataType, cuuint32_t, void*, const cuuint64_t*, const cuuint64_t*, const cuuint32_t*,
                             const cuuint32_t*, CUtensorMapInterleave, CUtensorMapSwizzle, CUtensorMapL2promotion, CUtensorMapFloatOOBfill);

void make_map(EncodeFn fn, CUtensorMap* m, const void* p, int rank, const cuuint64_t* dims, const cuuint64_t* strides, const cuuint32_t* box,
              CUtensorMapSwizzle sw = CU_TENSOR_MAP_SWIZZLE_128B, CUtensorMapL2promotion pr = CU_TENSOR_MAP_L2_PROMOTION_L2_128B) {
    const cuuint32_t es[3] = {1, 1, 1};
    fn(m, CU_TENSOR_MAP_DATA_TYPE_BFLOAT16, rank, const_cast<void*>(p), dims, strides, box, es, CU_TENSOR_MAP_INTERLEAVE_NONE,
       sw, pr, CU_TENSOR_MAP_FLOAT_OOB_FILL_NONE);
}

}

extern "C" void kernel_launch(void* const* d_in, const int* in_sizes, int n_in, void* d_out, int out_size) {
    const bf16* x = (const bf16*)d_in[0];
    const bf16* mem0 = (const bf16*)d_in[1];
    const bf16* Wo = (const bf16*)d_in[5];
    bf16* out = (bf16*)d_out;

    static EncodeFn enc = nullptr;
    static char* acc = nullptr;
    if (!enc) {
        void* p = nullptr;
        cudaGetSymbolAddress(&p, g_acc);
        acc = reinterpret_cast<char*>((reinterpret_cast<uintptr_t>(p) + 32767) & ~(uintptr_t)32767);
        void* fn = nullptr;
        cudaDriverEntryPointQueryResult st;
        cudaGetDriverEntryPoint("cuTensorMapEncodeTiled", &fn, cudaEnableDefault, &st);
        enc = (EncodeFn)fn;
        cudaFuncSetAttribute(chain_kernel, cudaFuncAttributeMaxDynamicSharedMemorySize, A_SMEM);
        cudaFuncSetAttribute(helper_kernel, cudaFuncAttributeMaxDynamicSharedMemorySize, B_SMEM);
    }
    CUtensorMap tmW[3], tmWo, tmX;
    {
        const cuuint64_t dims[2] = {4096, 576}, str[1] = {8192};
        const cuuint32_t box[2] = {64, 192};
        for (int i = 0; i < 3; i++) make_map(enc, &tmW[i], d_in[2 + i], 2, dims, str, box, CU_TENSOR_MAP_SWIZZLE_128B, W_PROMO);
    }
    {
        const cuuint64_t dims[2] = {576, 4096}, str[1] = {1152};
        const cuuint32_t box[2] = {64, 128};
        make_map(enc, &tmWo, Wo, 2, dims, str, box);
    }
    {
        const cuuint64_t dims[3] = {64, 2048, 9}, str[2] = {1152, 128};
        const cuuint32_t box[3] = {64, 32, 9};
        make_map(enc, &tmX, x, 3, dims, str, box);
    }
    CUtensorMap tmU, tmY;
    {
        const cuuint64_t dimsU[2] = {576, 2048}, strU[1] = {1152}, dimsY[2] = {1152, 2048}, strY[1] = {2304};
        const cuuint32_t box[2] = {16, 256};
        make_map(enc, &tmU, d_in[7], 2, dimsU, strU, box, CU_TENSOR_MAP_SWIZZLE_32B);
        make_map(enc, &tmY, out, 2, dimsY, strY, box, CU_TENSOR_MAP_SWIZZLE_32B, CU_TENSOR_MAP_L2_PROMOTION_NONE);
    }
    cudaStream_t st = cudaStreamPerThread;
    {
        cudaLaunchConfig_t cfg = {};
        cfg.gridDim = dim3(96); cfg.blockDim = dim3(384); cfg.dynamicSmemBytes = A_SMEM; cfg.stream = st;
        cudaLaunchAttribute at[1];
        at[0].id = cudaLaunchAttributeClusterDimension;
        at[0].val.clusterDim.x = 3; at[0].val.clusterDim.y = 1; at[0].val.clusterDim.z = 1;
        cfg.attrs = at; cfg.numAttrs = 1;
        cudaLaunchKernelEx(&cfg, chain_kernel, tmW[0], tmW[1], tmW[2], tmWo, tmX, mem0, acc);
    }
    {
        cudaLaunchConfig_t cfg = {};
        cfg.gridDim = dim3(NHELP); cfg.blockDim = dim3(384); cfg.dynamicSmemBytes = B_SMEM; cfg.stream = st;
        cudaLaunchAttribute at[1];
        at[0].id = cudaLaunchAttributeProgrammaticStreamSerialization;
        at[0].val.programmaticStreamSerializationAllowed = 1;
        cfg.attrs = at; cfg.numAttrs = 1;
        cudaLaunchKernelEx(&cfg, helper_kernel, tmU, tmY, tmWo, (const bf16*)d_in[8], (const bf16*)d_in[9], (const bf16*)d_in[10],
                           (const bf16*)d_in[11], (const bf16*)d_in[12], (const bf16*)d_in[13], out);
    }
}
```

```cpp
#include <cuda_runtime.h>
#include <cuda_bf16.h>
#include <cuda_fp16.h>
#include <cuda.h>
#include <stdint.h>

typedef __nv_bfloat16 bf16;

#define EVF 15
namespace {

constexpr int DM = 576, NH = 32, DH = 128, SEG = 32, NSEG = 64, SEQ = 2048, NST = 128;
constexpr int OUTW = 2 * DM;
constexpr unsigned SPIN_LIM = 1u << 15;

__device__ __align__(1024) uint4 g_acc[33 * 2048];
__device__ __align__(128) unsigned g_time[NSEG * 96];
__device__ __align__(1024) uint4 g_ox[NSEG * NH * 512];
__device__ __align__(1024) uint4 g_vx[NH * 2 * 512];
__device__ __align__(128) unsigned g_flag[NSEG * 4];
__device__ unsigned g_zero_cnt;

__device__ __forceinline__ uint32_t smem_u32(const void* p) { return (uint32_t)__cvta_generic_to_shared(p); }
__device__ __forceinline__ unsigned clk() { unsigned c; asm volatile("mov.u32 %0, %%clock;" : "=r"(c)::"memory"); return c; }
__device__ __forceinline__ unsigned gtime() { unsigned t; asm volatile("mov.u32 %0, %%globaltimer_lo;" : "=r"(t)::"memory"); return t; }
__device__ __forceinline__ uint32_t slot_off(int s) { return (s >> 1) * 32768 + (s & 1) * 512; }
__device__ __forceinline__ uint32_t lane_off(uint32_t L16) { return (L16 & 0x180) * 8 + (L16 & 0x40) * 4 + (L16 & 0x30); }
__device__ __forceinline__ uint32_t mapa(uint32_t a, uint32_t r) { uint32_t o; asm("mapa.shared::cluster.u32 %0, %1, %2;" : "=r"(o) : "r"(a), "r"(r)); return o; }
__device__ __forceinline__ void mbar_init(uint32_t b, uint32_t n) { asm volatile("mbarrier.init.shared::cta.b64 [%0], %1;" ::"r"(b), "r"(n) : "memory"); }
__device__ __forceinline__ void mbar_arrive(uint32_t b) { asm volatile("mbarrier.arrive.shared::cta.b64 _, [%0];" ::"r"(b) : "memory"); }
__device__ __forceinline__ void mbar_expect(uint32_t b, uint32_t tx) { asm volatile("mbarrier.arrive.expect_tx.shared::cta.b64 _, [%0], %1;" ::"r"(b), "r"(tx) : "memory"); }
__device__ __forceinline__ bool mbar_try(uint32_t b, uint32_t par) {
    uint32_t ok;
    asm volatile("{.reg .pred p; mbarrier.try_wait.parity.shared::cta.b64 p, [%1], %2; selp.u32 %0, 1, 0, p;}" : "=r"(ok) : "r"(b), "r"(par) : "memory");
    return ok;
}
__device__ __forceinline__ bool mbar_test(uint32_t b, uint32_t par) {
    uint32_t ok;
    asm volatile("{.reg .pred p; mbarrier.test_wait.parity.shared::cta.b64 p, [%1], %2; selp.u32 %0, 1, 0, p;}" : "=r"(ok) : "r"(b), "r"(par) : "memory");
    return ok;
}
__device__ __forceinline__ void mbar_wait(uint32_t b, uint32_t par) {
    asm volatile("{.reg .pred p, q; .reg .u32 c; mov.u32 c, 0;\n"
                 "W: mbarrier.try_wait.parity.shared::cta.b64 p, [%0], %1;\n"
                 "@p bra D;\n add.u32 c, c, 1; setp.lt.u32 q, c, %2;\n @q bra W;\n D:\n}" ::"r"(b), "r"(par), "n"(SPIN_LIM) : "memory");
}
constexpr unsigned LONG_LIM = 1u << 17;
__device__ __forceinline__ void mbar_wait_long(uint32_t b, uint32_t par) {
    asm volatile("{.reg .pred p, q; .reg .u32 c; mov.u32 c, 0;\n"
                 "W: mbarrier.try_wait.parity.shared::cta.b64 p, [%0], %1;\n"
                 "@p bra D;\n add.u32 c, c, 1; setp.lt.u32 q, c, %2;\n @q bra W;\n D:\n}" ::"r"(b), "r"(par), "n"(LONG_LIM) : "memory");
}
__device__ __forceinline__ void cluster_sync() { asm volatile("barrier.cluster.arrive.aligned; barrier.cluster.wait.aligned;" ::: "memory"); }
__device__ __forceinline__ void fence_async_smem() { asm volatile("fence.proxy.async.shared::cta;" ::: "memory"); }
__device__ __forceinline__ void ldsm4(uint32_t* r, uint32_t a) { asm volatile("ldmatrix.sync.aligned.m8n8.x4.shared.b16 {%0,%1,%2,%3},[%4];" : "=r"(r[0]), "=r"(r[1]), "=r"(r[2]), "=r"(r[3]) : "r"(a) : "memory"); }
__device__ __forceinline__ void ldsm4t(uint32_t* r, uint32_t a) { asm volatile("ldmatrix.sync.aligned.m8n8.x4.trans.shared.b16 {%0,%1,%2,%3},[%4];" : "=r"(r[0]), "=r"(r[1]), "=r"(r[2]), "=r"(r[3]) : "r"(a) : "memory"); }
__device__ __forceinline__ void stsm1(uint32_t a, uint32_t r0) { asm volatile("stmatrix.sync.aligned.m8n8.x1.shared.b16 [%0],{%1};" ::"r"(a), "r"(r0) : "memory"); }
__device__ __forceinline__ void stsm2t(uint32_t a, uint32_t r0, uint32_t r1) { asm volatile("stmatrix.sync.aligned.m8n8.x2.trans.shared.b16 [%0],{%1,%2};" ::"r"(a), "r"(r0), "r"(r1) : "memory"); }
__device__ __forceinline__ void stsm4t(uint32_t a, uint32_t r0, uint32_t r1, uint32_t r2, uint32_t r3) { asm volatile("stmatrix.sync.aligned.m8n8.x4.trans.shared.b16 [%0],{%1,%2,%3,%4};" ::"r"(a), "r"(r0), "r"(r1), "r"(r2), "r"(r3) : "memory"); }
__device__ __forceinline__ void stsm4(uint32_t a, uint32_t r0, uint32_t r1, uint32_t r2, uint32_t r3) { asm volatile("stmatrix.sync.aligned.m8n8.x4.shared.b16 [%0],{%1,%2,%3,%4};" ::"r"(a), "r"(r0), "r"(r1), "r"(r2), "r"(r3) : "memory"); }
__device__ __forceinline__ void sts32(uint32_t a, uint32_t v) { asm volatile("st.shared.b32 [%0], %1;" ::"r"(a), "r"(v) : "memory"); }
__device__ __forceinline__ void sts64(uint32_t a, uint32_t x, uint32_t y) { asm volatile("st.shared.v2.b32 [%0], {%1,%2};" ::"r"(a), "r"(x), "r"(y) : "memory"); }
__device__ __forceinline__ void sts128(uint32_t a, uint32_t x, uint32_t y, uint32_t z, uint32_t w) { asm volatile("st.shared.v4.b32 [%0], {%1,%2,%3,%4};" ::"r"(a), "r"(x), "r"(y), "r"(z), "r"(w) : "memory"); }
__device__ __forceinline__ void lds64(uint32_t* r, uint32_t a) { asm volatile("ld.shared.v2.b32 {%0,%1},[%2];" : "=r"(r[0]), "=r"(r[1]) : "r"(a) : "memory"); }
__device__ __forceinline__ float2 lds64f(uint32_t a) { float2 v; asm volatile("ld.shared.v2.f32 {%0,%1},[%2];" : "=f"(v.x), "=f"(v.y) : "r"(a) : "memory"); return v; }
__device__ __forceinline__ void lds128(uint32_t* r, uint32_t a) { asm volatile("ld.shared.v4.b32 {%0,%1,%2,%3},[%4];" : "=r"(r[0]), "=r"(r[1]), "=r"(r[2]), "=r"(r[3]) : "r"(a) : "memory"); }
__device__ __forceinline__ void st_async64(uint32_t a, uint32_t x, uint32_t y, uint32_t bar) {
    asm volatile("st.async.weak.shared::cluster.mbarrier::complete_tx::bytes.v2.b32 [%0], {%1,%2}, [%3];" ::"r"(a), "r"(x), "r"(y), "r"(bar) : "memory");
}
__device__ __forceinline__ void st_async32(uint32_t a, uint32_t x, uint32_t bar) {
    asm volatile("st.async.weak.shared::cluster.mbarrier::complete_tx::bytes.b32 [%0], %1, [%2];" ::"r"(a), "r"(x), "r"(bar) : "memory");
}
__device__ __forceinline__ void ldsm2(uint32_t* r, uint32_t a) { asm volatile("ldmatrix.sync.aligned.m8n8.x2.shared.b16 {%0,%1},[%2];" : "=r"(r[0]), "=r"(r[1]) : "r"(a) : "memory"); }
__device__ __forceinline__ uint32_t pack_f16_sat(float lo, float hi) { uint32_t r; asm("cvt.rn.satfinite.f16x2.f32 %0, %1, %2;" : "=r"(r) : "f"(hi), "f"(lo)); return r; }
__device__ __forceinline__ __half2 as_h2(uint32_t x) { return *reinterpret_cast<__half2*>(&x); }
__device__ __forceinline__ uint32_t as_u32(__half2 x) { return *reinterpret_cast<uint32_t*>(&x); }
__device__ __forceinline__ uint32_t pack_bf16(float lo, float hi) { uint32_t r; asm("cvt.rn.bf16x2.f32 %0, %1, %2;" : "=r"(r) : "f"(hi), "f"(lo)); return r; }
__device__ __forceinline__ float ex2(float x) { float r; asm("ex2.approx.ftz.f32 %0, %1;" : "=f"(r) : "f"(x)); return r; }
__device__ __forceinline__ float rcp(float x) { float r; asm("rcp.approx.ftz.f32 %0, %1;" : "=f"(r) : "f"(x)); return r; }
__device__ __forceinline__ void mma16(float* d, const uint32_t* a, uint32_t b0, uint32_t b1) {
    asm volatile("mma.sync.aligned.m16n8k16.row.col.f32.bf16.bf16.f32 {%0,%1,%2,%3},{%4,%5,%6,%7},{%8,%9},{%0,%1,%2,%3};"
                 : "+f"(d[0]), "+f"(d[1]), "+f"(d[2]), "+f"(d[3]) : "r"(a[0]), "r"(a[1]), "r"(a[2]), "r"(a[3]), "r"(b0), "r"(b1));
}
__device__ __forceinline__ void mma16z(float* d, const uint32_t* a, uint32_t b0, uint32_t b1) {
    asm volatile("mma.sync.aligned.m16n8k16.row.col.f32.bf16.bf16.f32 {%0,%1,%2,%3},{%4,%5,%6,%7},{%8,%9},{%10,%10,%10,%10};"
                 : "=f"(d[0]), "=f"(d[1]), "=f"(d[2]), "=f"(d[3]) : "r"(a[0]), "r"(a[1]), "r"(a[2]), "r"(a[3]), "r"(b0), "r"(b1), "f"(0.f));
}
__device__ __forceinline__ void mma8(float* d, uint32_t a0, uint32_t a1, uint32_t b0) {
    asm volatile("mma.sync.aligned.m16n8k8.row.col.f32.bf16.bf16.f32 {%0,%1,%2,%3},{%4,%5},{%6},{%0,%1,%2,%3};"
                 : "+f"(d[0]), "+f"(d[1]), "+f"(d[2]), "+f"(d[3]) : "r"(a0), "r"(a1), "r"(b0));
}
template <int ACC>
__device__ __forceinline__ void mma_sp(float* d, const uint32_t* a, const uint32_t* b) {
    if (ACC)
        asm volatile("mma.sp::ordered_metadata.sync.aligned.m16n8k32.row.col.f32.bf16.bf16.f32 {%0,%1,%2,%3},{%4,%5,%6,%7},{%8,%9,%10,%11},{%0,%1,%2,%3},%12,0x0;"
                     : "+f"(d[0]), "+f"(d[1]), "+f"(d[2]), "+f"(d[3])
                     : "r"(a[0]), "r"(a[1]), "r"(a[2]), "r"(a[3]), "r"(b[0]), "r"(b[1]), "r"(b[2]), "r"(b[3]), "r"(0xEEEE4444u));
    else
        asm volatile("mma.sp::ordered_metadata.sync.aligned.m16n8k32.row.col.f32.bf16.bf16.f32 {%0,%1,%2,%3},{%4,%5,%6,%7},{%8,%9,%10,%11},{%13,%13,%13,%13},%12,0x0;"
                     : "=f"(d[0]), "=f"(d[1]), "=f"(d[2]), "=f"(d[3])
                     : "r"(a[0]), "r"(a[1]), "r"(a[2]), "r"(a[3]), "r"(b[0]), "r"(b[1]), "r"(b[2]), "r"(b[3]), "r"(0xEEEE4444u), "f"(0.f));
}
__device__ __forceinline__ void mbar_arrive_if0(uint32_t b, uint32_t z) { asm volatile("{.reg .pred p; setp.eq.u32 p, %1, 0; @p mbarrier.arrive.shared::cta.b64 _, [%0];}" ::"r"(b), "r"(z) : "memory"); }
__device__ __forceinline__ void mbar_expect_if0(uint32_t b, uint32_t tx, uint32_t z) { asm volatile("{.reg .pred p; setp.eq.u32 p, %2, 0; @p mbarrier.arrive.expect_tx.shared::cta.b64 _, [%0], %1;}" ::"r"(b), "r"(tx), "r"(z) : "memory"); }
__device__ __forceinline__ float lds32f(uint32_t a) { float v; asm volatile("ld.shared.f32 %0,[%1];" : "=f"(v) : "r"(a) : "memory"); return v; }
__device__ __forceinline__ void wg_fence() { asm volatile("wgmma.fence.sync.aligned;" ::: "memory"); }
__device__ __forceinline__ void wg_commit() { asm volatile("wgmma.commit_group.sync.aligned;" ::: "memory"); }
template <int N> __device__ __forceinline__ void wg_wait() { asm volatile("wgmma.wait_group.sync.aligned %0;" ::"n"(N) : "memory"); }
__device__ __forceinline__ void delay(unsigned n) { if (n) { const unsigned t0 = clk(); while (clk() - t0 < n) {} } }
template <int ACC, uint32_t DHI = 0x40000040u, int TB = 0>
__device__ __forceinline__ void wg_rs_n32(float* d, const uint32_t* a, uint32_t dlo) {
    if (ACC)
        asm volatile("{.reg .b64 db; mov.b64 db, {%20, %21};\n"
                     "wgmma.mma_async.sync.aligned.m64n32k16.f32.bf16.bf16 {%0,%1,%2,%3,%4,%5,%6,%7,%8,%9,%10,%11,%12,%13,%14,%15},{%16,%17,%18,%19},db,1,1,1,%22;}"
                     : "+f"(d[0]), "+f"(d[1]), "+f"(d[2]), "+f"(d[3]), "+f"(d[4]), "+f"(d[5]), "+f"(d[6]), "+f"(d[7]),
                       "+f"(d[8]), "+f"(d[9]), "+f"(d[10]), "+f"(d[11]), "+f"(d[12]), "+f"(d[13]), "+f"(d[14]), "+f"(d[15])
                     : "r"(a[0]), "r"(a[1]), "r"(a[2]), "r"(a[3]), "r"(dlo), "r"(DHI), "n"(TB));
    else
        asm volatile("{.reg .b64 db; mov.b64 db, {%20, %21};\n"
                     "wgmma.mma_async.sync.aligned.m64n32k16.f32.bf16.bf16 {%0,%1,%2,%3,%4,%5,%6,%7,%8,%9,%10,%11,%12,%13,%14,%15},{%16,%17,%18,%19},db,0,1,1,%22;}"
                     : "=f"(d[0]), "=f"(d[1]), "=f"(d[2]), "=f"(d[3]), "=f"(d[4]), "=f"(d[5]), "=f"(d[6]), "=f"(d[7]),
                       "=f"(d[8]), "=f"(d[9]), "=f"(d[10]), "=f"(d[11]), "=f"(d[12]), "=f"(d[13]), "=f"(d[14]), "=f"(d[15])
                     : "r"(a[0]), "r"(a[1]), "r"(a[2]), "r"(a[3]), "r"(dlo), "r"(DHI), "n"(TB));
}
__device__ __forceinline__ uint32_t desc_lo(uint32_t addr) { return ((addr & 0x3FFFF) >> 4) | (1u << 16); }
__device__ __forceinline__ void tma2d(uint32_t dst, const CUtensorMap* m, int c0, int c1, uint32_t bar) {
    asm volatile("cp.async.bulk.tensor.2d.shared::cluster.global.mbarrier::complete_tx::bytes [%0], [%1, {%2,%3}], [%4];"
                 ::"r"(dst), "l"(m), "r"(c0), "r"(c1), "r"(bar) : "memory");
}
__device__ __forceinline__ uint64_t evict_first() { uint64_t p; asm("createpolicy.fractional.L2::evict_first.b64 %0, 1.0;" : "=l"(p)); return p; }
__device__ __forceinline__ void tma2d_once(uint32_t dst, const CUtensorMap* m, int c0, int c1, uint32_t bar) {
    const uint64_t pol = evict_first();
    asm volatile("cp.async.bulk.tensor.2d.shared::cluster.global.mbarrier::complete_tx::bytes.L2::cache_hint [%0], [%1, {%2,%3}], [%4], %5;"
                 ::"r"(dst), "l"(m), "r"(c0), "r"(c1), "r"(bar), "l"(pol) : "memory");
}
__device__ __forceinline__ void tma3d(uint32_t dst, const CUtensorMap* m, int c0, int c1, int c2, uint32_t bar) {
    asm volatile("cp.async.bulk.tensor.3d.shared::cluster.global.mbarrier::complete_tx::bytes [%0], [%1, {%2,%3,%4}], [%5];"
                 ::"r"(dst), "l"(m), "r"(c0), "r"(c1), "r"(c2), "r"(bar) : "memory");
}
__device__ __forceinline__ void tma3d_mc(uint32_t dst, const CUtensorMap* m, int c0, int c1, int c2, uint32_t bar, uint16_t mask) {
    if (EVF & 8) asm volatile("cp.async.bulk.tensor.3d.shared::cluster.global.mbarrier::complete_tx::bytes.multicast::cluster.L2::cache_hint [%0], [%1, {%2,%3,%4}], [%5], %6, %7;"
                 ::"r"(dst), "l"(m), "r"(c0), "r"(c1), "r"(c2), "r"(bar), "h"(mask), "l"(evict_first()) : "memory");
    else
    asm volatile("cp.async.bulk.tensor.3d.shared::cluster.global.mbarrier::complete_tx::bytes.multicast::cluster [%0], [%1, {%2,%3,%4}], [%5], %6;"
                 ::"r"(dst), "l"(m), "r"(c0), "r"(c1), "r"(c2), "r"(bar), "h"(mask) : "memory");
}
__device__ __forceinline__ void bulk_g2s_mc(uint32_t dst, const void* src, uint32_t bytes, uint32_t bar, uint16_t mask) {
    asm volatile("cp.async.bulk.shared::cluster.global.mbarrier::complete_tx::bytes.multicast::cluster [%0], [%1], %2, [%3], %4;"
                 ::"r"(dst), "l"(src), "r"(bytes), "r"(bar), "h"(mask) : "memory");
}
__device__ __forceinline__ void tma2d_prefetch(const CUtensorMap* m, int c0, int c1) {
    asm volatile("cp.async.bulk.prefetch.tensor.2d.L2.global [%0, {%1,%2}];" ::"l"(m), "r"(c0), "r"(c1) : "memory");
}
__device__ __forceinline__ void bulk_s2c(uint32_t dst, uint32_t src, uint32_t bytes, uint32_t bar) {
    asm volatile("cp.async.bulk.shared::cluster.shared::cta.mbarrier::complete_tx::bytes [%0], [%1], %2, [%3];" ::"r"(dst), "r"(src), "r"(bytes), "r"(bar) : "memory");
}
__device__ __forceinline__ void bulk_s2g(void* dst, uint32_t src, uint32_t bytes) {
    asm volatile("cp.async.bulk.global.shared::cta.bulk_group [%0], [%1], %2;" ::"l"(dst), "r"(src), "r"(bytes) : "memory");
}
__device__ __forceinline__ void bulk_commit() { asm volatile("cp.async.bulk.commit_group;" ::: "memory"); }
__device__ __forceinline__ void bulk_wait0() { asm volatile("cp.async.bulk.wait_group 0;" ::: "memory"); }
__device__ __forceinline__ uint4 ld_poll(const void* p) {
    uint4 v;
    asm volatile("ld.relaxed.gpu.global.v4.u32 {%0,%1,%2,%3},[%4];" : "=r"(v.x), "=r"(v.y), "=r"(v.z), "=r"(v.w) : "l"(p) : "memory");
    return v;
}
template <int IMM>
__device__ __forceinline__ void ld_poll_at(uint4& v, const void* p) {
    asm volatile("ld.relaxed.gpu.global.v4.u32 {%0,%1,%2,%3},[%4+%5];" : "=r"(v.x), "=r"(v.y), "=r"(v.z), "=r"(v.w) : "l"(p), "n"(IMM) : "memory");
}
__device__ __forceinline__ void look(uint4 (&v)[6], const void* p) {
    ld_poll_at<0>(v[0], p); ld_poll_at<16384>(v[1], p); ld_poll_at<64>(v[2], p);
    ld_poll_at<16384 + 64>(v[3], p); ld_poll_at<128>(v[4], p); ld_poll_at<16384 + 128>(v[5], p);
}
__device__ __forceinline__ unsigned ld_acquire(const unsigned* p) { unsigned v; asm volatile("ld.acquire.gpu.global.u32 %0,[%1];" : "=r"(v) : "l"(p) : "memory"); return v; }
__device__ __forceinline__ void red_release(unsigned* p, unsigned v) { asm volatile("red.release.gpu.global.add.u32 [%0], %1;" ::"l"(p), "r"(v) : "memory"); }

template <int ID, int N> __device__ __forceinline__ void bar_sync() { asm volatile("bar.sync %0, %1;" ::"n"(ID), "n"(N) : "memory"); }
template <int ID, int N> __device__ __forceinline__ void bar_arrive() { asm volatile("bar.arrive %0, %1;" ::"n"(ID), "n"(N) : "memory"); }
__device__ __forceinline__ void cluster_arrive() { asm volatile("barrier.cluster.arrive.relaxed.aligned;" ::: "memory"); }
__device__ __forceinline__ void cluster_wait() { asm volatile("barrier.cluster.wait.aligned;" ::: "memory"); }

constexpr uint32_t XB_BYTES = 36864;
constexpr uint32_t S_XB = 0;
constexpr uint32_t S_QM = 73728;
constexpr uint32_t S_KM = 74752;
constexpr uint32_t S_OM = 75776;
constexpr uint32_t S_SP = 77824;
constexpr uint32_t S_SUM = 80384;
constexpr uint32_t S_TGT = 81408;
constexpr uint32_t S_VM = 147456;
constexpr uint32_t S_QX = 86016;
constexpr uint32_t S_PX = S_QX;
constexpr uint32_t S_KX = 94208;
constexpr uint32_t S_VX = 102400;
constexpr uint32_t S_SX = 135168;
constexpr uint32_t S_OX = 155648;
constexpr uint32_t S_MEM = 172032;
constexpr uint32_t S_WO = 181248;
constexpr uint32_t S_BAR = 230400;
constexpr uint32_t S_ZERO = S_BAR + 128;
constexpr uint32_t A_SMEM = S_ZERO + 1024;
__host__ __device__ constexpr uint32_t s_w(int c) { return c == 0 ? S_WO : 73728 + (c - 1) * 49152; }
constexpr uint32_t B_W = S_BAR, B_WO = S_BAR + 24, B_X = S_BAR + 32, B_S = S_BAR + 48, B_VX = S_BAR + 56, B_SX = S_BAR + 72, B_M = S_BAR + 88, B_T = S_BAR + 112;
constexpr int NB_QK = 1, NB_O = 2, NB_RED = 3, NB_P = 4, NB_AUX = 5, NB_PRO = 6, NB_X = 7, NB_GO = 8, NB_L = 9, NB_PV = 10, NB_P2 = 11;

constexpr float SM_SCALE = 0.08838834764831845f * 1.4426950408889634f;
constexpr uint32_t ONES = 0x3F803F80u;
constexpr uint32_t FULL_COUNT = 0x4200u;
#define XLIM NSEG
#define TGT_NS 1040
#define LOOK_NS 100
#define RCP_AT 2
#define NCH 2
#define XTMA_NS 50
#define REG_MAIN0 232
#define REG_MAIN1 232
#define REG_AUX 40

#define HAND_AT 26
#define VX_AT 0
#define PV_MODE 2
#define W_PROMO CU_TENSOR_MAP_L2_PROMOTION_L2_128B
#define DESCPF 1
#define WO_AFTER 2
#define FIRST_NS 450
#define PACE 1
#define DEP_LATE 1
#define HSPLIT 2
#define FIN_NS 40
#define WO_LOOP 1
#define YST 1
#define TRICKLE_NS 700
#define REFRESH 0
#define PACE_H -1
#define U_NS 0
#define FIN0_NS 0
#define FLAG_NS 40
static_assert(REG_MAIN0 + REG_MAIN1 + REG_AUX <= 504, "the three warpgroups share 3 x 168 registers");
#define HSTAMP(i) do {} while (0)
#define HSTAMP2(i) do {} while (0)
#define HSTAMP3(i) do {} while (0)
#define HSTAMP4(i) do {} while (0)
#define TSTAMP(i, e) do {} while (0)

__device__ __forceinline__ void load_scores(uint32_t a, __half2 (&hs)[5]) {
    uint32_t r[10];
    ldsm4(r, a);
    ldsm4(r + 4, a + 512);
    ldsm2(r + 8, a + 1024);
    const __half2 hf = as_h2(0x38003800u);
#pragma unroll
    for (int T = 0; T < 5; T++) hs[T] = __hfma2(as_h2(r[2 * T]), hf, __hmul2(as_h2(r[2 * T + 1]), hf));
}
__device__ __forceinline__ void softmax_exp(const __half2 (&hs)[5], float (&ev)[10]) {
    __half2 m = __hmax2(__hmax2(__hmax2(hs[0], hs[1]), __hmax2(hs[2], hs[3])), hs[4]);
    const uint32_t mu = as_u32(m);
    const uint32_t m1 = __shfl_xor_sync(0xffffffffu, mu, 1), m2 = __shfl_xor_sync(0xffffffffu, mu, 2), m3 = __shfl_xor_sync(0xffffffffu, mu, 3);
    m = __hmax2(__hmax2(m, as_h2(m1)), __hmax2(as_h2(m2), as_h2(m3)));
    const float mc = -fmaxf(__low2float(m), __high2float(m)) * (2.f * SM_SCALE);
#pragma unroll
    for (int T = 0; T < 5; T++) {
        ev[2 * T] = ex2(fmaf(__low2float(hs[T]), 2.f * SM_SCALE, mc));
        ev[2 * T + 1] = ex2(fmaf(__high2float(hs[T]), 2.f * SM_SCALE, mc));
    }
}

__device__ __forceinline__ void x_scores(uint32_t sb, int seg, int wq, uint32_t L16, float (&ev)[10]) {
    __half2 hs[5];
    load_scores(sb + S_SX + (seg & 1) * 5120 + wq * 1280 + L16, hs);
    const int dg = (int)(L16 >> 6) - (int)((L16 >> 3) & 6) + 8 * wq;
#pragma unroll
    for (int T = 0; T < 4; T++) {
        uint32_t u = as_u32(hs[T]);
        if (dg < 8 * T + 1) u = (u & 0xFFFFu) | 0xFC000000u;
        if (dg < 8 * T) u = 0xFC00FC00u;
        hs[T] = as_h2(u);
    }
    softmax_exp(hs, ev);
}
__device__ __forceinline__ void x_probs(uint32_t sb, int seg, int wq, uint32_t L16, const float (&ev)[10]) {
    float l = ((ev[0] + ev[1]) + (ev[2] + ev[3])) + ((ev[4] + ev[5]) + (ev[6] + ev[7])) + (ev[8] + ev[9]);
    const float l1 = __shfl_xor_sync(0xffffffffu, l, 1), l2 = __shfl_xor_sync(0xffffffffu, l, 2), l3 = __shfl_xor_sync(0xffffffffu, l, 3);
    const float r = rcp((l + l1) + (l2 + l3));
    const uint32_t a = sb + S_PX + (seg & 1) * 4096 + wq * 640 + (L16 >> 2);
#pragma unroll
    for (int i = 0; i < 5; i++) sts32(a + i * 128, pack_bf16(ev[2 * i] * r, ev[2 * i + 1] * r));
}
__device__ __forceinline__ void x_pv_load(uint32_t sb, int seg, int w, uint32_t L16, uint32_t (&a)[3][4]) {
    lds128(a[0], sb + S_VX + (seg & 3) * 8192 + w * 1024 + L16);
    lds128(a[1], sb + S_VX + (seg & 3) * 8192 + w * 1024 + 512 + L16);
    lds64(a[2], sb + S_VM + (seg & 3) * 2048 + w * 256 + (L16 >> 1));
    a[2][2] = 0; a[2][3] = 0;
}
__device__ __forceinline__ void x_pv_run(uint32_t sb, int seg, const uint32_t (&a)[3][4], uint32_t (&pk)[8]) {
    const uint32_t d = ((sb + S_PX + (seg & 1) * 4096) & 0x3FFFF) >> 4;
    float o[16];
    wg_fence();
    wg_rs_n32<0, 40>(o, a[0], d | (8u << 16));
    wg_rs_n32<1, 40>(o, a[1], (d + 16) | (8u << 16));
    wg_rs_n32<1, 40>(o, a[2], d + 32);
    wg_commit();
    wg_wait<0>();
#pragma unroll
    for (int i = 0; i < 8; i++) pk[i] = pack_bf16(o[2 * i], o[2 * i + 1]);
}
__device__ __forceinline__ void x_pv_store(uint32_t sb, int seg, int w, uint32_t L16, const uint32_t (&pk)[8]) {
    const uint32_t a = sb + S_OX + (seg & 1) * 8192 + w * 1024 + L16;
    stsm4(a, pk[0], pk[1], pk[2], pk[3]);
    stsm4(a + 512, pk[4], pk[5], pk[6], pk[7]);
}
__device__ __forceinline__ void ox_store(uint32_t sb, int seg, uint32_t h) {
    fence_async_smem();
    bulk_s2g(g_ox + (seg * NH + h) * 512, sb + S_OX + (seg & 1) * 8192, 8192);
    bulk_commit();
}
__device__ __forceinline__ void ox_publish(int seg, uint32_t h) {
    bulk_wait0();
    asm volatile("fence.proxy.async.global;" ::: "memory");
    asm volatile("red.relaxed.gpu.global.add.u32 [%0], 1;" ::"l"(&g_flag[(h >> 3) * NSEG + seg]) : "memory");
}
__device__ __forceinline__ void vx_store(uint32_t sb, int seg, uint32_t h) {
    fence_async_smem();
    bulk_s2g(g_vx + (h * 2 + (seg & 1)) * 512, sb + S_VX + (seg & 3) * 8192, 8192);
    bulk_commit();
}
__device__ __forceinline__ void vx_fetch(uint32_t sb, int seg, uint32_t h) {
    bulk_wait0();
    bulk_g2s_mc(sb + S_VX + (seg & 3) * 8192, g_vx + (h * 2 + (seg & 1)) * 512, 8192, sb + B_VX + (seg & 1) * 8, 3);
}

__device__ __forceinline__ void x_pack(const float (&d)[16], uint32_t (&pk)[8]) {
#pragma unroll
    for (int i = 0; i < 8; i++) pk[i] = pack_bf16(d[2 * i], d[2 * i + 1]);
}
__device__ __forceinline__ void x_write(uint32_t sb, const uint32_t (&pk)[8], int seg, bool isv, int w, uint32_t L16) {
    if (!isv) {
        const uint32_t a = sb + S_QX + (w >> 2) * 8192 + (seg & 1) * 4096 + (w & 3) * 256 + (L16 & 0xF0) + (L16 & 0x100) * 4;
        stsm4t(a, pk[0], pk[1], pk[2], pk[3]);
        stsm4t(a + 2048, pk[4], pk[5], pk[6], pk[7]);
    } else {
        const uint32_t a = sb + S_VX + (seg & 3) * 8192 + w * 1024 + L16;
        sts128(a, pk[0], pk[1], pk[2], pk[3]);
        sts128(a + 512, pk[4], pk[5], pk[6], pk[7]);
    }
}

template <int K0, int K1>
__device__ __forceinline__ void x_project(float (&d)[16], const uint32_t (&wA)[36][4], uint32_t desc) {
#pragma unroll
    for (int i = K0; i < K1; i++) {
        const uint32_t db = desc + (((i >> 2) * 4096 + (i & 3) * 32) >> 4);
        if (i == 0) wg_rs_n32<0>(d, wA[i], db); else wg_rs_n32<1>(d, wA[i], db);
    }
}

__device__ __forceinline__ void mem_scores(uint32_t sb, uint32_t peerA, uint32_t peerB, uint32_t off, const uint32_t (&q0)[4], const uint32_t (&q1)[4],
                                           const uint32_t (&k0)[4], const uint32_t (&k1)[4]) {
    float e0[4], o0[4], e1[4], o1[4];
    mma16z(e0, q0, k0[0], k0[1]);
    mma16z(o0, q0, k0[2], k0[3]);
    mma16z(e1, q1, k1[0], k1[1]);
    mma16z(o1, q1, k1[2], k1[3]);
    const uint32_t sc = pack_f16_sat((e0[0] + o0[2]) + (e1[0] + o1[2]), (e0[1] + o0[3]) + (e1[1] + o1[3]));
    st_async32(peerB + off, sc, peerB + B_S);
    st_async32(peerA + off, sc, peerA + B_S);
    sts32(sb + off, sc);
    __syncwarp();
}

__device__ __forceinline__ unsigned post_time(int s, uint32_t L16) {
    delay(1);
    const unsigned t = gtime() | 1;
    if (L16 == 0) asm volatile("st.relaxed.gpu.global.u32 [%0], %1;" ::"l"(g_time + s * 96 + blockIdx.x), "r"(t) : "memory");
    return t;
}
__device__ __forceinline__ void plan_look(uint32_t sb, int s, uint32_t L16, unsigned t) {
    const char* p = reinterpret_cast<const char*>(g_time) + s * 384 + (L16 < 384 ? L16 : 0);
    uint4 v;
    unsigned c = 0;
    do { v = ld_poll(p); } while (__any_sync(0xffffffffu, (v.x & v.y & v.z & v.w & 1) == 0) && ++c < SPIN_LIM);
    const int d = max(max((int)(v.x - t), (int)(v.y - t)), max((int)(v.z - t), (int)(v.w - t))) + (s == 0 ? FIRST_NS : 0);
    const unsigned tgt = t + min(__reduce_max_sync(0xffffffffu, d), 20000) + TGT_NS;
    if (L16 < 48) { const uint32_t r = mapa(sb, L16 >> 4); st_async32(r + S_TGT, tgt, r + B_T); }
}

__device__ __forceinline__ void load_wo(uint32_t sb, int w, uint32_t L16, uint32_t (&woA)[8][4], uint32_t (&woB)[4][4]) {
    mbar_wait(sb + B_WO, 0);
    if (w < 4) TSTAMP(73, 0);
    const int m = L16 >> 7, r = (L16 >> 4) & 7;
    const int ca = 3 * w + (m & 1), cb = 3 * w + 2;
    const uint32_t aA = sb + S_WO + (ca >> 3) * 16384 + ((m >> 1) * 8 + r) * 128 + (((ca & 7) ^ r) << 4);
    const int eB = ((m & 2) + ((r >> 1) & 1)) * 8 + 4 * (m & 1) + 2 * (r >> 2) + (r & 1);
    const uint32_t aB = sb + S_WO + (cb >> 3) * 16384 + eB * 128 + (((cb & 7) ^ (eB & 7)) << 4);
#pragma unroll
    for (int i = 0; i < 8; i++) ldsm4t(woA[i], aA + i * 2048);
#pragma unroll
    for (int i = 0; i < 4; i++) ldsm4t(woB[i], aB + i * 4096);
}

template <int ROLE>
__device__ __forceinline__ void chain_main(const uint32_t sb, const uint32_t lane16, const int wq, const uint32_t j, const uint32_t h,
                                           const uint32_t peerA, const uint32_t peerB, char* const acc) {
    uint32_t L16 = lane16;
    constexpr bool isv = ROLE >= 2;
    constexpr int wg = ROLE & 1;
    const int w = wg * 4 + wq;
    const uint32_t xdesc = desc_lo(sb + S_XB);
    const uint32_t zero = h >> 20;
    uint32_t wA[36][4], woA[8][4], woB[4][4];
    float xd[16];
    {
        const int m = L16 >> 7, r = (L16 >> 4) & 7;
        const int blk = (ROLE == 1) ? ((wq & 2) * 2 + (wq & 1) + (m & 1) * 2) : (2 * wq + (m & 1));
        const uint32_t a = sb + wg * 24576 + ((m >> 1) * 8 + r) * 128 + ((blk ^ r) << 4);
        float x0[16];
#pragma unroll
        for (int c = 0; c < 3; c++) {
            mbar_wait(sb + B_W + 8 * c, 0);
            if (wg == 0) TSTAMP(70 + c, 0);
#pragma unroll
            for (int i = 0; i < 12; i++) ldsm4t(wA[12 * c + i], a + s_w(c) + i * 2048);
            if (c == WO_AFTER) bar_arrive<NB_PRO, 288>();
            if (c == 0) { mbar_wait(sb + B_X, 0); mbar_wait(sb + B_X + 8, 0); }
            if (c == 2) { bar_sync<NB_O, 256>(); cluster_arrive(); }
            wg_fence();
            if (c == 0) { x_project<0, 12>(x0, wA, xdesc); x_project<0, 12>(xd, wA, xdesc + (XB_BYTES >> 4)); wg_commit(); wg_wait<0>(); }
            if (c == 1) { x_project<12, 24>(x0, wA, xdesc); x_project<12, 24>(xd, wA, xdesc + (XB_BYTES >> 4)); wg_commit(); wg_wait<0>(); }
            if (c == 2) { x_project<24, 36>(x0, wA, xdesc); wg_commit(); wg_wait<0>(); }
        }
        uint32_t pk[8];
        x_pack(x0, pk);
        x_write(sb, pk, 0, isv, w, L16);
        bar_arrive<NB_AUX, 288>();
        wg_fence();
        x_project<24, 36>(xd, wA, xdesc + (XB_BYTES >> 4));
        wg_commit();
        cluster_wait();
        bar_sync<NB_O, 256>();
        if (wg == 0) TSTAMP(74, 0);
        if (WO_LOOP) {
#pragma unroll
            for (int i = 0; i < 8; i++) woA[i][0] = woA[i][1] = woA[i][2] = woA[i][3] = 0;
#pragma unroll
            for (int i = 0; i < 4; i++) woB[i][0] = woB[i][1] = woB[i][2] = woB[i][3] = 0;
        } else load_wo(sb, w, L16, woA, woB);
    }
    int s = 0;
#pragma unroll 1
    while (true) {
        const uint32_t par = s & 1;
        const uint32_t kx = sb + S_KX + par * 4096;
        asm volatile("" : "+r"(L16));
        uint32_t pk[8];
        if (wg == 0) { wg_wait<0>(); x_pack(xd, pk); x_write(sb, pk, s + 1, isv, w, L16); }
        float c0[4], c1[4];
        uint32_t k0[4], k1[4];
        {
            const uint32_t a = sb + S_MEM + L16;
            constexpr int CH = 18 / NCH;
            uint32_t b[3][4];
            bool ready = true;
            mbar_wait(sb + B_M, par);
            ldsm4(b[0], a);
            ldsm4(b[1], a + 512);
            if (wg == 1) { wg_wait<0>(); x_pack(xd, pk); }
            bar_arrive<NB_GO, 288>();
#pragma unroll
            for (int i = 0; i < 18; i++) {
                if ((i + 4) % CH == 0 && i + 4 < 18) ready = mbar_test(sb + B_M + ((i + 4) / CH) * 8, par);
                if ((i + 2) % CH == 0 && i + 2 < 18) { if (__builtin_expect(!ready, 0)) mbar_wait(sb + B_M + ((i + 2) / CH) * 8, par); }
                if (i + 2 < 18) ldsm4(b[(i + 2) % 3], a + (i + 2) * 512);
                if (ROLE == 0 && i == 16) ldsm4(k0, kx + wq * 1024 + L16);
                if (ROLE == 0 && i == 17) ldsm4(k1, kx + wq * 1024 + 512 + L16);
                if (i == 0) { mma16z(c0, wA[0], b[0][0], b[0][1]); mma16z(c1, wA[1], b[0][2], b[0][3]); }
                else { mma16(c0, wA[2 * i], b[i % 3][0], b[i % 3][1]); mma16(c1, wA[2 * i + 1], b[i % 3][2], b[i % 3][3]); }
            }
        }
        const uint32_t p0 = pack_bf16(c0[0] + c1[0], c0[1] + c1[1]), p1 = pack_bf16(c0[2] + c1[2], c0[3] + c1[3]);
        if (!isv) {
            stsm2t(sb + S_QM + w * 256 + L16, p0, p1);
            bar_sync<NB_QK, 384>();
            if (ROLE == 0) {
                uint32_t q0[4], q1[4];
                ldsm4(q0, sb + S_QM + L16);
                ldsm4(q1, sb + S_QM + 512 + L16);
                mem_scores(sb, peerA, peerB, S_SP + j * 128 + wq * 256 + (L16 >> 2), q0, q1, k0, k1);
                mbar_arrive_if0(sb + B_S, L16);
            } else {
                if (s + 2 < XLIM) mbar_wait(sb + B_X + par * 8, ((s + 2) >> 1) & 1);
                x_write(sb, pk, s + 1, isv, w, L16);
                if (wq != 0) {
                    const int rt = (wq == 3) ? 0 : 1;
                    const uint32_t qa = sb + S_QX + par * 4096 + rt * 2048 + (L16 & 0x80) * 8 + (L16 & 0x170);
                    const uint32_t kb0 = (wq == 2 ? kx + 2048 : sb + S_KM) + L16;
                    const uint32_t kb1 = (wq == 2 ? kx + 3072 : kx) + L16;
                    const uint32_t kb2 = kx + 1024 + L16;
                    float a0[4], a1[4], a2[4];
#pragma unroll
                    for (int hf = 0; hf < 2; hf++) {
                        uint32_t qa0[4], qa1[4], b[4];
                        ldsm4(qa0, qa + hf * 512);
                        ldsm4(qa1, qa + hf * 512 + 128);
                        ldsm4(b, kb0 + hf * 512);
                        if (hf == 0) mma16z(a0, qa0, b[0], b[1]); else mma16(a0, qa0, b[0], b[1]);
                        mma16(a0, qa1, b[2], b[3]);
                        ldsm4(b, kb1 + hf * 512);
                        if (hf == 0) mma16z(a1, qa0, b[0], b[1]); else mma16(a1, qa0, b[0], b[1]);
                        mma16(a1, qa1, b[2], b[3]);
                        ldsm4(b, kb2 + hf * 512);
                        if (hf == 0) mma16z(a2, qa0, b[0], b[1]); else mma16(a2, qa0, b[0], b[1]);
                        mma16(a2, qa1, b[2], b[3]);
                    }
                    mbar_wait(sb + B_S, par);
                    const uint32_t dst = peerB + S_SX + par * 5120 + j * 128 + rt * 2560 + (L16 >> 2);
                    const uint32_t bar = peerB + B_SX + par * 8;
                    const uint32_t T0 = (wq == 2 ? 2 : 4) * 256, T1 = (wq == 2 ? 3 : 0) * 256;
                    st_async32(dst + T0, pack_f16_sat(a0[0], a0[1]), bar);
                    st_async32(dst + 1280 + T0, pack_f16_sat(a0[2], a0[3]), bar);
                    if (wq != 2) st_async32(dst + T1, pack_f16_sat(a1[0], a1[1]), bar);
                    st_async32(dst + 1280 + T1, pack_f16_sat(a1[2], a1[3]), bar);
                    if (wq == 1) st_async32(dst + 256, pack_f16_sat(a2[0], a2[1]), bar);
                    if (wq != 2) st_async32(dst + 1280 + 256, pack_f16_sat(a2[2], a2[3]), bar);
                }
            }
        } else {
            const uint32_t off = S_VM + (s & 3) * 2048 + w * 256 + (L16 >> 1);
            st_async64(peerA + off, p0, p1, peerA + B_S);
            st_async64(peerB + off, p0, p1, peerB + B_S);
            sts64(sb + off, p0, p1);
            __syncwarp();
            mbar_expect_if0(sb + B_S, 160, L16);
            if (ROLE == 3) x_write(sb, pk, s + 1, isv, w, L16);
            if (PV_MODE >= 2 && ROLE == 2) { bar_arrive<NB_P, 384>(); bar_arrive<NB_PV, 288>(); }
            else {
                uint32_t pva[3][4];
                x_pv_load(sb, s + 2, w, L16, pva);
                bar_sync<NB_P, 384>();
                x_pv_run(sb, s, pva, pk);
                if (PV_MODE == 2) x_pv_load(sb, s + 2, wq, L16, pva);
                x_pv_store(sb, s, w, L16, pk);
                if (PV_MODE == 2) { x_pv_run(sb, s, pva, pk); x_pv_store(sb, s, wq, L16, pk); }
                bar_arrive<NB_PV, 288>();
            }
            if (ROLE == 3 && s + 2 < XLIM) mbar_wait(sb + B_X + par * 8, ((s + 2) >> 1) & 1);
        }
        if (WO_LOOP == 0 && s == NSEG - 1) break;
        if (WO_LOOP && ((s + 1) & (NSEG - 1)) <= 1) {
            if (s) break;
            load_wo(sb, w, L16, woA, woB);
        }
        if (wg == 0) {
            if (!isv) mbar_wait(sb + B_VX + par * 8, (s >> 1) & 1);
            uint32_t va[4][4];
            const uint32_t vx = sb + S_VX + (s & 3) * 8192 + wq * 2048 + L16;
            const uint32_t vm = sb + S_VM + (s & 3) * 2048 + wq * 512 + (L16 >> 1);
            lds128(va[0], vx);
            lds128(va[2], vx + 1024);
            mbar_wait(sb + B_S, par);
            __half2 hs[5];
            load_scores(sb + S_SP + L16, hs);
            float ev[10];
            softmax_exp(hs, ev);
            lds128(va[1], vx + 512);
            lds128(va[3], vx + 1536);
            uint32_t p[5];
#pragma unroll
            for (int i = 0; i < 5; i++) p[i] = pack_bf16(ev[2 * i], ev[2 * i + 1]);
            uint32_t vm0[2], vm1[2];
            const uint32_t ones[4] = {ONES, ONES, ONES, ONES};
            float sum[4], o0[4], o1[4];
            mma16z(o0, va[0], p[0], p[1]);
            mma16z(o1, va[2], p[0], p[1]);
            mma16z(sum, ones, p[0], p[1]);
            lds64(vm0, vm);
            lds64(vm1, vm + 256);
            mma16(o0, va[1], p[2], p[3]);
            mma16(o1, va[3], p[2], p[3]);
            mma16(sum, ones, p[2], p[3]);
            mma8(o0, vm0[0], vm0[1], p[4]);
            mma8(o1, vm1[0], vm1[1], p[4]);
            mma8(sum, ONES, ONES, p[4]);
            stsm4t(sb + S_OM + wq * 512 + L16, pack_bf16(o0[0], o0[1]), pack_bf16(o0[2], o0[3]), pack_bf16(o1[0], o1[1]), pack_bf16(o1[2], o1[3]));
            sts64(sb + S_SUM + wq * 256 + (L16 >> 1), __float_as_uint(sum[0]), __float_as_uint(sum[1]));
        }
        bar_sync<NB_O, 256>();
        {
            float a0[4], a1[4], e[4];
            float2 sc;
            float sr, r0, r1, rr;
#pragma unroll
            for (int i = 0; i < 4; i++) {
                uint32_t b[4];
                ldsm4(b, sb + S_OM + i * 512 + L16);
                if (i == 0) {
                    mma16z(a0, woA[0], b[0], b[1]); mma16z(a1, woA[1], b[2], b[3]);
                    mma_sp<0>(e, b, woB[0]);
                } else {
                    if (i == 1) { sc = lds64f(sb + S_SUM + (L16 >> 1)); sr = lds32f(sb + S_SUM + ((L16 >> 4) & 0x1C)); }
                    const uint32_t z = __float_as_uint(a0[0]) & zero;
                    mma16(a0, woA[2 * i], b[0], b[1]); mma16(a1, woA[2 * i + 1], b[2], b[3]);
                    mma_sp<1>(e, b, woB[i]);
                    if (i == RCP_AT) {
                        r0 = rcp(__uint_as_float(__float_as_uint(sc.x) | z));
                        r1 = rcp(__uint_as_float(__float_as_uint(sc.y) | z));
                        rr = rcp(__uint_as_float(__float_as_uint(sr) | z));
                    }
                }
            }
            asm volatile("" : "+r"(L16));
            char* const rslot = acc + (slot_off(s + 1) + j * 64 + w * 4096) + lane_off(L16);
            asm volatile("red.relaxed.gpu.global.add.noftz.v4.bf16x2 [%0], {%1,%2,%3,%4};"
                         ::"l"(rslot), "r"(pack_bf16((a0[0] + a1[0]) * r0, (a0[1] + a1[1]) * r1)), "r"(pack_bf16((a0[2] + a1[2]) * r0, (a0[3] + a1[3]) * r1)),
                           "r"(pack_bf16((e[0] + e[2]) * rr, (e[1] + e[3]) * rr)), "r"(0x3F80u) : "memory");
        }
        bar_arrive<NB_RED, 384>();
        if (wg == 0) {
            if (PV_MODE == 3 && isv) bar_arrive<NB_P2, 384>();
            bar_sync<NB_X, 256>();
            wg_fence();
            x_project<0, HAND_AT>(xd, wA, xdesc + par * (XB_BYTES >> 4));
            bar_arrive<NB_L, 256>();
            x_project<HAND_AT, 36>(xd, wA, xdesc + par * (XB_BYTES >> 4));
        } else {
            bar_arrive<NB_X, 256>();
            if (PV_MODE == 3 && isv) {
                uint32_t pva[3][4];
                asm volatile("" : "+r"(L16));
                x_pv_load(sb, s + 3, wq, L16, pva);
                bar_sync<NB_P2, 384>();
                x_pv_run(sb, s + 1, pva, pk);
                x_pv_store(sb, s + 1, wq, L16, pk);
            }
            bar_sync<NB_L, 256>();
            wg_fence();
            x_project<0, 36>(xd, wA, xdesc + par * (XB_BYTES >> 4));
        }
        wg_commit();
        s++;
    }
    if (isv) {
#pragma unroll 1
        for (int seg = NSEG - 2; seg < NSEG; seg++) {
            uint32_t pva[3][4], pk[8];
            x_pv_load(sb, seg, w, L16, pva);
            bar_sync<NB_RED, 384>();
            x_pv_run(sb, seg, pva, pk);
            x_pv_store(sb, seg, w, L16, pk);
            bar_arrive<NB_QK, 384>();
        }
    }
}

template <bool isv>
__device__ __forceinline__ void chain_aux(const uint32_t sb, const uint32_t lane16, const int wq, const uint32_t j, const uint32_t h,
                                          const uint32_t peerA, const uint32_t peerB, const CUtensorMap* tmWo, const CUtensorMap* tmX,
                                          char* const acc, const CUtensorMap* m0, const CUtensorMap* m1) {
    const int t = wq * 32 + (lane16 >> 4);
    cluster_arrive();
    {
        for (int c2 = 0; c2 < 3; c2++) mbar_arrive_if0(sb + B_M + c2 * 8, lane16);
        if (wq == 0) {
            if (PACE) {
                mbar_wait(sb + B_W, 0);
                if (t == 0) {
                    mbar_expect(sb + B_W + 16, 49152);
                    tma2d_once(sb + s_w(2), m0, h * 128 + (isv ? 0 : 64 * j), 384, sb + B_W + 16);
                    tma2d_once(sb + s_w(2) + 24576, m1, h * 128 + (isv ? 64 : 64 * j), 384, sb + B_W + 16);
                }
                __syncwarp();
            }
            bar_sync<NB_PRO, 288>();
            if (t == 0) {
                fence_async_smem();
                mbar_expect(sb + B_WO, 49152);
                for (int b = 0; b < 3; b++) tma2d(sb + S_WO + b * 16384, tmWo, 192 * j + 64 * b, h * 128, sb + B_WO);
            }
        } else if (wq == 3) {
            bulk_wait0();
            asm volatile("fence.proxy.async.global;" ::: "memory");
            __syncwarp();
            if (lane16 == 0) {
                if (h == 0) asm volatile("red.relaxed.gpu.global.add.u32 [%0], 1;" ::"l"(&g_zero_cnt) : "memory");
            }
            __syncwarp();
            unsigned c = 0;
            while (ld_acquire(&g_zero_cnt) < 3 && ++c < SPIN_LIM) __nanosleep(100);
            TSTAMP(76, 0);
            if (DEP_LATE) mbar_wait(sb + B_W + 16, 0);
            asm volatile("griddepcontrol.launch_dependents;" ::: "memory");
        }
        __syncwarp();
        cluster_wait();
        if (wq == 0) bar_sync<NB_AUX, 288>();
        if (t == 0) {
            fence_async_smem();
            if (!isv) mbar_expect(sb + B_VX, 8192);
            else {
                bulk_s2c(peerA + S_VX, sb + S_VX, 8192, peerA + B_VX);
                bulk_s2c(peerB + S_VX, sb + S_VX, 8192, peerB + B_VX);
            }
            mbar_expect(sb + B_X, XB_BYTES);
            tma3d(sb + S_XB, tmX, 0, 64, 0, sb + B_X);
        }
        __syncwarp();
    }
    TSTAMP(0, 0);
    uint32_t L16 = lane16;
    const char* slot = acc + wq * 4096 + lane_off(L16);
    float ev[10];
    int s = 0;
#pragma unroll 1
    while (true) {
        const uint32_t par = s & 1;
        asm volatile("" : "+r"(L16));
        if (!isv) {
            if (wq == 0) {
                bar_sync<NB_QK, 384>();
                uint32_t q0[4], q1[4], k0[4], k1[4];
                ldsm4(q0, sb + S_QM + L16);
                ldsm4(k0, sb + S_KM + L16);
                ldsm4(q1, sb + S_QM + 512 + L16);
                ldsm4(k1, sb + S_KM + 512 + L16);
                mem_scores(sb, peerA, peerB, S_SP + j * 128 + 1024 + (L16 >> 2), q0, q1, k0, k1);
                mbar_expect_if0(sb + B_S, 640 + 2048, L16);
            } else if (wq == 3) {
                bar_sync<NB_GO, 288>();
                const unsigned t = post_time(s, L16);
                bar_sync<NB_QK, 384>();
                if (j == 0 && s < NSEG - 1) {
                    if (LOOK_NS) __nanosleep(LOOK_NS);
                    plan_look(sb, s, L16, t);
                }
            } else {
                bar_arrive<NB_QK, 384>();
                if (wq == 2) {
                    if (L16 == 0) {
                        if (s + 3 < XLIM) mbar_expect(sb + B_X + (par ^ 1) * 8, XB_BYTES);
                        mbar_expect(sb + B_VX + (par ^ 1) * 8, 8192);
                        mbar_expect(sb + B_T, 4);
                        if (s == 2 && h == 0 && j == 0) g_zero_cnt = 0;
                        if (REFRESH && s + REFRESH == 2 * h) asm volatile("cp.async.bulk.prefetch.L2.global [%0], %1;" ::"l"(acc + h * 32768 + j * 16384), "r"(16384) : "memory");
                    }
                } else if (s + 3 < XLIM && j == 1) {
                    mbar_wait(sb + B_S, par);
                    if (XTMA_NS) __nanosleep(XTMA_NS);
                    if (L16 == 0) tma3d_mc(sb + S_XB + (par ^ 1) * XB_BYTES, tmX, 0, (s + 3) * SEG, 0, sb + B_X + (par ^ 1) * 8, 7);
                }
                __syncwarp();
            }
        } else {
            if (wq == 3) {
                bar_sync<NB_GO, 288>();
                post_time(s, L16);
            } else if (L16 == 0) {
                if (wq == 0) {
                    if (s >= 1) vx_fetch(sb, s, h);
                } else if (wq == 1) {
                    if (s >= 3) ox_publish(s - 3, h);
                } else {
                    mbar_expect(sb + B_SX + par * 8, 3584);
                    mbar_expect(sb + B_T, 4);
                    if (s + 3 < XLIM) mbar_expect(sb + B_X + (par ^ 1) * 8, XB_BYTES);
                }
            }
            __syncwarp();
            if (s >= 1) mbar_wait(sb + B_SX + (par ^ 1) * 8, ((s - 1) >> 1) & 1);
            if (PV_MODE != 3) fence_async_smem();
            bar_sync<NB_P, 384>();
            if (VX_AT == 0 && wq == 0) { if (L16 == 0 && s + 1 < NSEG) vx_store(sb, s + 1, h); __syncwarp(); }
            x_scores(sb, s + 1, wq, L16, ev);
            if (VX_AT == 1 && wq == 0) { if (L16 == 0 && s + 1 < NSEG) vx_store(sb, s + 1, h); __syncwarp(); }
            if (wq == 1) {
                bar_sync<NB_PV, 288>();
                if (L16 == 0 && s >= 2) ox_store(sb, s - 2, h);
                __syncwarp();
            }
            x_probs(sb, s + 1, wq, L16, ev);
            if (PV_MODE == 3 && s < NSEG - 1) { fence_async_smem(); bar_arrive<NB_P2, 384>(); }
        }
        if (s == NSEG - 1) break;
        mbar_wait(sb + B_T, par);
        const unsigned tgt = __float_as_uint(lds32f(sb + S_TGT));
        bar_sync<NB_RED, 384>();
        asm volatile("" : "+r"(L16));
        slot += par ? 32768 - 512 : 512;
        while ((int)(gtime() - tgt) < 0) {}
        uint4 v[6];
        look(v, slot);
        s++;
        const uint32_t ma = sb + S_MEM + wq * 384 + L16;
        unsigned c = 0;
        constexpr int CW = 6 / NCH;
        int done = NCH;
#pragma unroll
        for (int k = 0; k < NCH; k++) {
            uint32_t bad = 0;
#pragma unroll
            for (int i = CW * k; i < CW * k + CW; i++) { stsm2t(ma + i * 1536, v[i].x, v[i].y); stsm1(ma + i * 1536 + 256, v[i].z); bad |= v[i].w ^ FULL_COUNT; }
            const bool again = __any_sync(0xffffffffu, bad != 0);
            mbar_arrive_if0(sb + B_M + k * 8, L16 | (uint32_t)again);
            if (again) { done = k; break; }
        }
        if (done < NCH) {
            uint32_t bad;
            do {
                look(v, slot);
                bad = 0;
#pragma unroll
                for (int i = 0; i < 6; i++) { stsm2t(ma + i * 1536, v[i].x, v[i].y); stsm1(ma + i * 1536 + 256, v[i].z); bad |= v[i].w ^ FULL_COUNT; }
            } while (++c < SPIN_LIM && __any_sync(0xffffffffu, bad != 0));
            __syncwarp();
#pragma unroll
            for (int k = 0; k < NCH; k++) if (k >= done) mbar_arrive_if0(sb + B_M + k * 8, L16);
        }
        TSTAMP(s, c | t_pack);
    }
    if (!isv) {
        mbar_wait(sb + B_VX + 8, ((NSEG - 1) >> 1) & 1);
        mbar_wait(sb + B_S, 1);
    } else {
        fence_async_smem();
        bar_arrive<NB_RED, 384>();
        mbar_wait(sb + B_S, 1);
        mbar_wait(sb + B_SX + 8, ((NSEG - 1) >> 1) & 1);
        x_scores(sb, NSEG - 1, wq, L16, ev);
        bar_sync<NB_QK, 384>();
        if (wq == 2 && L16 == 0) ox_store(sb, NSEG - 2, h);
        if (wq == 1 && L16 == 0) ox_publish(NSEG - 3, h);
        __syncwarp();
        x_probs(sb, NSEG - 1, wq, L16, ev);
        fence_async_smem();
        bar_arrive<NB_RED, 384>();
        if (wq == 2) { if (L16 == 0) ox_publish(NSEG - 2, h); __syncwarp(); bar_arrive<NB_QK, 384>(); }
        else bar_sync<NB_QK, 384>();
        if (wq == 3 && L16 == 0) { ox_store(sb, NSEG - 1, h); ox_publish(NSEG - 1, h); }
    }
}

__global__ void __launch_bounds__(384, 1)
chain_kernel(const __grid_constant__ CUtensorMap tmWq, const __grid_constant__ CUtensorMap tmWk, const __grid_constant__ CUtensorMap tmWv,
             const __grid_constant__ CUtensorMap tmWo, const __grid_constant__ CUtensorMap tmX, const bf16* __restrict__ mem0, char* const acc) {
    extern __shared__ __align__(1024) uint8_t smem[];
    const uint32_t sb = smem_u32(smem);
    const int tid = threadIdx.x;
    const uint32_t L16 = __shfl_sync(0xffffffffu, (tid & 31) * 16, tid & 31);
    const int w = __shfl_sync(0xffffffffu, tid >> 5, 0), wg = w >> 2, wq = w & 3;
    uint32_t j, h;
    asm("mov.u32 %0, %%cluster_ctarank;" : "=r"(j));
    asm("mov.u32 %0, %%clusterid.x;" : "=r"(h));
    const bool isv = (j == 2);
    const uint32_t peerA = mapa(sb, isv ? 0 : (j ^ 1)), peerB = mapa(sb, isv ? 1 : 2);
    if (DESCPF && w == 10 && L16 < 64) {
        const CUtensorMap* m = L16 == 0 ? &tmX : L16 == 16 ? (isv ? &tmWv : &tmWq) : L16 == 32 ? &tmWk : &tmWo;
        asm volatile("prefetch.tensormap [%0];" ::"l"(m) : "memory");
    }
    if (w == 11) {
        sts128(sb + S_ZERO + L16, 0, 0, 0, 0);
        sts128(sb + S_ZERO + 512 + L16, 0, 0, 0, 0);
        fence_async_smem();
        __syncwarp();
        const int i = L16 >> 4, kb = j * 11 + i;
        if (i < 11 && kb < 32) bulk_s2g(acc + h * 32768 + kb * 1024, sb + S_ZERO, 1024);
        if (i == 11) bulk_s2g(g_time + blockIdx.x * 64, sb + S_ZERO, 256);
        if (i == 12 && blockIdx.x == 0) bulk_s2g(g_flag, sb + S_ZERO, 1024);
        bulk_commit();
    }
    if (tid == 256) {
        for (int c = 0; c < 3; c++) { mbar_init(sb + B_W + 8 * c, 1); mbar_init(sb + B_M + 8 * c, 4); }
        mbar_init(sb + B_WO, 1); mbar_init(sb + B_T, 1);
        mbar_init(sb + B_X, 1); mbar_init(sb + B_X + 8, 1);
        mbar_init(sb + B_S, isv ? 8 : 5);
        mbar_init(sb + B_VX, 1); mbar_init(sb + B_VX + 8, 1);
        mbar_init(sb + B_SX, 1); mbar_init(sb + B_SX + 8, 1);
        asm volatile("fence.mbarrier_init.release.cluster;" ::: "memory");
        const CUtensorMap* m0 = isv ? &tmWv : &tmWq;
        const CUtensorMap* m1 = isv ? &tmWv : &tmWk;
        const int c0 = h * 128 + (isv ? 0 : 64 * j), c1 = h * 128 + (isv ? 64 : 64 * j);
        mbar_expect(sb + B_X, XB_BYTES);
        tma3d(sb + S_XB, &tmX, 0, 0, 0, sb + B_X);
        mbar_expect(sb + B_X + 8, XB_BYTES);
        tma3d(sb + S_XB + XB_BYTES, &tmX, 0, 32, 0, sb + B_X + 8);
#pragma unroll 1
        for (int c = 0; c < (PACE ? 2 : 3); c++) {
            mbar_expect(sb + B_W + 8 * c, 49152);
            tma2d_once(sb + s_w(c), m0, c0, c * 192, sb + B_W + 8 * c);
            tma2d_once(sb + s_w(c) + 24576, m1, c1, c * 192, sb + B_W + 8 * c);
        }
    } else if (tid < 256) {
        uint4 v0, v1, v2;
        v0 = *reinterpret_cast<const uint4*>(mem0 + (tid & 7) * DM + (tid >> 3) * 8);
        v1 = *reinterpret_cast<const uint4*>(mem0 + (tid & 7) * DM + (tid >> 3) * 8 + 256);
        if (tid < 64) v2 = *reinterpret_cast<const uint4*>(mem0 + (tid & 7) * DM + (tid >> 3) * 8 + 512);
        sts128(sb + S_MEM + tid * 16, v0.x, v0.y, v0.z, v0.w);
        sts128(sb + S_MEM + 4096 + tid * 16, v1.x, v1.y, v1.z, v1.w);
        if (tid < 64) sts128(sb + S_MEM + 8192 + tid * 16, v2.x, v2.y, v2.z, v2.w);
    }
    __syncthreads();
    if (wg == 2) {
        asm volatile("setmaxnreg.dec.sync.aligned.u32 %0;" ::"n"(REG_AUX));
        if (!isv) chain_aux<false>(sb, L16, wq, j, h, peerA, peerB, &tmWo, &tmX, acc, &tmWq, &tmWk);
        else chain_aux<true>(sb, L16, wq, j, h, peerA, peerB, &tmWo, &tmX, acc, &tmWv, &tmWv);
        __syncwarp();
        cluster_arrive(); cluster_wait();
        TSTAMP(65, 0);
    } else if (wg == 0) {
        asm volatile("setmaxnreg.inc.sync.aligned.u32 %0;" ::"n"(REG_MAIN0));
        if (!isv) chain_main<0>(sb, L16, wq, j, h, peerA, peerB, acc);
        else chain_main<2>(sb, L16, wq, j, h, peerA, peerB, acc);
        cluster_arrive(); cluster_wait();
    } else {
        asm volatile("setmaxnreg.inc.sync.aligned.u32 %0;" ::"n"(REG_MAIN1));
        if (!isv) chain_main<1>(sb, L16, wq, j, h, peerA, peerB, acc);
        else chain_main<3>(sb, L16, wq, j, h, peerA, peerB, acc);
        cluster_arrive(); cluster_wait();
    }
}

constexpr int NHELP = 36;
constexpr uint32_t H_U = 0;
constexpr uint32_t UT_PITCH = 4368;
constexpr uint32_t H_UT = 65536;
constexpr uint32_t KW_BYTES = 8320;
constexpr uint32_t H_KW = 135424;
constexpr uint32_t H_PAR = 201984;
constexpr uint32_t H_KD = 214272;
constexpr uint32_t H_IDX = 224640;
constexpr uint32_t H_STAGE = 0;
constexpr uint32_t H_RED = 196608;
constexpr uint32_t H_FIN = 212992;
constexpr uint32_t H_OWN = 214016;
constexpr uint32_t H_BAR = 229376;
constexpr uint32_t B_SMEM = H_BAR + 384;
constexpr uint32_t HB_U = H_BAR, HB_WO = H_BAR + 8, HB_EMPTY = H_BAR + 16, HB_RFULL = H_BAR + 64, HB_REMPTY = H_BAR + 80, HB_FIN = H_BAR + 96, HB_FULL = H_BAR + 128, HB_SENT = H_BAR + 320;
constexpr int RING = 8;
__device__ __align__(1024) uint4 g_part[RING * 9 * 4 * 4 * 128];

__device__ __forceinline__ float2 cmul(float2 a, float2 b) { return make_float2(fmaf(a.x, b.x, -a.y * b.y), fmaf(a.x, b.y, a.y * b.x)); }
__device__ __forceinline__ float2 csqr(float2 a) { return make_float2(fmaf(a.x, a.x, -a.y * a.y), (a.x + a.x) * a.y); }
__device__ __forceinline__ float2 cexp(float zr, float zi, float p) {
    const float m = ex2(zr * p);
    const float r = zi * p;
    const float a = (fabsf(r) < 4194304.f ? r - ((r + 12582912.f) - 12582912.f) : 0.f) * 6.283185307179586f;
    return make_float2(m * __cosf(a), m * __sinf(a));
}
__device__ __forceinline__ uint32_t pack_f16(float lo, float hi) { uint32_t r; asm("cvt.rn.f16x2.f32 %0, %1, %2;" : "=r"(r) : "f"(hi), "f"(lo)); return r; }
__device__ __forceinline__ void mma16h(float* d, const uint32_t* a, uint32_t b0, uint32_t b1) {
    asm volatile("mma.sync.aligned.m16n8k16.row.col.f32.f16.f16.f32 {%0,%1,%2,%3},{%4,%5,%6,%7},{%8,%9},{%0,%1,%2,%3};"
                 : "+f"(d[0]), "+f"(d[1]), "+f"(d[2]), "+f"(d[3]) : "r"(a[0]), "r"(a[1]), "r"(a[2]), "r"(a[3]), "r"(b0), "r"(b1));
}
__device__ __forceinline__ float bf_round(float x) { return __bfloat162float(__float2bfloat16_rn(x)); }
__device__ __forceinline__ uint32_t lds32(uint32_t a) { uint32_t v; asm volatile("ld.shared.b32 %0,[%1];" : "=r"(v) : "r"(a) : "memory"); return v; }
__device__ __forceinline__ uint32_t lds16(uint32_t a) { uint16_t v; asm volatile("ld.shared.u16 %0,[%1];" : "=h"(v) : "r"(a) : "memory"); return v; }

__device__ __forceinline__ void s4d_kernel(uint32_t par, uint32_t kd, int d, int lane, const bf16* __restrict__ logA, const bf16* __restrict__ Aim,
                                           const bf16* __restrict__ Cre, const bf16* __restrict__ Cim, const bf16* __restrict__ logdt) {
    const float dt = bf_round(expf(__bfloat162float(logdt[d])));
    float4 q[4];
    float cmax = 0.f, last = 0.f;
#pragma unroll
    for (int i = 0; i < 4; i++) {
        const int n = d * NST + i * 32 + lane;
        q[i].x = -bf_round(expf(__bfloat162float(logA[n]))) * dt * 1.4426950408889634f;
        q[i].y = __bfloat162float(Aim[n]) * dt * 0.15915494309189535f;
        q[i].z = 2.f * (__bfloat162float(Cre[n]) * dt);
        q[i].w = 2.f * (__bfloat162float(Cim[n]) * dt);
        cmax = fmaxf(cmax, fmaxf(fabsf(q[i].z), fabsf(q[i].w)));
        const float2 e = cexp(q[i].x, q[i].y, 2048.f);
        last += q[i].z * e.x - q[i].w * e.y;
        const float2 w64 = cexp(q[i].x, q[i].y, 64.f);
        sts64(par + 2048 + (i * 32 + lane) * 8, __float_as_uint(w64.x), __float_as_uint(w64.y));
    }
#pragma unroll
    for (int o = 16; o; o >>= 1) { cmax = fmaxf(cmax, __shfl_xor_sync(0xffffffffu, cmax, o)); last += __shfl_xor_sync(0xffffffffu, last, o); }
    const float cs = __uint_as_float(max(__float_as_uint(cmax) & 0x7F800000u, 0x00800000u));
    const float ci = 1.f / cs;
#pragma unroll
    for (int i = 0; i < 4; i++) sts128(par + (i * 32 + lane) * 16, __float_as_uint(q[i].x), __float_as_uint(q[i].y), __float_as_uint(q[i].z * ci), __float_as_uint(q[i].w * ci));
    __syncwarp();
    float acc[5][4];
#pragma unroll
    for (int i = 0; i < 5; i++) acc[i][0] = acc[i][1] = acc[i][2] = acc[i][3] = 0.f;
    const float g = (float)(lane >> 2);
#pragma unroll 2
    for (int ks = 0; ks < 16; ks++) {
        uint32_t A[5][4], B[4][2];
#pragma unroll
        for (int hf = 0; hf < 2; hf++) {
            uint32_t r[4];
            const int n = ks * 8 + hf * 4 + (lane & 3);
            lds128(r, par + n * 16);
            const float2 w64 = lds64f(par + 2048 + n * 8);
            const float2 c = make_float2(__uint_as_float(r[2]), __uint_as_float(r[3]));
            float2 y = cexp(__uint_as_float(r[0]), __uint_as_float(r[1]), g);
#pragma unroll
            for (int k = 0; k < 4; k++) {
                const float2 cy = cmul(c, y);
                B[k][hf] = pack_f16(cy.x, -cy.y);
                if (k < 3) y = csqr(y);
            }
            const float2 xl = cmul(y, w64);
            float2 x0 = cmul(xl, w64), x1 = cmul(x0, w64);
            A[0][2 * hf] = pack_f16(y.x, y.y);
            A[0][2 * hf + 1] = pack_f16(xl.x, xl.y);
#pragma unroll
            for (int k = 0; k < 4; k++) {
                A[k + 1][2 * hf] = pack_f16(x0.x, x0.y);
                A[k + 1][2 * hf + 1] = pack_f16(x1.x, x1.y);
                if (k < 3) { x0 = csqr(x0); x1 = csqr(x1); }
            }
        }
        mma16h(acc[0], A[0], B[0][0], B[0][1]);
#pragma unroll
        for (int k = 0; k < 4; k++) mma16h(acc[k + 1], A[k + 1], B[k][0], B[k][1]);
    }
    __syncwarp();
#pragma unroll
    for (int i = 0; i < 5; i++) {
        sts32(kd + i * 256 + lane * 4, pack_bf16(acc[i][0] * cs, acc[i][1] * cs));
        sts32(kd + i * 256 + 128 + lane * 4, pack_bf16(acc[i][2] * cs, acc[i][3] * cs));
    }
    if (lane == 0) sts32(kd + 1280, pack_bf16(last, 0.f));
    __syncwarp();
}
__device__ __forceinline__ void s4d_expand(uint32_t kw, uint32_t kd, uint32_t idx, int lane) {
    if (lane < 16) sts32(kw + lane * 4, 0);
#pragma unroll 4
    for (int it = 0; it < 16; it++) {
        const int l = (it * 32 + lane) * 4;
        uint32_t j[2];
        lds64(j, idx + l * 2);
        const uint32_t jm = l ? lds16(idx + l * 2 - 2) : 1282;
        const uint32_t vm = lds16(kd + jm), v0 = lds16(kd + (j[0] & 0xFFFF)), v1 = lds16(kd + (j[0] >> 16)), v2 = lds16(kd + (j[1] & 0xFFFF)), v3 = lds16(kd + (j[1] >> 16));
        sts128(kw + 64 + l * 4, v0 | (vm << 16), v1 | (v0 << 16), v2 | (v1 << 16), v3 | (v2 << 16));
    }
    __syncwarp();
}

__device__ __forceinline__ void s4d_conv(uint32_t ut, uint32_t kw, int lane) {
    float acc[16][4];
#pragma unroll
    for (int i = 0; i < 16; i++) acc[i][0] = acc[i][1] = acc[i][2] = acc[i][3] = 0.f;
    const uint32_t ka = kw + 64 + ((lane >> 2) - 2 * (lane & 3)) * 4;
    const uint32_t ua = ut + 256 + lane * 8;
#pragma unroll 1
    for (int rho = 0; rho < 8; rho++) {
        uint32_t B[16][2];
#pragma unroll
        for (int q = 0; q < 16; q++) lds64(B[q], ua + q * 256 - rho * 32);
#pragma unroll
        for (int m = 0; m < 16; m++) {
            uint32_t A[4];
            const uint32_t x = ka + m * 512 + rho * 64;
            A[0] = lds32(x); A[1] = lds32(x + 32); A[2] = lds32(x - 32); A[3] = A[0];
#pragma unroll
            for (int i = m; i < 16; i++) mma16(acc[i], A, B[i - m][0], B[i - m][1]);
        }
    }
    __syncwarp();
    const uint32_t ya = ut + 256 + (lane & 7) * 32 + ((lane >> 3) & 1) * 16 + (lane >> 4) * 256;
#pragma unroll
    for (int i = 0; i < 16; i += 2)
        stsm4t(ya + i * 256, pack_bf16(acc[i][0], acc[i][1]), pack_bf16(acc[i][2], acc[i][3]),
               pack_bf16(acc[i + 1][0], acc[i + 1][1]), pack_bf16(acc[i + 1][2], acc[i + 1][3]));
}

__global__ void __launch_bounds__(384, 1)
helper_kernel(const __grid_constant__ CUtensorMap tmU, const __grid_constant__ CUtensorMap tmY, const __grid_constant__ CUtensorMap tmWo,
              const bf16* __restrict__ logA, const bf16* __restrict__ Aim, const bf16* __restrict__ Cre, const bf16* __restrict__ Cim,
              const bf16* __restrict__ logdt, const bf16* __restrict__ Dskip, bf16* __restrict__ out) {
    extern __shared__ __align__(1024) uint8_t smem[];
    const uint32_t sb = smem_u32(smem);
    const int tid = threadIdx.x, lane = tid & 31;
    const int w = __shfl_sync(0xffffffffu, tid >> 5, 0);
    const int d0 = blockIdx.x * 16;
    HSTAMP(0);
    if (tid == 0) {
        mbar_init(sb + HB_U, 1); mbar_init(sb + HB_WO, 1);
        for (int i = 0; i < 6; i++) mbar_init(sb + HB_EMPTY + 8 * i, 4);
        for (int i = 0; i < 24; i++) mbar_init(sb + HB_FULL + 8 * i, 1);
        for (int i = 0; i < 2; i++) { mbar_init(sb + HB_RFULL + 8 * i, 4); mbar_init(sb + HB_REMPTY + 8 * i, 4); }
        for (int i = 0; i < 4; i++) { mbar_init(sb + HB_FIN + 8 * i, 2); mbar_init(sb + HB_SENT + 8 * i, 4); }
        fence_async_smem();
    }
    __syncthreads();
    if (tid == 352) {
        mbar_expect(sb + HB_U, 65536);
        for (int i = 0; i < 8; i++) { if (EVF & 2) tma2d_once(sb + H_U + i * 8192, &tmU, d0, i * 256, sb + HB_U); else tma2d(sb + H_U + i * 8192, &tmU, d0, i * 256, sb + HB_U); if (U_NS) __nanosleep(U_NS); }
    }
    __syncwarp();
    const int m = lane >> 3, r = lane & 7;
    const uint32_t kw = sb + H_KW + w * KW_BYTES;
    if (w < 8) {
        s4d_kernel(kw, sb + H_KD + w * 1296, d0 + w, lane, logA, Aim, Cre, Cim, logdt);
        bar_sync<1, 384>();
        HSTAMP(1);
        if (w >= 4) {
            uint4* dst = g_part + ((blockIdx.x % 9) * 16 + blockIdx.x / 9) * 128 + (tid & 127);
#pragma unroll 4
            for (int i = 0; i < RING * 4; i++) if ((i & 3) != blockIdx.x / 9) dst[(i >> 2) * (9 * 16 * 128) + (i & 3) * 512] = make_uint4(0, 0, 0, 0);
        }
        s4d_expand(kw, sb + H_KD + w * 1296, sb + H_IDX, lane);
        bar_arrive<2, 384>();
        s4d_conv(sb + H_UT + w * UT_PITCH, kw, lane);
        bar_sync<3, 384>();
        s4d_expand(kw, sb + H_KD + w * 1296, sb + H_IDX, lane);
        s4d_conv(sb + H_UT + (8 + w) * UT_PITCH, kw, lane);
    } else {
        for (int l = tid - 256; l < SEQ; l += 128) {
            const int jx = l < 128 ? l : (int)__bfloat16_as_ushort(__float2bfloat16_rn((float)l)) - (133 << 7);
            asm volatile("st.shared.u16 [%0], %1;" ::"r"(sb + H_IDX + l * 2), "h"((unsigned short)(jx * 2)) : "memory");
        }
        for (int i = tid - 256; i < 256; i += 128) sts128(sb + H_UT + (i >> 4) * UT_PITCH + (i & 15) * 16, 0, 0, 0, 0);
        mbar_wait(sb + HB_U, 0);
        const uint32_t src = sb + H_U + ((m & 1) * 8 + r) * 32 + (((m >> 1) ^ (r >> 2)) << 4);
        const uint32_t dst = sb + H_UT + 256 + (lane >> 2) * UT_PITCH + (lane & 3) * 8;
#pragma unroll 4
        for (int grp = w - 8; grp < 128; grp += 4) {
            uint32_t v[4];
            ldsm4t(v, src + grp * 512);
            sts64(dst + grp * 32, v[0], v[1]);
            sts64(dst + 8 * UT_PITCH + grp * 32, v[2], v[3]);
        }
        bar_arrive<1, 384>();
        bar_sync<2, 384>();
#pragma unroll 1
        for (int c = w - 8; c < 8; c += 4) s4d_kernel(sb + H_PAR + (w - 8) * 3072, sb + H_KD + c * 1296, d0 + 8 + c, lane, logA, Aim, Cre, Cim, logdt);
        bar_arrive<3, 384>();
    }
    __syncthreads();
    HSTAMP(2);
    const int cc = blockIdx.x % 9, kq = blockIdx.x / 9;
    {
        const __nv_bfloat162 D0 = *reinterpret_cast<const __nv_bfloat162*>(Dskip + d0 + (lane & 3) * 2);
        const __nv_bfloat162 D1 = *reinterpret_cast<const __nv_bfloat162*>(Dskip + d0 + 8 + (lane & 3) * 2);
        const uint32_t ua = sb + H_U + ((m & 1) * 8 + r) * 32 + (((m >> 1) ^ (r >> 2)) << 4);
        const uint32_t ya = sb + H_UT + 256 + ((m >> 1) * 8 + r) * UT_PITCH + (m & 1) * 16;
        for (int grp = w; grp < 128; grp += 12) {
            uint32_t u[4], y[4];
            ldsm4(u, ua + grp * 512);
            ldsm4t(y, ya + grp * 32);
#pragma unroll
            for (int i = 0; i < 4; i++) {
                const __nv_bfloat162 o = __hadd2_rn(*reinterpret_cast<__nv_bfloat162*>(&y[i]), __hmul2_rn(*reinterpret_cast<__nv_bfloat162*>(&u[i]), i < 2 ? D0 : D1));
                y[i] = *reinterpret_cast<const uint32_t*>(&o);
            }
            stsm4(ua + grp * 512, y[0], y[1], y[2], y[3]);
        }
        fence_async_smem();
        __syncthreads();
        if (tid == 0) {
            mbar_expect(sb + HB_WO, 131072);
            for (int i = 0; i < 8; i++) {
                if (YST) asm volatile("cp.async.bulk.tensor.2d.global.shared::cta.bulk_group [%0, {%1,%2}], [%3];" ::"l"(&tmY), "r"(DM + d0), "r"(i * 256), "r"(sb + H_U + i * 8192) : "memory");
                if (EVF & 2) tma2d_once(sb + 65536 + i * 16384, &tmWo, cc * 64, (kq * 8 + i) * 128, sb + HB_WO);
                else tma2d(sb + 65536 + i * 16384, &tmWo, cc * 64, (kq * 8 + i) * 128, sb + HB_WO);
                if (TRICKLE_NS) __nanosleep(TRICKLE_NS);
            }
            bulk_commit();
            asm volatile("cp.async.bulk.wait_group.read 0;" ::: "memory");
        }
    }
    __syncwarp();
    if (w < 8) {
        asm volatile("setmaxnreg.inc.sync.aligned.u32 208;");
        const int wg = w >> 2;
        uint32_t wo[32][4];
        mbar_wait_long(sb + HB_WO, 0);
        const uint32_t a = sb + 65536 + wg * 65536 + ((m >> 1) * 8 + r) * 128 + (((2 * (w & 3) + (m & 1)) ^ r) << 4);
#pragma unroll
        for (int i = 0; i < 32; i++) ldsm4t(wo[i], a + i * 2048);
        __syncthreads();
        HSTAMP(3);
        const int t = tid & 127;
        int st = 0, ph = 0;
#pragma unroll 1
        for (int s = 0; s < NSEG; s++) {
            const uint32_t desc = (((sb + H_STAGE + st * 65536 + wg * 32768) & 0x3FFFF) >> 4) | (8u << 16);
            float d[16];
#pragma unroll
            for (int q = 0; q < HSPLIT; q++) {
                mbar_wait_long(sb + HB_FULL + ((st * 2 + wg) * 4 + q) * 8, ph);
                wg_fence();
#pragma unroll
                for (int i = q * (32 / HSPLIT); i < (q + 1) * (32 / HSPLIT); i++) {
                    if (i == 0) wg_rs_n32<0, 16, 1>(d, wo[i], desc); else wg_rs_n32<1, 16, 1>(d, wo[i], desc + i * 64);
                }
                wg_commit();
            }
            wg_wait<0>();
            mbar_arrive_if0(sb + HB_EMPTY + (st * 2 + wg) * 8, lane);
            if (++st == 3) { st = 0; ph ^= 1; }
            const uint32_t ra = sb + H_RED + (s & 1) * 8192 + t * 16;
            if (wg == 0) {
                if (s >= 2) mbar_wait_long(sb + HB_REMPTY + (s & 1) * 8, ((s - 2) >> 1) & 1);
#pragma unroll
                for (int i = 0; i < 4; i++) sts128(ra + i * 2048, __float_as_uint(d[4 * i]), __float_as_uint(d[4 * i + 1]), __float_as_uint(d[4 * i + 2]), __float_as_uint(d[4 * i + 3]));
                __syncwarp();
                mbar_arrive_if0(sb + HB_RFULL + (s & 1) * 8, lane);
            } else {
                mbar_wait_long(sb + HB_RFULL + (s & 1) * 8, (s >> 1) & 1);
                if (s >= 4) mbar_wait_long(sb + HB_FIN + (s & 3) * 8, ((s - 4) >> 2) & 1);
                uint4* dst = g_part + (((s % RING) * 9 + cc) * 16 + kq) * 128 + t;
#pragma unroll
                for (int i = 0; i < 4; i++) {
                    uint32_t p[4];
                    lds128(p, ra + i * 2048);
#pragma unroll
                    for (int k = 0; k < 4; k++) p[k] = ((__float_as_uint(__uint_as_float(p[k]) + d[4 * i + k]) + 64) & ~127u) | (s + 1);
                    if (i != kq) asm volatile("st.relaxed.gpu.global.v4.u32 [%0], {%1,%2,%3,%4};" ::"l"(dst + i * 512), "r"(p[0]), "r"(p[1]), "r"(p[2]), "r"(p[3]) : "memory");
                    else sts128(sb + H_OWN + (s & 3) * 2048 + t * 16, p[0], p[1], p[2], p[3]);
                }
                __syncwarp();
                mbar_arrive_if0(sb + HB_REMPTY + (s & 1) * 8, lane);
                mbar_arrive_if0(sb + HB_SENT + (s & 3) * 8, lane);
                HSTAMP4(s);
            }
        }
        if (tid == 0) bulk_wait0();
    } else {
        asm volatile("setmaxnreg.dec.sync.aligned.u32 88;");
        __syncthreads();
        if (w == 8) {
            int st = 0, ph = 1, ready = 0;
            for (int s = 0; s < NSEG; s++) {
                unsigned c = 0;
                while (ready <= s) {
                    const unsigned f = ld_acquire(&g_flag[kq * NSEG + min(s + (lane & 3), NSEG - 1)]);
                    ready = s + __ffs(~(__ballot_sync(0xffffffffu, f >= 8) & 15)) - 1;
                    if (++c >= LONG_LIM) break;
                    if (ready <= s && FLAG_NS) __nanosleep(FLAG_NS);
                }
                __syncwarp();
                if (lane == 0) {
                    asm volatile("fence.proxy.async.global;" ::: "memory");
                    HSTAMP3(s);
                    if (PACE_H >= 0 && s > 0 && s < NSEG - 3) {
                        const int pst = st ? st - 1 : 2;
                        mbar_wait_long(sb + HB_FULL + ((pst * 2 + 1) * 4 + (PACE_H < 0 ? 0 : PACE_H)) * 8, st ? ph ^ 1 : ph);
                    }
                    mbar_wait_long(sb + HB_EMPTY + st * 16, ph);
                    mbar_wait_long(sb + HB_EMPTY + st * 16 + 8, ph);
#pragma unroll
                    for (int k = 0; k < 2 * HSPLIT; k++) {
                        const int g = k & 1, q = k >> 1;
                        constexpr uint32_t bytes = 32768 / HSPLIT;
                        const uint32_t bar = sb + HB_FULL + ((st * 2 + g) * 4 + q) * 8;
                        mbar_expect(bar, bytes);
                        if (EVF & 4) asm volatile("cp.async.bulk.shared::cluster.global.mbarrier::complete_tx::bytes.L2::cache_hint [%0], [%1], %2, [%3], %4;"
                                     ::"r"(sb + H_STAGE + st * 65536 + g * 32768 + q * bytes), "l"(g_ox + (s * NH + kq * 8 + g * 4) * 512 + q * (bytes / 16)), "r"(bytes), "r"(bar), "l"(evict_first()) : "memory");
                        else
                        asm volatile("cp.async.bulk.shared::cluster.global.mbarrier::complete_tx::bytes [%0], [%1], %2, [%3];"
                                     ::"r"(sb + H_STAGE + st * 65536 + g * 32768 + q * bytes), "l"(g_ox + (s * NH + kq * 8 + g * 4) * 512 + q * (bytes / 16)), "r"(bytes), "r"(bar) : "memory");
                    }
                }
                __syncwarp();
                if (++st == 3) { st = 0; ph ^= 1; }
            }
        } else if (w < 11) {
            const int f = w - 9;
            const uint32_t fa = sb + H_FIN + f * 512;
            for (int s = 0; s < NSEG; s++) {
                mbar_wait_long(sb + HB_SENT + (s & 3) * 8, (s >> 2) & 1);
                const uint4* src = g_part + (((s % RING) * 9 + cc) * 16 + kq * 4) * 128 + f * 64 + lane;
                uint4 v[8];
                lds128(&v[6].x, sb + H_OWN + (s & 3) * 2048 + (f * 64 + lane) * 16);
                lds128(&v[7].x, sb + H_OWN + (s & 3) * 2048 + (f * 64 + 32 + lane) * 16);
                if (FIN0_NS) __nanosleep(FIN0_NS);
                unsigned c = 0;
                while (true) {
                    uint32_t bad = 0;
#pragma unroll
                    for (int i = 0; i < 6; i++) v[i] = ld_poll(src + ((kq + 1 + (i >> 1)) & 3) * 128 + (i & 1) * 32);
#pragma unroll
                    for (int i = 0; i < 6; i++) bad |= (v[i].x ^ (s + 1)) | (v[i].y ^ (s + 1)) | (v[i].z ^ (s + 1)) | (v[i].w ^ (s + 1));
                    if (!__any_sync(0xffffffffu, (bad & 127) != 0) || ++c >= LONG_LIM) break;
                    if (FIN_NS) __nanosleep(FIN_NS);
                }
                mbar_arrive_if0(sb + HB_FIN + (s & 3) * 8, lane);
                uint32_t pk[4];
#pragma unroll
                for (int u = 0; u < 2; u++) {
                    float o[4] = {0.f, 0.f, 0.f, 0.f};
#pragma unroll
                    for (int k = 0; k < 4; k++) {
                        o[0] += __uint_as_float(v[2 * k + u].x & ~127u); o[1] += __uint_as_float(v[2 * k + u].y & ~127u);
                        o[2] += __uint_as_float(v[2 * k + u].z & ~127u); o[3] += __uint_as_float(v[2 * k + u].w & ~127u);
                    }
                    pk[2 * u] = pack_bf16(o[0], o[1]); pk[2 * u + 1] = pack_bf16(o[2], o[3]);
                }
                stsm4t(fa + r * 64 + ((m ^ (r >> 1)) << 4), pk[0], pk[1], pk[2], pk[3]);
                __syncwarp();
                uint32_t o4[4];
                lds128(o4, fa + (lane >> 2) * 64 + (((lane & 3) ^ (lane >> 3)) << 4));
                *reinterpret_cast<uint4*>(out + (s * SEG + kq * 8 + (lane >> 2)) * OUTW + cc * 64 + f * 32 + (lane & 3) * 8) = make_uint4(o4[0], o4[1], o4[2], o4[3]);
                __syncwarp();
                HSTAMP2(s);
            }
            asm volatile("griddepcontrol.wait;" ::: "memory");
        }
    }
}

typedef CUresult (*EncodeFn)(CUtensorMap*, CUtensorMapDataType, cuuint32_t, void*, const cuuint64_t*, const cuuint64_t*, const cuuint32_t*,
                             const cuuint32_t*, CUtensorMapInterleave, CUtensorMapSwizzle, CUtensorMapL2promotion, CUtensorMapFloatOOBfill);

void make_map(EncodeFn fn, CUtensorMap* m, const void* p, int rank, const cuuint64_t* dims, const cuuint64_t* strides, const cuuint32_t* box,
              CUtensorMapSwizzle sw = CU_TENSOR_MAP_SWIZZLE_128B, CUtensorMapL2promotion pr = CU_TENSOR_MAP_L2_PROMOTION_L2_128B) {
    const cuuint32_t es[3] = {1, 1, 1};
    fn(m, CU_TENSOR_MAP_DATA_TYPE_BFLOAT16, rank, const_cast<void*>(p), dims, strides, box, es, CU_TENSOR_MAP_INTERLEAVE_NONE,
       sw, pr, CU_TENSOR_MAP_FLOAT_OOB_FILL_NONE);
}

}

extern "C" void kernel_launch(void* const* d_in, const int* in_sizes, int n_in, void* d_out, int out_size) {
    const bf16* x = (const bf16*)d_in[0];
    const bf16* mem0 = (const bf16*)d_in[1];
    const bf16* Wo = (const bf16*)d_in[5];
    bf16* out = (bf16*)d_out;

    static EncodeFn enc = nullptr;
    static char* acc = nullptr;
    if (!enc) {
        void* p = nullptr;
        cudaGetSymbolAddress(&p, g_acc);
        acc = reinterpret_cast<char*>((reinterpret_cast<uintptr_t>(p) + 32767) & ~(uintptr_t)32767);
        void* fn = nullptr;
        cudaDriverEntryPointQueryResult st;
        cudaGetDriverEntryPoint("cuTensorMapEncodeTiled", &fn, cudaEnableDefault, &st);
        enc = (EncodeFn)fn;
        cudaFuncSetAttribute(chain_kernel, cudaFuncAttributeMaxDynamicSharedMemorySize, A_SMEM);
        cudaFuncSetAttribute(helper_kernel, cudaFuncAttributeMaxDynamicSharedMemorySize, B_SMEM);
    }
    CUtensorMap tmW[3], tmWo, tmX;
    {
        const cuuint64_t dims[2] = {4096, 576}, str[1] = {8192};
        const cuuint32_t box[2] = {64, 192};
        for (int i = 0; i < 3; i++) make_map(enc, &tmW[i], d_in[2 + i], 2, dims, str, box, CU_TENSOR_MAP_SWIZZLE_128B, W_PROMO);
    }
    {
        const cuuint64_t dims[2] = {576, 4096}, str[1] = {1152};
        const cuuint32_t box[2] = {64, 128};
        make_map(enc, &tmWo, Wo, 2, dims, str, box);
    }
    {
        const cuuint64_t dims[3] = {64, 2048, 9}, str[2] = {1152, 128};
        const cuuint32_t box[3] = {64, 32, 9};
        make_map(enc, &tmX, x, 3, dims, str, box);
    }
    CUtensorMap tmU, tmY;
    {
        const cuuint64_t dimsU[2] = {576, 2048}, strU[1] = {1152}, dimsY[2] = {1152, 2048}, strY[1] = {2304};
        const cuuint32_t box[2] = {16, 256};
        make_map(enc, &tmU, d_in[7], 2, dimsU, strU, box, CU_TENSOR_MAP_SWIZZLE_32B);
        make_map(enc, &tmY, out, 2, dimsY, strY, box, CU_TENSOR_MAP_SWIZZLE_32B, CU_TENSOR_MAP_L2_PROMOTION_NONE);
    }
    cudaStream_t st = cudaStreamPerThread;
    {
        cudaLaunchConfig_t cfg = {};
        cfg.gridDim = dim3(96); cfg.blockDim = dim3(384); cfg.dynamicSmemBytes = A_SMEM; cfg.stream = st;
        cudaLaunchAttribute at[1];
        at[0].id = cudaLaunchAttributeClusterDimension;
        at[0].val.clusterDim.x = 3; at[0].val.clusterDim.y = 1; at[0].val.clusterDim.z = 1;
        cfg.attrs = at; cfg.numAttrs = 1;
        cudaLaunchKernelEx(&cfg, chain_kernel, tmW[0], tmW[1], tmW[2], tmWo, tmX, mem0, acc);
    }
    {
        cudaLaunchConfig_t cfg = {};
        cfg.gridDim = dim3(NHELP); cfg.blockDim = dim3(384); cfg.dynamicSmemBytes = B_SMEM; cfg.stream = st;
        cudaLaunchAttribute at[1];
        at[0].id = cudaLaunchAttributeProgrammaticStreamSerialization;
        at[0].val.programmaticStreamSerializationAllowed = 1;
        cfg.attrs = at; cfg.numAttrs = 1;
        cudaLaunchKernelEx(&cfg, helper_kernel, tmU, tmY, tmWo, (const bf16*)d_in[8], (const bf16*)d_in[9], (const bf16*)d_in[10],
                           (const bf16*)d_in[11], (const bf16*)d_in[12], (const bf16*)d_in[13], out);
    }
}
```

```cpp
#include <cuda_runtime.h>
#include <cuda_bf16.h>
#include <cuda_fp16.h>
#include <cuda.h>
#include <stdint.h>

typedef __nv_bfloat16 bf16;

#define EVF 15
namespace {

constexpr int DM = 576, NH = 32, DH = 128, SEG = 32, NSEG = 64, SEQ = 2048, NST = 128;
constexpr int OUTW = 2 * DM;
constexpr unsigned SPIN_LIM = 1u << 15;

__device__ __align__(1024) uint4 g_acc[33 * 2048];
__device__ __align__(128) unsigned g_time[NSEG * 96];
__device__ __align__(1024) uint4 g_ox[NSEG * NH * 512];
__device__ __align__(1024) uint4 g_vx[NH * 2 * 512];
__device__ __align__(128) unsigned g_flag[NSEG * 4];
__device__ unsigned g_zero_cnt;

__device__ __forceinline__ uint32_t smem_u32(const void* p) { return (uint32_t)__cvta_generic_to_shared(p); }
__device__ __forceinline__ unsigned clk() { unsigned c; asm volatile("mov.u32 %0, %%clock;" : "=r"(c)::"memory"); return c; }
__device__ __forceinline__ unsigned gtime() { unsigned t; asm volatile("mov.u32 %0, %%globaltimer_lo;" : "=r"(t)::"memory"); return t; }
__device__ __forceinline__ uint32_t slot_off(int s) { return (s >> 1) * 32768 + (s & 1) * 512; }
__device__ __forceinline__ uint32_t lane_off(uint32_t L16) { return (L16 & 0x180) * 8 + (L16 & 0x40) * 4 + (L16 & 0x30); }
__device__ __forceinline__ uint32_t mapa(uint32_t a, uint32_t r) { uint32_t o; asm("mapa.shared::cluster.u32 %0, %1, %2;" : "=r"(o) : "r"(a), "r"(r)); return o; }
__device__ __forceinline__ void mbar_init(uint32_t b, uint32_t n) { asm volatile("mbarrier.init.shared::cta.b64 [%0], %1;" ::"r"(b), "r"(n) : "memory"); }
__device__ __forceinline__ void mbar_arrive(uint32_t b) { asm volatile("mbarrier.arrive.shared::cta.b64 _, [%0];" ::"r"(b) : "memory"); }
__device__ __forceinline__ void mbar_expect(uint32_t b, uint32_t tx) { asm volatile("mbarrier.arrive.expect_tx.shared::cta.b64 _, [%0], %1;" ::"r"(b), "r"(tx) : "memory"); }
__device__ __forceinline__ bool mbar_try(uint32_t b, uint32_t par) {
    uint32_t ok;
    asm volatile("{.reg .pred p; mbarrier.try_wait.parity.shared::cta.b64 p, [%1], %2; selp.u32 %0, 1, 0, p;}" : "=r"(ok) : "r"(b), "r"(par) : "memory");
    return ok;
}
__device__ __forceinline__ bool mbar_test(uint32_t b, uint32_t par) {
    uint32_t ok;
    asm volatile("{.reg .pred p; mbarrier.test_wait.parity.shared::cta.b64 p, [%1], %2; selp.u32 %0, 1, 0, p;}" : "=r"(ok) : "r"(b), "r"(par) : "memory");
    return ok;
}
__device__ __forceinline__ void mbar_wait(uint32_t b, uint32_t par) {
    asm volatile("{.reg .pred p, q; .reg .u32 c; mov.u32 c, 0;\n"
                 "W: mbarrier.try_wait.parity.shared::cta.b64 p, [%0], %1;\n"
                 "@p bra D;\n add.u32 c, c, 1; setp.lt.u32 q, c, %2;\n @q bra W;\n D:\n}" ::"r"(b), "r"(par), "n"(SPIN_LIM) : "memory");
}
constexpr unsigned LONG_LIM = 1u << 17;
__device__ __forceinline__ void mbar_wait_long(uint32_t b, uint32_t par) {
    asm volatile("{.reg .pred p, q; .reg .u32 c; mov.u32 c, 0;\n"
                 "W: mbarrier.try_wait.parity.shared::cta.b64 p, [%0], %1;\n"
                 "@p bra D;\n add.u32 c, c, 1; setp.lt.u32 q, c, %2;\n @q bra W;\n D:\n}" ::"r"(b), "r"(par), "n"(LONG_LIM) : "memory");
}
__device__ __forceinline__ void cluster_sync() { asm volatile("barrier.cluster.arrive.aligned; barrier.cluster.wait.aligned;" ::: "memory"); }
__device__ __forceinline__ void fence_async_smem() { asm volatile("fence.proxy.async.shared::cta;" ::: "memory"); }
__device__ __forceinline__ void ldsm4(uint32_t* r, uint32_t a) { asm volatile("ldmatrix.sync.aligned.m8n8.x4.shared.b16 {%0,%1,%2,%3},[%4];" : "=r"(r[0]), "=r"(r[1]), "=r"(r[2]), "=r"(r[3]) : "r"(a) : "memory"); }
__device__ __forceinline__ void ldsm4t(uint32_t* r, uint32_t a) { asm volatile("ldmatrix.sync.aligned.m8n8.x4.trans.shared.b16 {%0,%1,%2,%3},[%4];" : "=r"(r[0]), "=r"(r[1]), "=r"(r[2]), "=r"(r[3]) : "r"(a) : "memory"); }
__device__ __forceinline__ void stsm1(uint32_t a, uint32_t r0) { asm volatile("stmatrix.sync.aligned.m8n8.x1.shared.b16 [%0],{%1};" ::"r"(a), "r"(r0) : "memory"); }
__device__ __forceinline__ void stsm2t(uint32_t a, uint32_t r0, uint32_t r1) { asm volatile("stmatrix.sync.aligned.m8n8.x2.trans.shared.b16 [%0],{%1,%2};" ::"r"(a), "r"(r0), "r"(r1) : "memory"); }
__device__ __forceinline__ void stsm4t(uint32_t a, uint32_t r0, uint32_t r1, uint32_t r2, uint32_t r3) { asm volatile("stmatrix.sync.aligned.m8n8.x4.trans.shared.b16 [%0],{%1,%2,%3,%4};" ::"r"(a), "r"(r0), "r"(r1), "r"(r2), "r"(r3) : "memory"); }
__device__ __forceinline__ void stsm4(uint32_t a, uint32_t r0, uint32_t r1, uint32_t r2, uint32_t r3) { asm volatile("stmatrix.sync.aligned.m8n8.x4.shared.b16 [%0],{%1,%2,%3,%4};" ::"r"(a), "r"(r0), "r"(r1), "r"(r2), "r"(r3) : "memory"); }
__device__ __forceinline__ void sts32(uint32_t a, uint32_t v) { asm volatile("st.shared.b32 [%0], %1;" ::"r"(a), "r"(v) : "memory"); }
__device__ __forceinline__ void sts64(uint32_t a, uint32_t x, uint32_t y) { asm volatile("st.shared.v2.b32 [%0], {%1,%2};" ::"r"(a), "r"(x), "r"(y) : "memory"); }
__device__ __forceinline__ void sts128(uint32_t a, uint32_t x, uint32_t y, uint32_t z, uint32_t w) { asm volatile("st.shared.v4.b32 [%0], {%1,%2,%3,%4};" ::"r"(a), "r"(x), "r"(y), "r"(z), "r"(w) : "memory"); }
__device__ __forceinline__ void lds64(uint32_t* r, uint32_t a) { asm volatile("ld.shared.v2.b32 {%0,%1},[%2];" : "=r"(r[0]), "=r"(r[1]) : "r"(a) : "memory"); }
__device__ __forceinline__ float2 lds64f(uint32_t a) { float2 v; asm volatile("ld.shared.v2.f32 {%0,%1},[%2];" : "=f"(v.x), "=f"(v.y) : "r"(a) : "memory"); return v; }
__device__ __forceinline__ void lds128(uint32_t* r, uint32_t a) { asm volatile("ld.shared.v4.b32 {%0,%1,%2,%3},[%4];" : "=r"(r[0]), "=r"(r[1]), "=r"(r[2]), "=r"(r[3]) : "r"(a) : "memory"); }
__device__ __forceinline__ void st_async64(uint32_t a, uint32_t x, uint32_t y, uint32_t bar) {
    asm volatile("st.async.weak.shared::cluster.mbarrier::complete_tx::bytes.v2.b32 [%0], {%1,%2}, [%3];" ::"r"(a), "r"(x), "r"(y), "r"(bar) : "memory");
}
__device__ __forceinline__ void st_async32(uint32_t a, uint32_t x, uint32_t bar) {
    asm volatile("st.async.weak.shared::cluster.mbarrier::complete_tx::bytes.b32 [%0], %1, [%2];" ::"r"(a), "r"(x), "r"(bar) : "memory");
}
__device__ __forceinline__ void ldsm2(uint32_t* r, uint32_t a) { asm volatile("ldmatrix.sync.aligned.m8n8.x2.shared.b16 {%0,%1},[%2];" : "=r"(r[0]), "=r"(r[1]) : "r"(a) : "memory"); }
__device__ __forceinline__ uint32_t pack_f16_sat(float lo, float hi) { uint32_t r; asm("cvt.rn.satfinite.f16x2.f32 %0, %1, %2;" : "=r"(r) : "f"(hi), "f"(lo)); return r; }
__device__ __forceinline__ __half2 as_h2(uint32_t x) { return *reinterpret_cast<__half2*>(&x); }
__device__ __forceinline__ uint32_t as_u32(__half2 x) { return *reinterpret_cast<uint32_t*>(&x); }
__device__ __forceinline__ uint32_t pack_bf16(float lo, float hi) { uint32_t r; asm("cvt.rn.bf16x2.f32 %0, %1, %2;" : "=r"(r) : "f"(hi), "f"(lo)); return r; }
__device__ __forceinline__ float ex2(float x) { float r; asm("ex2.approx.ftz.f32 %0, %1;" : "=f"(r) : "f"(x)); return r; }
__device__ __forceinline__ float rcp(float x) { float r; asm("rcp.approx.ftz.f32 %0, %1;" : "=f"(r) : "f"(x)); return r; }
__device__ __forceinline__ void mma16(float* d, const uint32_t* a, uint32_t b0, uint32_t b1) {
    asm volatile("mma.sync.aligned.m16n8k16.row.col.f32.bf16.bf16.f32 {%0,%1,%2,%3},{%4,%5,%6,%7},{%8,%9},{%0,%1,%2,%3};"
                 : "+f"(d[0]), "+f"(d[1]), "+f"(d[2]), "+f"(d[3]) : "r"(a[0]), "r"(a[1]), "r"(a[2]), "r"(a[3]), "r"(b0), "r"(b1));
}
__device__ __forceinline__ void mma16z(float* d, const uint32_t* a, uint32_t b0, uint32_t b1) {
    asm volatile("mma.sync.aligned.m16n8k16.row.col.f32.bf16.bf16.f32 {%0,%1,%2,%3},{%4,%5,%6,%7},{%8,%9},{%10,%10,%10,%10};"
                 : "=f"(d[0]), "=f"(d[1]), "=f"(d[2]), "=f"(d[3]) : "r"(a[0]), "r"(a[1]), "r"(a[2]), "r"(a[3]), "r"(b0), "r"(b1), "f"(0.f));
}
__device__ __forceinline__ void mma8(float* d, uint32_t a0, uint32_t a1, uint32_t b0) {
    asm volatile("mma.sync.aligned.m16n8k8.row.col.f32.bf16.bf16.f32 {%0,%1,%2,%3},{%4,%5},{%6},{%0,%1,%2,%3};"
                 : "+f"(d[0]), "+f"(d[1]), "+f"(d[2]), "+f"(d[3]) : "r"(a0), "r"(a1), "r"(b0));
}
template <int ACC>
__device__ __forceinline__ void mma_sp(float* d, const uint32_t* a, const uint32_t* b) {
    if (ACC)
        asm volatile("mma.sp::ordered_metadata.sync.aligned.m16n8k32.row.col.f32.bf16.bf16.f32 {%0,%1,%2,%3},{%4,%5,%6,%7},{%8,%9,%10,%11},{%0,%1,%2,%3},%12,0x0;"
                     : "+f"(d[0]), "+f"(d[1]), "+f"(d[2]), "+f"(d[3])
                     : "r"(a[0]), "r"(a[1]), "r"(a[2]), "r"(a[3]), "r"(b[0]), "r"(b[1]), "r"(b[2]), "r"(b[3]), "r"(0xEEEE4444u));
    else
        asm volatile("mma.sp::ordered_metadata.sync.aligned.m16n8k32.row.col.f32.bf16.bf16.f32 {%0,%1,%2,%3},{%4,%5,%6,%7},{%8,%9,%10,%11},{%13,%13,%13,%13},%12,0x0;"
                     : "=f"(d[0]), "=f"(d[1]), "=f"(d[2]), "=f"(d[3])
                     : "r"(a[0]), "r"(a[1]), "r"(a[2]), "r"(a[3]), "r"(b[0]), "r"(b[1]), "r"(b[2]), "r"(b[3]), "r"(0xEEEE4444u), "f"(0.f));
}
__device__ __forceinline__ void mbar_arrive_if0(uint32_t b, uint32_t z) { asm volatile("{.reg .pred p; setp.eq.u32 p, %1, 0; @p mbarrier.arrive.shared::cta.b64 _, [%0];}" ::"r"(b), "r"(z) : "memory"); }
__device__ __forceinline__ void mbar_expect_if0(uint32_t b, uint32_t tx, uint32_t z) { asm volatile("{.reg .pred p; setp.eq.u32 p, %2, 0; @p mbarrier.arrive.expect_tx.shared::cta.b64 _, [%0], %1;}" ::"r"(b), "r"(tx), "r"(z) : "memory"); }
__device__ __forceinline__ float lds32f(uint32_t a) { float v; asm volatile("ld.shared.f32 %0,[%1];" : "=f"(v) : "r"(a) : "memory"); return v; }
__device__ __forceinline__ void wg_fence() { asm volatile("wgmma.fence.sync.aligned;" ::: "memory"); }
__device__ __forceinline__ void wg_commit() { asm volatile("wgmma.commit_group.sync.aligned;" ::: "memory"); }
template <int N> __device__ __forceinline__ void wg_wait() { asm volatile("wgmma.wait_group.sync.aligned %0;" ::"n"(N) : "memory"); }
__device__ __forceinline__ void delay(unsigned n) { if (n) { const unsigned t0 = clk(); while (clk() - t0 < n) {} } }
template <int ACC, uint32_t DHI = 0x40000040u, int TB = 0>
__device__ __forceinline__ void wg_rs_n32(float* d, const uint32_t* a, uint32_t dlo) {
    if (ACC)
        asm volatile("{.reg .b64 db; mov.b64 db, {%20, %21};\n"
                     "wgmma.mma_async.sync.aligned.m64n32k16.f32.bf16.bf16 {%0,%1,%2,%3,%4,%5,%6,%7,%8,%9,%10,%11,%12,%13,%14,%15},{%16,%17,%18,%19},db,1,1,1,%22;}"
                     : "+f"(d[0]), "+f"(d[1]), "+f"(d[2]), "+f"(d[3]), "+f"(d[4]), "+f"(d[5]), "+f"(d[6]), "+f"(d[7]),
                       "+f"(d[8]), "+f"(d[9]), "+f"(d[10]), "+f"(d[11]), "+f"(d[12]), "+f"(d[13]), "+f"(d[14]), "+f"(d[15])
                     : "r"(a[0]), "r"(a[1]), "r"(a[2]), "r"(a[3]), "r"(dlo), "r"(DHI), "n"(TB));
    else
        asm volatile("{.reg .b64 db; mov.b64 db, {%20, %21};\n"
                     "wgmma.mma_async.sync.aligned.m64n32k16.f32.bf16.bf16 {%0,%1,%2,%3,%4,%5,%6,%7,%8,%9,%10,%11,%12,%13,%14,%15},{%16,%17,%18,%19},db,0,1,1,%22;}"
                     : "=f"(d[0]), "=f"(d[1]), "=f"(d[2]), "=f"(d[3]), "=f"(d[4]), "=f"(d[5]), "=f"(d[6]), "=f"(d[7]),
                       "=f"(d[8]), "=f"(d[9]), "=f"(d[10]), "=f"(d[11]), "=f"(d[12]), "=f"(d[13]), "=f"(d[14]), "=f"(d[15])
                     : "r"(a[0]), "r"(a[1]), "r"(a[2]), "r"(a[3]), "r"(dlo), "r"(DHI), "n"(TB));
}
__device__ __forceinline__ uint32_t desc_lo(uint32_t addr) { return ((addr & 0x3FFFF) >> 4) | (1u << 16); }
__device__ __forceinline__ void tma2d(uint32_t dst, const CUtensorMap* m, int c0, int c1, uint32_t bar) {
    asm volatile("cp.async.bulk.tensor.2d.shared::cluster.global.mbarrier::complete_tx::bytes [%0], [%1, {%2,%3}], [%4];"
                 ::"r"(dst), "l"(m), "r"(c0), "r"(c1), "r"(bar) : "memory");
}
__device__ __forceinline__ uint64_t evict_first() { uint64_t p; asm("createpolicy.fractional.L2::evict_first.b64 %0, 1.0;" : "=l"(p)); return p; }
__device__ __forceinline__ void tma2d_once(uint32_t dst, const CUtensorMap* m, int c0, int c1, uint32_t bar) {
    const uint64_t pol = evict_first();
    asm volatile("cp.async.bulk.tensor.2d.shared::cluster.global.mbarrier::complete_tx::bytes.L2::cache_hint [%0], [%1, {%2,%3}], [%4], %5;"
                 ::"r"(dst), "l"(m), "r"(c0), "r"(c1), "r"(bar), "l"(pol) : "memory");
}
__device__ __forceinline__ void tma3d(uint32_t dst, const CUtensorMap* m, int c0, int c1, int c2, uint32_t bar) {
    asm volatile("cp.async.bulk.tensor.3d.shared::cluster.global.mbarrier::complete_tx::bytes [%0], [%1, {%2,%3,%4}], [%5];"
                 ::"r"(dst), "l"(m), "r"(c0), "r"(c1), "r"(c2), "r"(bar) : "memory");
}
__device__ __forceinline__ void tma3d_mc(uint32_t dst, const CUtensorMap* m, int c0, int c1, int c2, uint32_t bar, uint16_t mask) {
    if (EVF & 8) asm volatile("cp.async.bulk.tensor.3d.shared::cluster.global.mbarrier::complete_tx::bytes.multicast::cluster.L2::cache_hint [%0], [%1, {%2,%3,%4}], [%5], %6, %7;"
                 ::"r"(dst), "l"(m), "r"(c0), "r"(c1), "r"(c2), "r"(bar), "h"(mask), "l"(evict_first()) : "memory");
    else
    asm volatile("cp.async.bulk.tensor.3d.shared::cluster.global.mbarrier::complete_tx::bytes.multicast::cluster [%0], [%1, {%2,%3,%4}], [%5], %6;"
                 ::"r"(dst), "l"(m), "r"(c0), "r"(c1), "r"(c2), "r"(bar), "h"(mask) : "memory");
}
__device__ __forceinline__ void bulk_g2s_mc(uint32_t dst, const void* src, uint32_t bytes, uint32_t bar, uint16_t mask) {
    asm volatile("cp.async.bulk.shared::cluster.global.mbarrier::complete_tx::bytes.multicast::cluster [%0], [%1], %2, [%3], %4;"
                 ::"r"(dst), "l"(src), "r"(bytes), "r"(bar), "h"(mask) : "memory");
}
__device__ __forceinline__ void tma2d_prefetch(const CUtensorMap* m, int c0, int c1) {
    asm volatile("cp.async.bulk.prefetch.tensor.2d.L2.global [%0, {%1,%2}];" ::"l"(m), "r"(c0), "r"(c1) : "memory");
}
__device__ __forceinline__ void bulk_s2c(uint32_t dst, uint32_t src, uint32_t bytes, uint32_t bar) {
    asm volatile("cp.async.bulk.shared::cluster.shared::cta.mbarrier::complete_tx::bytes [%0], [%1], %2, [%3];" ::"r"(dst), "r"(src), "r"(bytes), "r"(bar) : "memory");
}
__device__ __forceinline__ void bulk_s2g(void* dst, uint32_t src, uint32_t bytes) {
    asm volatile("cp.async.bulk.global.shared::cta.bulk_group [%0], [%1], %2;" ::"l"(dst), "r"(src), "r"(bytes) : "memory");
}
__device__ __forceinline__ void bulk_commit() { asm volatile("cp.async.bulk.commit_group;" ::: "memory"); }
__device__ __forceinline__ void bulk_wait0() { asm volatile("cp.async.bulk.wait_group 0;" ::: "memory"); }
__device__ __forceinline__ uint4 ld_poll(const void* p) {
    uint4 v;
    asm volatile("ld.relaxed.gpu.global.v4.u32 {%0,%1,%2,%3},[%4];" : "=r"(v.x), "=r"(v.y), "=r"(v.z), "=r"(v.w) : "l"(p) : "memory");
    return v;
}
template <int IMM>
__device__ __forceinline__ void ld_poll_at(uint4& v, const void* p) {
    asm volatile("ld.relaxed.gpu.global.v4.u32 {%0,%1,%2,%3},[%4+%5];" : "=r"(v.x), "=r"(v.y), "=r"(v.z), "=r"(v.w) : "l"(p), "n"(IMM) : "memory");
}
__device__ __forceinline__ void look(uint4 (&v)[6], const void* p) {
    ld_poll_at<0>(v[0], p); ld_poll_at<16384>(v[1], p); ld_poll_at<64>(v[2], p);
    ld_poll_at<16384 + 64>(v[3], p); ld_poll_at<128>(v[4], p); ld_poll_at<16384 + 128>(v[5], p);
}
__device__ __forceinline__ unsigned ld_acquire(const unsigned* p) { unsigned v; asm volatile("ld.acquire.gpu.global.u32 %0,[%1];" : "=r"(v) : "l"(p) : "memory"); return v; }
__device__ __forceinline__ void red_release(unsigned* p, unsigned v) { asm volatile("red.release.gpu.global.add.u32 [%0], %1;" ::"l"(p), "r"(v) : "memory"); }

template <int ID, int N> __device__ __forceinline__ void bar_sync() { asm volatile("bar.sync %0, %1;" ::"n"(ID), "n"(N) : "memory"); }
template <int ID, int N> __device__ __forceinline__ void bar_arrive() { asm volatile("bar.arrive %0, %1;" ::"n"(ID), "n"(N) : "memory"); }
__device__ __forceinline__ void cluster_arrive() { asm volatile("barrier.cluster.arrive.relaxed.aligned;" ::: "memory"); }
__device__ __forceinline__ void cluster_wait() { asm volatile("barrier.cluster.wait.aligned;" ::: "memory"); }

constexpr uint32_t XB_BYTES = 36864;
constexpr uint32_t S_XB = 0;
constexpr uint32_t S_QM = 73728;
constexpr uint32_t S_KM = 74752;
constexpr uint32_t S_OM = 75776;
constexpr uint32_t S_SP = 77824;
constexpr uint32_t S_SUM = 80384;
constexpr uint32_t S_TGT = 81408;
constexpr uint32_t S_VM = 147456;
constexpr uint32_t S_QX = 86016;
constexpr uint32_t S_PX = S_QX;
constexpr uint32_t S_KX = 94208;
constexpr uint32_t S_VX = 102400;
constexpr uint32_t S_SX = 135168;
constexpr uint32_t S_OX = 155648;
constexpr uint32_t S_MEM = 172032;
constexpr uint32_t S_WO = 181248;
constexpr uint32_t S_BAR = 230400;
constexpr uint32_t S_ZERO = S_BAR + 128;
constexpr uint32_t A_SMEM = S_ZERO + 1024;
__host__ __device__ constexpr uint32_t s_w(int c) { return c == 0 ? S_WO : 73728 + (c - 1) * 49152; }
constexpr uint32_t B_W = S_BAR, B_WO = S_BAR + 24, B_X = S_BAR + 32, B_S = S_BAR + 48, B_VX = S_BAR + 56, B_SX = S_BAR + 72, B_M = S_BAR + 88, B_T = S_BAR + 112;
constexpr int NB_QK = 1, NB_O = 2, NB_RED = 3, NB_P = 4, NB_AUX = 5, NB_PRO = 6, NB_X = 7, NB_GO = 8, NB_L = 9, NB_PV = 10, NB_T0 = 11;

constexpr float SM_SCALE = 0.08838834764831845f * 1.4426950408889634f;
constexpr uint32_t ONES = 0x3F803F80u;
constexpr uint32_t FULL_COUNT = 0x4200u;
#define XLIM NSEG
#define TGT_NS 1056
#define LOOK_NS 100
#define RCP_AT 2
#define NCH 2
#define XTMA_NS 50
#define REG_MAIN0 232
#define REG_MAIN1 232
#define REG_AUX 40

#define HAND_AT 26
#define PUB_EARLY 0
#define W_PROMO CU_TENSOR_MAP_L2_PROMOTION_L2_128B
#define DESCPF 1
#define WO_AFTER 2
#define FIRST_NS 450
#define PACE 1
#define DEP_LATE 1
#define HSPLIT 2
#define FIN_NS 40
#define WO_LOOP 1
#define YST 1
#define TRICKLE_NS 700
#define REFRESH 0
#define U_NS 0
#define FIN0_NS 0
#define FLAG_NS 40
static_assert(REG_MAIN0 + REG_MAIN1 + REG_AUX <= 504, "the three warpgroups share 3 x 168 registers");
#define HSTAMP(i) do {} while (0)
#define HSTAMP2(i) do {} while (0)
#define HSTAMP3(i) do {} while (0)
#define HSTAMP4(i) do {} while (0)
#define TSTAMP(i, e) do {} while (0)

__device__ __forceinline__ void load_scores(uint32_t a, __half2 (&hs)[5]) {
    uint32_t r[10];
    ldsm4(r, a);
    ldsm4(r + 4, a + 512);
    ldsm2(r + 8, a + 1024);
    const __half2 hf = as_h2(0x38003800u);
#pragma unroll
    for (int T = 0; T < 5; T++) hs[T] = __hfma2(as_h2(r[2 * T]), hf, __hmul2(as_h2(r[2 * T + 1]), hf));
}
__device__ __forceinline__ void softmax_exp(const __half2 (&hs)[5], float (&ev)[10]) {
    __half2 m = __hmax2(__hmax2(__hmax2(hs[0], hs[1]), __hmax2(hs[2], hs[3])), hs[4]);
    const uint32_t mu = as_u32(m);
    const uint32_t m1 = __shfl_xor_sync(0xffffffffu, mu, 1), m2 = __shfl_xor_sync(0xffffffffu, mu, 2), m3 = __shfl_xor_sync(0xffffffffu, mu, 3);
    m = __hmax2(__hmax2(m, as_h2(m1)), __hmax2(as_h2(m2), as_h2(m3)));
    const float mc = -fmaxf(__low2float(m), __high2float(m)) * (2.f * SM_SCALE);
#pragma unroll
    for (int T = 0; T < 5; T++) {
        ev[2 * T] = ex2(fmaf(__low2float(hs[T]), 2.f * SM_SCALE, mc));
        ev[2 * T + 1] = ex2(fmaf(__high2float(hs[T]), 2.f * SM_SCALE, mc));
    }
}

__device__ __forceinline__ void x_scores(uint32_t sb, int seg, int wq, uint32_t L16, float (&ev)[10]) {
    __half2 hs[5];
    load_scores(sb + S_SX + (seg & 1) * 5120 + wq * 1280 + L16, hs);
    const int dg = (int)(L16 >> 6) - (int)((L16 >> 3) & 6) + 8 * wq;
#pragma unroll
    for (int T = 0; T < 4; T++) {
        uint32_t u = as_u32(hs[T]);
        if (dg < 8 * T + 1) u = (u & 0xFFFFu) | 0xFC000000u;
        if (dg < 8 * T) u = 0xFC00FC00u;
        hs[T] = as_h2(u);
    }
    softmax_exp(hs, ev);
}
__device__ __forceinline__ void x_probs(uint32_t sb, int seg, int wq, uint32_t L16, const float (&ev)[10]) {
    float l = ((ev[0] + ev[1]) + (ev[2] + ev[3])) + ((ev[4] + ev[5]) + (ev[6] + ev[7])) + (ev[8] + ev[9]);
    const float l1 = __shfl_xor_sync(0xffffffffu, l, 1), l2 = __shfl_xor_sync(0xffffffffu, l, 2), l3 = __shfl_xor_sync(0xffffffffu, l, 3);
    const float r = rcp((l + l1) + (l2 + l3));
    const uint32_t a = sb + S_PX + (seg & 1) * 4096 + wq * 640 + (L16 >> 2);
#pragma unroll
    for (int i = 0; i < 5; i++) sts32(a + i * 128, pack_bf16(ev[2 * i] * r, ev[2 * i + 1] * r));
}
__device__ __forceinline__ void x_pv_load(uint32_t sb, int seg, int w, uint32_t L16, uint32_t (&a)[3][4]) {
    lds128(a[0], sb + S_VX + (seg & 3) * 8192 + w * 1024 + L16);
    lds128(a[1], sb + S_VX + (seg & 3) * 8192 + w * 1024 + 512 + L16);
    lds64(a[2], sb + S_VM + (seg & 3) * 2048 + w * 256 + (L16 >> 1));
    a[2][2] = 0; a[2][3] = 0;
}
__device__ __forceinline__ void x_pv_run(uint32_t sb, int seg, const uint32_t (&a)[3][4], uint32_t (&pk)[8]) {
    const uint32_t d = ((sb + S_PX + (seg & 1) * 4096) & 0x3FFFF) >> 4;
    float o[16];
    wg_fence();
    wg_rs_n32<0, 40>(o, a[0], d | (8u << 16));
    wg_rs_n32<1, 40>(o, a[1], (d + 16) | (8u << 16));
    wg_rs_n32<1, 40>(o, a[2], d + 32);
    wg_commit();
    wg_wait<0>();
#pragma unroll
    for (int i = 0; i < 8; i++) pk[i] = pack_bf16(o[2 * i], o[2 * i + 1]);
}
__device__ __forceinline__ void x_pv_store(uint32_t sb, int seg, int w, uint32_t L16, const uint32_t (&pk)[8]) {
    const uint32_t a = sb + S_OX + (seg & 1) * 8192 + w * 1024 + L16;
    stsm4(a, pk[0], pk[1], pk[2], pk[3]);
    stsm4(a + 512, pk[4], pk[5], pk[6], pk[7]);
}
template <int BAR, int CNT>
__device__ __forceinline__ void x_pv_both(uint32_t sb, int seg, int wq, uint32_t L16) {
    uint32_t pva[3][4], pk[8];
    x_pv_load(sb, seg, wq + 4, L16, pva);
    bar_sync<BAR, CNT>();
    x_pv_run(sb, seg, pva, pk);
    x_pv_load(sb, seg, wq, L16, pva);
    x_pv_store(sb, seg, wq + 4, L16, pk);
    x_pv_run(sb, seg, pva, pk);
    x_pv_store(sb, seg, wq, L16, pk);
}
__device__ __forceinline__ void ox_store(uint32_t sb, int seg, uint32_t h) {
    fence_async_smem();
    bulk_s2g(g_ox + (seg * NH + h) * 512, sb + S_OX + (seg & 1) * 8192, 8192);
    bulk_commit();
}
__device__ __forceinline__ void ox_publish(int seg, uint32_t h) {
    bulk_wait0();
    asm volatile("fence.proxy.async.global;" ::: "memory");
    asm volatile("red.relaxed.gpu.global.add.u32 [%0], 1;" ::"l"(&g_flag[(h >> 3) * NSEG + seg]) : "memory");
}
__device__ __forceinline__ void vx_store(uint32_t sb, int seg, uint32_t h) {
    fence_async_smem();
    bulk_s2g(g_vx + (h * 2 + (seg & 1)) * 512, sb + S_VX + (seg & 3) * 8192, 8192);
    bulk_commit();
}
__device__ __forceinline__ void vx_fetch(uint32_t sb, int seg, uint32_t h) {
    bulk_wait0();
    bulk_g2s_mc(sb + S_VX + (seg & 3) * 8192, g_vx + (h * 2 + (seg & 1)) * 512, 8192, sb + B_VX + (seg & 1) * 8, 3);
}

__device__ __forceinline__ void x_pack(const float (&d)[16], uint32_t (&pk)[8]) {
#pragma unroll
    for (int i = 0; i < 8; i++) pk[i] = pack_bf16(d[2 * i], d[2 * i + 1]);
}
__device__ __forceinline__ void x_write(uint32_t sb, const uint32_t (&pk)[8], int seg, bool isv, int w, uint32_t L16) {
    if (!isv) {
        const uint32_t a = sb + S_QX + (w >> 2) * 8192 + (seg & 1) * 4096 + (w & 3) * 256 + (L16 & 0xF0) + (L16 & 0x100) * 4;
        stsm4t(a, pk[0], pk[1], pk[2], pk[3]);
        stsm4t(a + 2048, pk[4], pk[5], pk[6], pk[7]);
    } else {
        const uint32_t a = sb + S_VX + (seg & 3) * 8192 + w * 1024 + L16;
        sts128(a, pk[0], pk[1], pk[2], pk[3]);
        sts128(a + 512, pk[4], pk[5], pk[6], pk[7]);
    }
}

template <int K0, int K1>
__device__ __forceinline__ void x_project(float (&d)[16], const uint32_t (&wA)[36][4], uint32_t desc) {
#pragma unroll
    for (int i = K0; i < K1; i++) {
        const uint32_t db = desc + (((i >> 2) * 4096 + (i & 3) * 32) >> 4);
        if (i == 0) wg_rs_n32<0>(d, wA[i], db); else wg_rs_n32<1>(d, wA[i], db);
    }
}

__device__ __forceinline__ void mem_scores(uint32_t sb, uint32_t peerA, uint32_t peerB, uint32_t off, const uint32_t (&q0)[4], const uint32_t (&q1)[4],
                                           const uint32_t (&k0)[4], const uint32_t (&k1)[4]) {
    float e0[4], o0[4], e1[4], o1[4];
    mma16z(e0, q0, k0[0], k0[1]);
    mma16z(o0, q0, k0[2], k0[3]);
    mma16z(e1, q1, k1[0], k1[1]);
    mma16z(o1, q1, k1[2], k1[3]);
    const uint32_t sc = pack_f16_sat((e0[0] + o0[2]) + (e1[0] + o1[2]), (e0[1] + o0[3]) + (e1[1] + o1[3]));
    st_async32(peerB + off, sc, peerB + B_S);
    st_async32(peerA + off, sc, peerA + B_S);
    sts32(sb + off, sc);
    __syncwarp();
}

__device__ __forceinline__ unsigned post_time(int s, uint32_t L16) {
    delay(1);
    const unsigned t = gtime() | 1;
    if (L16 == 0) asm volatile("st.relaxed.gpu.global.u32 [%0], %1;" ::"l"(g_time + s * 96 + blockIdx.x), "r"(t) : "memory");
    return t;
}
__device__ __forceinline__ void plan_look(uint32_t sb, int s, uint32_t L16, unsigned t) {
    const char* p = reinterpret_cast<const char*>(g_time) + s * 384 + (L16 < 384 ? L16 : 0);
    uint4 v;
    unsigned c = 0;
    do { v = ld_poll(p); } while (__any_sync(0xffffffffu, (v.x & v.y & v.z & v.w & 1) == 0) && ++c < SPIN_LIM);
    const int d = max(max((int)(v.x - t), (int)(v.y - t)), max((int)(v.z - t), (int)(v.w - t))) + (s == 0 ? FIRST_NS : 0);
    const unsigned tgt = t + min(__reduce_max_sync(0xffffffffu, d), 20000) + TGT_NS;
    if (L16 < 48) { const uint32_t r = mapa(sb, L16 >> 4); st_async32(r + S_TGT, tgt, r + B_T); }
}

__device__ __forceinline__ void load_wo(uint32_t sb, int w, uint32_t L16, uint32_t (&woA)[8][4], uint32_t (&woB)[4][4]) {
    mbar_wait(sb + B_WO, 0);
    if (w < 4) TSTAMP(73, 0);
    const int m = L16 >> 7, r = (L16 >> 4) & 7;
    const int ca = 3 * w + (m & 1), cb = 3 * w + 2;
    const uint32_t aA = sb + S_WO + (ca >> 3) * 16384 + ((m >> 1) * 8 + r) * 128 + (((ca & 7) ^ r) << 4);
    const int eB = ((m & 2) + ((r >> 1) & 1)) * 8 + 4 * (m & 1) + 2 * (r >> 2) + (r & 1);
    const uint32_t aB = sb + S_WO + (cb >> 3) * 16384 + eB * 128 + (((cb & 7) ^ (eB & 7)) << 4);
#pragma unroll
    for (int i = 0; i < 8; i++) ldsm4t(woA[i], aA + i * 2048);
#pragma unroll
    for (int i = 0; i < 4; i++) ldsm4t(woB[i], aB + i * 4096);
}

template <int ROLE>
__device__ __forceinline__ void chain_main(const uint32_t sb, const uint32_t lane16, const int wq, const uint32_t j, const uint32_t h,
                                           const uint32_t peerA, const uint32_t peerB, char* const acc) {
    uint32_t L16 = lane16;
    constexpr bool isv = ROLE >= 2;
    constexpr int wg = ROLE & 1;
    const int w = wg * 4 + wq;
    const uint32_t xdesc = desc_lo(sb + S_XB);
    const uint32_t zero = h >> 20;
    uint32_t wA[36][4], woA[8][4], woB[4][4];
    float xd[16];
    {
        const int m = L16 >> 7, r = (L16 >> 4) & 7;
        const int blk = (ROLE == 1) ? ((wq & 2) * 2 + (wq & 1) + (m & 1) * 2) : (2 * wq + (m & 1));
        const uint32_t a = sb + wg * 24576 + ((m >> 1) * 8 + r) * 128 + ((blk ^ r) << 4);
        float x0[16];
#pragma unroll
        for (int c = 0; c < 3; c++) {
            mbar_wait(sb + B_W + 8 * c, 0);
            if (wg == 0) TSTAMP(70 + c, 0);
#pragma unroll
            for (int i = 0; i < 12; i++) ldsm4t(wA[12 * c + i], a + s_w(c) + i * 2048);
            if (c == WO_AFTER) bar_arrive<NB_PRO, 288>();
            if (c == 0) { mbar_wait(sb + B_X, 0); mbar_wait(sb + B_X + 8, 0); }
            if (c == 2) { bar_sync<NB_O, 256>(); cluster_arrive(); }
            wg_fence();
            if (c == 0) { x_project<0, 12>(x0, wA, xdesc); x_project<0, 12>(xd, wA, xdesc + (XB_BYTES >> 4)); wg_commit(); wg_wait<0>(); }
            if (c == 1) { x_project<12, 24>(x0, wA, xdesc); x_project<12, 24>(xd, wA, xdesc + (XB_BYTES >> 4)); wg_commit(); wg_wait<0>(); }
            if (c == 2) { x_project<24, 36>(x0, wA, xdesc); wg_commit(); wg_wait<0>(); }
        }
        uint32_t pk[8];
        x_pack(x0, pk);
        x_write(sb, pk, 0, isv, w, L16);
        bar_arrive<NB_AUX, 288>();
        wg_fence();
        x_project<24, 36>(xd, wA, xdesc + (XB_BYTES >> 4));
        wg_commit();
        cluster_wait();
        bar_sync<NB_O, 256>();
        if (wg == 0) TSTAMP(74, 0);
        if (WO_LOOP) {
#pragma unroll
            for (int i = 0; i < 8; i++) woA[i][0] = woA[i][1] = woA[i][2] = woA[i][3] = 0;
#pragma unroll
            for (int i = 0; i < 4; i++) woB[i][0] = woB[i][1] = woB[i][2] = woB[i][3] = 0;
        } else load_wo(sb, w, L16, woA, woB);
    }
    int s = 0;
#pragma unroll 1
    while (true) {
        const uint32_t par = s & 1;
        const uint32_t kx = sb + S_KX + par * 4096;
        asm volatile("" : "+r"(L16));
        uint32_t pk[8];
        if (wg == 0) { wg_wait<0>(); x_pack(xd, pk); x_write(sb, pk, s + 1, isv, w, L16); }
        float c0[4], c1[4];
        uint32_t k0[4], k1[4];
        {
            const uint32_t a = sb + S_MEM + L16;
            constexpr int CH = 18 / NCH;
            uint32_t b[3][4];
            bool ready = true;
            mbar_wait(sb + B_M, par);
            ldsm4(b[0], a);
            ldsm4(b[1], a + 512);
            if (wg == 1) { wg_wait<0>(); x_pack(xd, pk); }
            bar_arrive<NB_GO, 288>();
#pragma unroll
            for (int i = 0; i < 18; i++) {
                if ((i + 4) % CH == 0 && i + 4 < 18) ready = mbar_test(sb + B_M + ((i + 4) / CH) * 8, par);
                if ((i + 2) % CH == 0 && i + 2 < 18) { if (__builtin_expect(!ready, 0)) mbar_wait(sb + B_M + ((i + 2) / CH) * 8, par); }
                if (i + 2 < 18) ldsm4(b[(i + 2) % 3], a + (i + 2) * 512);
                if (ROLE == 0 && i == 16) ldsm4(k0, kx + wq * 1024 + L16);
                if (ROLE == 0 && i == 17) ldsm4(k1, kx + wq * 1024 + 512 + L16);
                if (i == 0) { mma16z(c0, wA[0], b[0][0], b[0][1]); mma16z(c1, wA[1], b[0][2], b[0][3]); }
                else { mma16(c0, wA[2 * i], b[i % 3][0], b[i % 3][1]); mma16(c1, wA[2 * i + 1], b[i % 3][2], b[i % 3][3]); }
            }
        }
        const uint32_t p0 = pack_bf16(c0[0] + c1[0], c0[1] + c1[1]), p1 = pack_bf16(c0[2] + c1[2], c0[3] + c1[3]);
        if (!isv) {
            stsm2t(sb + S_QM + w * 256 + L16, p0, p1);
            bar_sync<NB_QK, 384>();
            if (ROLE == 0) {
                uint32_t q0[4], q1[4];
                ldsm4(q0, sb + S_QM + L16);
                ldsm4(q1, sb + S_QM + 512 + L16);
                mem_scores(sb, peerA, peerB, S_SP + j * 128 + wq * 256 + (L16 >> 2), q0, q1, k0, k1);
                mbar_arrive_if0(sb + B_S, L16);
            } else {
                if (s + 2 < XLIM) mbar_wait(sb + B_X + par * 8, ((s + 2) >> 1) & 1);
                x_write(sb, pk, s + 1, isv, w, L16);
                if (wq != 0) {
                    const int rt = (wq == 3) ? 0 : 1;
                    const uint32_t qa = sb + S_QX + par * 4096 + rt * 2048 + (L16 & 0x80) * 8 + (L16 & 0x170);
                    const uint32_t kb0 = (wq == 2 ? kx + 2048 : sb + S_KM) + L16;
                    const uint32_t kb1 = (wq == 2 ? kx + 3072 : kx) + L16;
                    const uint32_t kb2 = kx + 1024 + L16;
                    float a0[4], a1[4], a2[4];
#pragma unroll
                    for (int hf = 0; hf < 2; hf++) {
                        uint32_t qa0[4], qa1[4], b[4];
                        ldsm4(qa0, qa + hf * 512);
                        ldsm4(qa1, qa + hf * 512 + 128);
                        ldsm4(b, kb0 + hf * 512);
                        if (hf == 0) mma16z(a0, qa0, b[0], b[1]); else mma16(a0, qa0, b[0], b[1]);
                        mma16(a0, qa1, b[2], b[3]);
                        ldsm4(b, kb1 + hf * 512);
                        if (hf == 0) mma16z(a1, qa0, b[0], b[1]); else mma16(a1, qa0, b[0], b[1]);
                        mma16(a1, qa1, b[2], b[3]);
                        ldsm4(b, kb2 + hf * 512);
                        if (hf == 0) mma16z(a2, qa0, b[0], b[1]); else mma16(a2, qa0, b[0], b[1]);
                        mma16(a2, qa1, b[2], b[3]);
                    }
                    if (s < NSEG - 1) mbar_wait(sb + B_S, par);
                    const uint32_t dst = peerB + S_SX + par * 5120 + j * 128 + rt * 2560 + (L16 >> 2);
                    const uint32_t bar = peerB + B_SX + par * 8;
                    const uint32_t T0 = (wq == 2 ? 2 : 4) * 256, T1 = (wq == 2 ? 3 : 0) * 256;
                    st_async32(dst + T0, pack_f16_sat(a0[0], a0[1]), bar);
                    st_async32(dst + 1280 + T0, pack_f16_sat(a0[2], a0[3]), bar);
                    if (wq != 2) st_async32(dst + T1, pack_f16_sat(a1[0], a1[1]), bar);
                    st_async32(dst + 1280 + T1, pack_f16_sat(a1[2], a1[3]), bar);
                    if (wq == 1) st_async32(dst + 256, pack_f16_sat(a2[0], a2[1]), bar);
                    if (wq != 2) st_async32(dst + 1280 + 256, pack_f16_sat(a2[2], a2[3]), bar);
                }
            }
        } else {
            const uint32_t off = S_VM + (s & 3) * 2048 + w * 256 + (L16 >> 1);
            st_async64(peerA + off, p0, p1, peerA + B_S);
            st_async64(peerB + off, p0, p1, peerB + B_S);
            sts64(sb + off, p0, p1);
            __syncwarp();
            mbar_expect_if0(sb + B_S, 160, L16);
            if (ROLE == 2) bar_arrive<NB_P, 384>();
            else {
                if (s == NSEG - 1) break;
                x_write(sb, pk, s + 1, isv, w, L16);
                x_pv_both<NB_P, 384>(sb, s + 2, wq, L16);
                bar_arrive<NB_PV, 160>();
                if (s + 2 < XLIM) mbar_wait(sb + B_X + par * 8, ((s + 2) >> 1) & 1);
            }
        }
        if (WO_LOOP == 0 && s == NSEG - 1) break;
        if (WO_LOOP && ((s + 1) & (NSEG - 1)) <= 1) {
            if (s) break;
            load_wo(sb, w, L16, woA, woB);
        }
        if (wg == 0) {
            if (!isv) mbar_wait(sb + B_VX + par * 8, (s >> 1) & 1);
            uint32_t va[4][4];
            const uint32_t vx = sb + S_VX + (s & 3) * 8192 + wq * 2048 + L16;
            const uint32_t vm = sb + S_VM + (s & 3) * 2048 + wq * 512 + (L16 >> 1);
            lds128(va[0], vx);
            lds128(va[2], vx + 1024);
            mbar_wait(sb + B_S, par);
            __half2 hs[5];
            load_scores(sb + S_SP + L16, hs);
            float ev[10];
            softmax_exp(hs, ev);
            lds128(va[1], vx + 512);
            lds128(va[3], vx + 1536);
            uint32_t p[5];
#pragma unroll
            for (int i = 0; i < 5; i++) p[i] = pack_bf16(ev[2 * i], ev[2 * i + 1]);
            uint32_t vm0[2], vm1[2];
            const uint32_t ones[4] = {ONES, ONES, ONES, ONES};
            float sum[4], o0[4], o1[4];
            mma16z(o0, va[0], p[0], p[1]);
            mma16z(o1, va[2], p[0], p[1]);
            mma16z(sum, ones, p[0], p[1]);
            lds64(vm0, vm);
            lds64(vm1, vm + 256);
            mma16(o0, va[1], p[2], p[3]);
            mma16(o1, va[3], p[2], p[3]);
            mma16(sum, ones, p[2], p[3]);
            mma8(o0, vm0[0], vm0[1], p[4]);
            mma8(o1, vm1[0], vm1[1], p[4]);
            mma8(sum, ONES, ONES, p[4]);
            stsm4t(sb + S_OM + wq * 512 + L16, pack_bf16(o0[0], o0[1]), pack_bf16(o0[2], o0[3]), pack_bf16(o1[0], o1[1]), pack_bf16(o1[2], o1[3]));
            sts64(sb + S_SUM + wq * 256 + (L16 >> 1), __float_as_uint(sum[0]), __float_as_uint(sum[1]));
        }
        bar_sync<NB_O, 256>();
        {
            float a0[4], a1[4], e[4];
            float2 sc;
            float sr, r0, r1, rr;
#pragma unroll
            for (int i = 0; i < 4; i++) {
                uint32_t b[4];
                ldsm4(b, sb + S_OM + i * 512 + L16);
                if (i == 0) {
                    mma16z(a0, woA[0], b[0], b[1]); mma16z(a1, woA[1], b[2], b[3]);
                    mma_sp<0>(e, b, woB[0]);
                } else {
                    if (i == 1) { sc = lds64f(sb + S_SUM + (L16 >> 1)); sr = lds32f(sb + S_SUM + ((L16 >> 4) & 0x1C)); }
                    const uint32_t z = __float_as_uint(a0[0]) & zero;
                    mma16(a0, woA[2 * i], b[0], b[1]); mma16(a1, woA[2 * i + 1], b[2], b[3]);
                    mma_sp<1>(e, b, woB[i]);
                    if (i == RCP_AT) {
                        r0 = rcp(__uint_as_float(__float_as_uint(sc.x) | z));
                        r1 = rcp(__uint_as_float(__float_as_uint(sc.y) | z));
                        rr = rcp(__uint_as_float(__float_as_uint(sr) | z));
                    }
                }
            }
            asm volatile("" : "+r"(L16));
            char* const rslot = acc + (slot_off(s + 1) + j * 64 + w * 4096) + lane_off(L16);
            asm volatile("red.relaxed.gpu.global.add.noftz.v4.bf16x2 [%0], {%1,%2,%3,%4};"
                         ::"l"(rslot), "r"(pack_bf16((a0[0] + a1[0]) * r0, (a0[1] + a1[1]) * r1)), "r"(pack_bf16((a0[2] + a1[2]) * r0, (a0[3] + a1[3]) * r1)),
                           "r"(pack_bf16((e[0] + e[2]) * rr, (e[1] + e[3]) * rr)), "r"(0x3F80u) : "memory");
        }
        bar_arrive<NB_RED, 384>();
        if (wg == 0) {
            bar_sync<NB_X, 256>();
            wg_fence();
            x_project<0, HAND_AT>(xd, wA, xdesc + par * (XB_BYTES >> 4));
            bar_arrive<NB_L, 256>();
            x_project<HAND_AT, 36>(xd, wA, xdesc + par * (XB_BYTES >> 4));
            wg_commit();
        } else {
            bar_arrive<NB_X, 256>();
            if (s < NSEG - 2) {
                bar_sync<NB_L, 256>();
                wg_fence();
                x_project<0, 36>(xd, wA, xdesc + par * (XB_BYTES >> 4));
                wg_commit();
            } else {
                if (isv) {
                    x_pv_both<NB_T0, 256>(sb, NSEG - 3, wq, L16);
                    bar_sync<NB_AUX, 128>();
                    if (wq == 0 && L16 == 0) ox_store(sb, NSEG - 3, h);
                    __syncwarp();
                    x_pv_both<NB_T0 + 1, 256>(sb, NSEG - 2, wq, L16);
                    bar_sync<NB_AUX, 128>();
                    if (L16 == 0) {
                        if (wq == 0) ox_publish(NSEG - 3, h);
                        if (wq == 1) ox_store(sb, NSEG - 2, h);
                    }
                    __syncwarp();
                }
                wg_fence();
                x_project<0, 1>(xd, wA, xdesc);
                wg_commit();
            }
        }
        s++;
    }
    if (isv) {
        if (w == 5 && L16 == 0) ox_publish(NSEG - 2, h);
        __syncwarp();
        uint32_t pva[3][4], pk[8];
        x_pv_load(sb, NSEG - 1, w, L16, pva);
        bar_sync<NB_T0 + 2, 384>();
        x_pv_run(sb, NSEG - 1, pva, pk);
        x_pv_store(sb, NSEG - 1, w, L16, pk);
        bar_sync<NB_O, 256>();
        if (w == 0 && L16 == 0) { ox_store(sb, NSEG - 1, h); ox_publish(NSEG - 1, h); }
        __syncwarp();
    }
}

template <bool isv>
__device__ __forceinline__ void chain_aux(const uint32_t sb, const uint32_t lane16, const int wq, const uint32_t j, const uint32_t h,
                                          const uint32_t peerA, const uint32_t peerB, const CUtensorMap* tmWo, const CUtensorMap* tmX,
                                          char* const acc, const CUtensorMap* m0, const CUtensorMap* m1) {
    const int t = wq * 32 + (lane16 >> 4);
    cluster_arrive();
    {
        for (int c2 = 0; c2 < 3; c2++) mbar_arrive_if0(sb + B_M + c2 * 8, lane16);
        if (wq == 0) {
            if (PACE) {
                mbar_wait(sb + B_W, 0);
                if (t == 0) {
                    mbar_expect(sb + B_W + 16, 49152);
                    tma2d_once(sb + s_w(2), m0, h * 128 + (isv ? 0 : 64 * j), 384, sb + B_W + 16);
                    tma2d_once(sb + s_w(2) + 24576, m1, h * 128 + (isv ? 64 : 64 * j), 384, sb + B_W + 16);
                }
                __syncwarp();
            }
            bar_sync<NB_PRO, 288>();
            if (t == 0) {
                fence_async_smem();
                mbar_expect(sb + B_WO, 49152);
                for (int b = 0; b < 3; b++) tma2d(sb + S_WO + b * 16384, tmWo, 192 * j + 64 * b, h * 128, sb + B_WO);
            }
        } else if (wq == 3) {
            bulk_wait0();
            asm volatile("fence.proxy.async.global;" ::: "memory");
            __syncwarp();
            if (lane16 == 0) {
                if (h == 0) asm volatile("red.relaxed.gpu.global.add.u32 [%0], 1;" ::"l"(&g_zero_cnt) : "memory");
            }
            __syncwarp();
            unsigned c = 0;
            while (ld_acquire(&g_zero_cnt) < 3 && ++c < SPIN_LIM) __nanosleep(100);
            TSTAMP(76, 0);
            if (DEP_LATE) mbar_wait(sb + B_W + 16, 0);
            asm volatile("griddepcontrol.launch_dependents;" ::: "memory");
        }
        __syncwarp();
        cluster_wait();
        if (wq == 0) bar_sync<NB_AUX, 288>();
        if (t == 0) {
            fence_async_smem();
            if (!isv) mbar_expect(sb + B_VX, 8192);
            else {
                bulk_s2c(peerA + S_VX, sb + S_VX, 8192, peerA + B_VX);
                bulk_s2c(peerB + S_VX, sb + S_VX, 8192, peerB + B_VX);
            }
            mbar_expect(sb + B_X, XB_BYTES);
            tma3d(sb + S_XB, tmX, 0, 64, 0, sb + B_X);
        }
        __syncwarp();
    }
    TSTAMP(0, 0);
    uint32_t L16 = lane16;
    const char* slot = acc + wq * 4096 + lane_off(L16);
    float ev[10];
    int s = 0;
#pragma unroll 1
    while (true) {
        const uint32_t par = s & 1;
        asm volatile("" : "+r"(L16));
        if (!isv) {
            if (wq == 0) {
                bar_sync<NB_QK, 384>();
                uint32_t q0[4], q1[4], k0[4], k1[4];
                ldsm4(q0, sb + S_QM + L16);
                ldsm4(k0, sb + S_KM + L16);
                ldsm4(q1, sb + S_QM + 512 + L16);
                ldsm4(k1, sb + S_KM + 512 + L16);
                mem_scores(sb, peerA, peerB, S_SP + j * 128 + 1024 + (L16 >> 2), q0, q1, k0, k1);
                mbar_expect_if0(sb + B_S, 640 + 2048, L16);
            } else if (wq == 3) {
                bar_sync<NB_GO, 288>();
                const unsigned t = post_time(s, L16);
                bar_sync<NB_QK, 384>();
                if (j == 0 && s < NSEG - 1) {
                    if (LOOK_NS) __nanosleep(LOOK_NS);
                    plan_look(sb, s, L16, t);
                }
            } else {
                bar_arrive<NB_QK, 384>();
                if (wq == 2) {
                    if (L16 == 0) {
                        if (s + 3 < XLIM) mbar_expect(sb + B_X + (par ^ 1) * 8, XB_BYTES);
                        mbar_expect(sb + B_VX + (par ^ 1) * 8, 8192);
                        mbar_expect(sb + B_T, 4);
                        if (s == 2 && h == 0 && j == 0) g_zero_cnt = 0;
                        if (REFRESH && s + REFRESH == 2 * h) asm volatile("cp.async.bulk.prefetch.L2.global [%0], %1;" ::"l"(acc + h * 32768 + j * 16384), "r"(16384) : "memory");
                    }
                } else if (s + 3 < XLIM && j == 1) {
                    mbar_wait(sb + B_S, par);
                    if (XTMA_NS) __nanosleep(XTMA_NS);
                    if (L16 == 0) tma3d_mc(sb + S_XB + (par ^ 1) * XB_BYTES, tmX, 0, (s + 3) * SEG, 0, sb + B_X + (par ^ 1) * 8, 7);
                }
                __syncwarp();
            }
        } else {
            if (wq == 3) {
                bar_sync<NB_GO, 288>();
                post_time(s, L16);
            } else if (L16 == 0) {
                if (wq == 0) {
                    if (s >= 1) vx_fetch(sb, s, h);
                } else if (wq == 1) {
                    if (!PUB_EARLY && s >= 3 && s < NSEG - 1) ox_publish(s - 3, h);
                } else {
                    mbar_expect(sb + B_SX + par * 8, 3584);
                    mbar_expect(sb + B_T, 4);
                    if (s + 3 < XLIM) mbar_expect(sb + B_X + (par ^ 1) * 8, XB_BYTES);
                }
            }
            __syncwarp();
            if (s == NSEG - 1) break;
            if (s >= 1) mbar_wait(sb + B_SX + (par ^ 1) * 8, ((s - 1) >> 1) & 1);
            fence_async_smem();
            bar_sync<NB_P, 384>();
            if (wq == 0) { if (L16 == 0) vx_store(sb, s + 1, h); __syncwarp(); }
            x_scores(sb, s + 1, wq, L16, ev);
            if (wq == 1) {
                bar_sync<NB_PV, 160>();
                if (L16 == 0 && s >= 2) ox_store(sb, s - 2, h);
                __syncwarp();
            }
            x_probs(sb, s + 1, wq, L16, ev);
        }
        if (s == NSEG - 1) break;
        mbar_wait(sb + B_T, par);
        const unsigned tgt = __float_as_uint(lds32f(sb + S_TGT));
        if (isv && s == NSEG - 2) { fence_async_smem(); bar_arrive<NB_T0, 256>(); }
        bar_sync<NB_RED, 384>();
        if (isv) {
            if (wq == 1 && (PUB_EARLY || s == NSEG - 2)) {
                if (PUB_EARLY > 1) while ((int)(gtime() - tgt) < -PUB_EARLY) {}
                if (L16 == 0 && s >= 2) ox_publish(s - 2, h);
                __syncwarp();
            }
            if (s == NSEG - 2) {
                mbar_wait(sb + B_SX, (s >> 1) & 1);
                x_scores(sb, s, wq, L16, ev);
                x_probs(sb, s, wq, L16, ev);
                fence_async_smem();
                bar_arrive<NB_T0 + 1, 256>();
            }
        }
        asm volatile("" : "+r"(L16));
        slot += par ? 32768 - 512 : 512;
        while ((int)(gtime() - tgt) < 0) {}
        uint4 v[6];
        look(v, slot);
        s++;
        const uint32_t ma = sb + S_MEM + wq * 384 + L16;
        unsigned c = 0;
        constexpr int CW = 6 / NCH;
        int done = NCH;
#pragma unroll
        for (int k = 0; k < NCH; k++) {
            uint32_t bad = 0;
#pragma unroll
            for (int i = CW * k; i < CW * k + CW; i++) { stsm2t(ma + i * 1536, v[i].x, v[i].y); stsm1(ma + i * 1536 + 256, v[i].z); bad |= v[i].w ^ FULL_COUNT; }
            const bool again = __any_sync(0xffffffffu, bad != 0);
            mbar_arrive_if0(sb + B_M + k * 8, L16 | (uint32_t)again);
            if (again) { done = k; break; }
        }
        if (done < NCH) {
            uint32_t bad;
            do {
                look(v, slot);
                bad = 0;
#pragma unroll
                for (int i = 0; i < 6; i++) { stsm2t(ma + i * 1536, v[i].x, v[i].y); stsm1(ma + i * 1536 + 256, v[i].z); bad |= v[i].w ^ FULL_COUNT; }
            } while (++c < SPIN_LIM && __any_sync(0xffffffffu, bad != 0));
            __syncwarp();
#pragma unroll
            for (int k = 0; k < NCH; k++) if (k >= done) mbar_arrive_if0(sb + B_M + k * 8, L16);
        }
        TSTAMP(s, c | t_pack);
    }
    if (!isv) {
        mbar_wait(sb + B_VX + 8, ((NSEG - 1) >> 1) & 1);
        mbar_wait(sb + B_S, 1);
    } else {
        mbar_wait(sb + B_SX + 8, ((NSEG - 1) >> 1) & 1);
        x_scores(sb, NSEG - 1, wq, L16, ev);
        x_probs(sb, NSEG - 1, wq, L16, ev);
        fence_async_smem();
        bar_arrive<NB_T0 + 2, 384>();
        mbar_wait(sb + B_S, 1);
    }
}

__global__ void __launch_bounds__(384, 1)
chain_kernel(const __grid_constant__ CUtensorMap tmWq, const __grid_constant__ CUtensorMap tmWk, const __grid_constant__ CUtensorMap tmWv,
             const __grid_constant__ CUtensorMap tmWo, const __grid_constant__ CUtensorMap tmX, const bf16* __restrict__ mem0, char* const acc) {
    extern __shared__ __align__(1024) uint8_t smem[];
    const uint32_t sb = smem_u32(smem);
    const int tid = threadIdx.x;
    const uint32_t L16 = __shfl_sync(0xffffffffu, (tid & 31) * 16, tid & 31);
    const int w = __shfl_sync(0xffffffffu, tid >> 5, 0), wg = w >> 2, wq = w & 3;
    uint32_t j, h;
    asm("mov.u32 %0, %%cluster_ctarank;" : "=r"(j));
    asm("mov.u32 %0, %%clusterid.x;" : "=r"(h));
    const bool isv = (j == 2);
    const uint32_t peerA = mapa(sb, isv ? 0 : (j ^ 1)), peerB = mapa(sb, isv ? 1 : 2);
    if (DESCPF && w == 10 && L16 < 64) {
        const CUtensorMap* m = L16 == 0 ? &tmX : L16 == 16 ? (isv ? &tmWv : &tmWq) : L16 == 32 ? &tmWk : &tmWo;
        asm volatile("prefetch.tensormap [%0];" ::"l"(m) : "memory");
    }
    if (w == 11) {
        sts128(sb + S_ZERO + L16, 0, 0, 0, 0);
        sts128(sb + S_ZERO + 512 + L16, 0, 0, 0, 0);
        fence_async_smem();
        __syncwarp();
        const int i = L16 >> 4, kb = j * 11 + i;
        if (i < 11 && kb < 32) bulk_s2g(acc + h * 32768 + kb * 1024, sb + S_ZERO, 1024);
        if (i == 11) bulk_s2g(g_time + blockIdx.x * 64, sb + S_ZERO, 256);
        if (i == 12 && blockIdx.x == 0) bulk_s2g(g_flag, sb + S_ZERO, 1024);
        bulk_commit();
    }
    if (tid == 256) {
        for (int c = 0; c < 3; c++) { mbar_init(sb + B_W + 8 * c, 1); mbar_init(sb + B_M + 8 * c, 4); }
        mbar_init(sb + B_WO, 1); mbar_init(sb + B_T, 1);
        mbar_init(sb + B_X, 1); mbar_init(sb + B_X + 8, 1);
        mbar_init(sb + B_S, isv ? 8 : 5);
        mbar_init(sb + B_VX, 1); mbar_init(sb + B_VX + 8, 1);
        mbar_init(sb + B_SX, 1); mbar_init(sb + B_SX + 8, 1);
        asm volatile("fence.mbarrier_init.release.cluster;" ::: "memory");
        const CUtensorMap* m0 = isv ? &tmWv : &tmWq;
        const CUtensorMap* m1 = isv ? &tmWv : &tmWk;
        const int c0 = h * 128 + (isv ? 0 : 64 * j), c1 = h * 128 + (isv ? 64 : 64 * j);
        mbar_expect(sb + B_X, XB_BYTES);
        tma3d(sb + S_XB, &tmX, 0, 0, 0, sb + B_X);
        mbar_expect(sb + B_X + 8, XB_BYTES);
        tma3d(sb + S_XB + XB_BYTES, &tmX, 0, 32, 0, sb + B_X + 8);
#pragma unroll 1
        for (int c = 0; c < (PACE ? 2 : 3); c++) {
            mbar_expect(sb + B_W + 8 * c, 49152);
            tma2d_once(sb + s_w(c), m0, c0, c * 192, sb + B_W + 8 * c);
            tma2d_once(sb + s_w(c) + 24576, m1, c1, c * 192, sb + B_W + 8 * c);
        }
    } else if (tid < 256) {
        uint4 v0, v1, v2;
        v0 = *reinterpret_cast<const uint4*>(mem0 + (tid & 7) * DM + (tid >> 3) * 8);
        v1 = *reinterpret_cast<const uint4*>(mem0 + (tid & 7) * DM + (tid >> 3) * 8 + 256);
        if (tid < 64) v2 = *reinterpret_cast<const uint4*>(mem0 + (tid & 7) * DM + (tid >> 3) * 8 + 512);
        sts128(sb + S_MEM + tid * 16, v0.x, v0.y, v0.z, v0.w);
        sts128(sb + S_MEM + 4096 + tid * 16, v1.x, v1.y, v1.z, v1.w);
        if (tid < 64) sts128(sb + S_MEM + 8192 + tid * 16, v2.x, v2.y, v2.z, v2.w);
    }
    __syncthreads();
    if (wg == 2) {
        asm volatile("setmaxnreg.dec.sync.aligned.u32 %0;" ::"n"(REG_AUX));
        if (!isv) chain_aux<false>(sb, L16, wq, j, h, peerA, peerB, &tmWo, &tmX, acc, &tmWq, &tmWk);
        else chain_aux<true>(sb, L16, wq, j, h, peerA, peerB, &tmWo, &tmX, acc, &tmWv, &tmWv);
        __syncwarp();
        cluster_arrive(); cluster_wait();
        TSTAMP(65, 0);
    } else if (wg == 0) {
        asm volatile("setmaxnreg.inc.sync.aligned.u32 %0;" ::"n"(REG_MAIN0));
        if (!isv) chain_main<0>(sb, L16, wq, j, h, peerA, peerB, acc);
        else chain_main<2>(sb, L16, wq, j, h, peerA, peerB, acc);
        cluster_arrive(); cluster_wait();
    } else {
        asm volatile("setmaxnreg.inc.sync.aligned.u32 %0;" ::"n"(REG_MAIN1));
        if (!isv) chain_main<1>(sb, L16, wq, j, h, peerA, peerB, acc);
        else chain_main<3>(sb, L16, wq, j, h, peerA, peerB, acc);
        cluster_arrive(); cluster_wait();
    }
}

constexpr int NHELP = 36;
constexpr uint32_t H_U = 0;
constexpr uint32_t UT_PITCH = 4368;
constexpr uint32_t H_UT = 65536;
constexpr uint32_t KW_BYTES = 8320;
constexpr uint32_t H_KW = 135424;
constexpr uint32_t H_PAR = 201984;
constexpr uint32_t H_KD = 214272;
constexpr uint32_t H_IDX = 224640;
constexpr uint32_t H_STAGE = 0;
constexpr uint32_t H_RED = 196608;
constexpr uint32_t H_FIN = 212992;
constexpr uint32_t H_OWN = 214016;
constexpr uint32_t H_BAR = 229376;
constexpr uint32_t B_SMEM = H_BAR + 384;
constexpr uint32_t HB_U = H_BAR, HB_WO = H_BAR + 8, HB_EMPTY = H_BAR + 16, HB_FIN = H_BAR + 96, HB_FULL = H_BAR + 128, HB_SENT = H_BAR + 320;
constexpr int RING = 8;
__device__ __align__(1024) uint4 g_part[RING * 9 * 4 * 4 * 128];

__device__ __forceinline__ float2 cmul(float2 a, float2 b) { return make_float2(fmaf(a.x, b.x, -a.y * b.y), fmaf(a.x, b.y, a.y * b.x)); }
__device__ __forceinline__ float2 csqr(float2 a) { return make_float2(fmaf(a.x, a.x, -a.y * a.y), (a.x + a.x) * a.y); }
__device__ __forceinline__ float2 cexp(float zr, float zi, float p) {
    const float m = ex2(zr * p);
    const float r = zi * p;
    const float a = (fabsf(r) < 4194304.f ? r - ((r + 12582912.f) - 12582912.f) : 0.f) * 6.283185307179586f;
    return make_float2(m * __cosf(a), m * __sinf(a));
}
__device__ __forceinline__ uint32_t pack_f16(float lo, float hi) { uint32_t r; asm("cvt.rn.f16x2.f32 %0, %1, %2;" : "=r"(r) : "f"(hi), "f"(lo)); return r; }
__device__ __forceinline__ void mma16h(float* d, const uint32_t* a, uint32_t b0, uint32_t b1) {
    asm volatile("mma.sync.aligned.m16n8k16.row.col.f32.f16.f16.f32 {%0,%1,%2,%3},{%4,%5,%6,%7},{%8,%9},{%0,%1,%2,%3};"
                 : "+f"(d[0]), "+f"(d[1]), "+f"(d[2]), "+f"(d[3]) : "r"(a[0]), "r"(a[1]), "r"(a[2]), "r"(a[3]), "r"(b0), "r"(b1));
}
__device__ __forceinline__ float bf_round(float x) { return __bfloat162float(__float2bfloat16_rn(x)); }
__device__ __forceinline__ uint32_t lds32(uint32_t a) { uint32_t v; asm volatile("ld.shared.b32 %0,[%1];" : "=r"(v) : "r"(a) : "memory"); return v; }
__device__ __forceinline__ uint32_t lds16(uint32_t a) { uint16_t v; asm volatile("ld.shared.u16 %0,[%1];" : "=h"(v) : "r"(a) : "memory"); return v; }

__device__ __forceinline__ void s4d_kernel(uint32_t par, uint32_t kd, int d, int lane, const bf16* __restrict__ logA, const bf16* __restrict__ Aim,
                                           const bf16* __restrict__ Cre, const bf16* __restrict__ Cim, const bf16* __restrict__ logdt) {
    const float dt = bf_round(expf(__bfloat162float(logdt[d])));
    float4 q[4];
    float cmax = 0.f, last = 0.f;
#pragma unroll
    for (int i = 0; i < 4; i++) {
        const int n = d * NST + i * 32 + lane;
        q[i].x = -bf_round(expf(__bfloat162float(logA[n]))) * dt * 1.4426950408889634f;
        q[i].y = __bfloat162float(Aim[n]) * dt * 0.15915494309189535f;
        q[i].z = 2.f * (__bfloat162float(Cre[n]) * dt);
        q[i].w = 2.f * (__bfloat162float(Cim[n]) * dt);
        cmax = fmaxf(cmax, fmaxf(fabsf(q[i].z), fabsf(q[i].w)));
        const float2 e = cexp(q[i].x, q[i].y, 2048.f);
        last += q[i].z * e.x - q[i].w * e.y;
        const float2 w64 = cexp(q[i].x, q[i].y, 64.f);
        sts64(par + 2048 + (i * 32 + lane) * 8, __float_as_uint(w64.x), __float_as_uint(w64.y));
    }
#pragma unroll
    for (int o = 16; o; o >>= 1) { cmax = fmaxf(cmax, __shfl_xor_sync(0xffffffffu, cmax, o)); last += __shfl_xor_sync(0xffffffffu, last, o); }
    const float cs = __uint_as_float(max(__float_as_uint(cmax) & 0x7F800000u, 0x00800000u));
    const float ci = 1.f / cs;
#pragma unroll
    for (int i = 0; i < 4; i++) sts128(par + (i * 32 + lane) * 16, __float_as_uint(q[i].x), __float_as_uint(q[i].y), __float_as_uint(q[i].z * ci), __float_as_uint(q[i].w * ci));
    __syncwarp();
    float acc[5][4];
#pragma unroll
    for (int i = 0; i < 5; i++) acc[i][0] = acc[i][1] = acc[i][2] = acc[i][3] = 0.f;
    const float g = (float)(lane >> 2);
#pragma unroll 2
    for (int ks = 0; ks < 16; ks++) {
        uint32_t A[5][4], B[4][2];
#pragma unroll
        for (int hf = 0; hf < 2; hf++) {
            uint32_t r[4];
            const int n = ks * 8 + hf * 4 + (lane & 3);
            lds128(r, par + n * 16);
            const float2 w64 = lds64f(par + 2048 + n * 8);
            const float2 c = make_float2(__uint_as_float(r[2]), __uint_as_float(r[3]));
            float2 y = cexp(__uint_as_float(r[0]), __uint_as_float(r[1]), g);
#pragma unroll
            for (int k = 0; k < 4; k++) {
                const float2 cy = cmul(c, y);
                B[k][hf] = pack_f16(cy.x, -cy.y);
                if (k < 3) y = csqr(y);
            }
            const float2 xl = cmul(y, w64);
            float2 x0 = cmul(xl, w64), x1 = cmul(x0, w64);
            A[0][2 * hf] = pack_f16(y.x, y.y);
            A[0][2 * hf + 1] = pack_f16(xl.x, xl.y);
#pragma unroll
            for (int k = 0; k < 4; k++) {
                A[k + 1][2 * hf] = pack_f16(x0.x, x0.y);
                A[k + 1][2 * hf + 1] = pack_f16(x1.x, x1.y);
                if (k < 3) { x0 = csqr(x0); x1 = csqr(x1); }
            }
        }
        mma16h(acc[0], A[0], B[0][0], B[0][1]);
#pragma unroll
        for (int k = 0; k < 4; k++) mma16h(acc[k + 1], A[k + 1], B[k][0], B[k][1]);
    }
    __syncwarp();
#pragma unroll
    for (int i = 0; i < 5; i++) {
        sts32(kd + i * 256 + lane * 4, pack_bf16(acc[i][0] * cs, acc[i][1] * cs));
        sts32(kd + i * 256 + 128 + lane * 4, pack_bf16(acc[i][2] * cs, acc[i][3] * cs));
    }
    if (lane == 0) sts32(kd + 1280, pack_bf16(last, 0.f));
    __syncwarp();
}
__device__ __forceinline__ void s4d_expand(uint32_t kw, uint32_t kd, uint32_t idx, int lane) {
    if (lane < 16) sts32(kw + lane * 4, 0);
#pragma unroll 4
    for (int it = 0; it < 16; it++) {
        const int l = (it * 32 + lane) * 4;
        uint32_t j[2];
        lds64(j, idx + l * 2);
        const uint32_t jm = l ? lds16(idx + l * 2 - 2) : 1282;
        const uint32_t vm = lds16(kd + jm), v0 = lds16(kd + (j[0] & 0xFFFF)), v1 = lds16(kd + (j[0] >> 16)), v2 = lds16(kd + (j[1] & 0xFFFF)), v3 = lds16(kd + (j[1] >> 16));
        sts128(kw + 64 + l * 4, v0 | (vm << 16), v1 | (v0 << 16), v2 | (v1 << 16), v3 | (v2 << 16));
    }
    __syncwarp();
}

__device__ __forceinline__ void s4d_conv(uint32_t ut, uint32_t kw, int lane) {
    float acc[16][4];
#pragma unroll
    for (int i = 0; i < 16; i++) acc[i][0] = acc[i][1] = acc[i][2] = acc[i][3] = 0.f;
    const uint32_t ka = kw + 64 + ((lane >> 2) - 2 * (lane & 3)) * 4;
    const uint32_t ua = ut + 256 + lane * 8;
#pragma unroll 1
    for (int rho = 0; rho < 8; rho++) {
        uint32_t B[16][2];
#pragma unroll
        for (int q = 0; q < 16; q++) lds64(B[q], ua + q * 256 - rho * 32);
#pragma unroll
        for (int m = 0; m < 16; m++) {
            uint32_t A[4];
            const uint32_t x = ka + m * 512 + rho * 64;
            A[0] = lds32(x); A[1] = lds32(x + 32); A[2] = lds32(x - 32); A[3] = A[0];
#pragma unroll
            for (int i = m; i < 16; i++) mma16(acc[i], A, B[i - m][0], B[i - m][1]);
        }
    }
    __syncwarp();
    const uint32_t ya = ut + 256 + (lane & 7) * 32 + ((lane >> 3) & 1) * 16 + (lane >> 4) * 256;
#pragma unroll
    for (int i = 0; i < 16; i += 2)
        stsm4t(ya + i * 256, pack_bf16(acc[i][0], acc[i][1]), pack_bf16(acc[i][2], acc[i][3]),
               pack_bf16(acc[i + 1][0], acc[i + 1][1]), pack_bf16(acc[i + 1][2], acc[i + 1][3]));
}

__global__ void __launch_bounds__(384, 1)
helper_kernel(const __grid_constant__ CUtensorMap tmU, const __grid_constant__ CUtensorMap tmY, const __grid_constant__ CUtensorMap tmWo,
              const bf16* __restrict__ logA, const bf16* __restrict__ Aim, const bf16* __restrict__ Cre, const bf16* __restrict__ Cim,
              const bf16* __restrict__ logdt, const bf16* __restrict__ Dskip, bf16* __restrict__ out) {
    extern __shared__ __align__(1024) uint8_t smem[];
    const uint32_t sb = smem_u32(smem);
    const int tid = threadIdx.x, lane = tid & 31;
    const int w = __shfl_sync(0xffffffffu, tid >> 5, 0);
    const int d0 = blockIdx.x * 16;
    HSTAMP(0);
    if (tid == 0) {
        mbar_init(sb + HB_U, 1); mbar_init(sb + HB_WO, 1);
        for (int i = 0; i < 3; i++) mbar_init(sb + HB_EMPTY + 8 * i, 8);
        for (int i = 0; i < 24; i++) mbar_init(sb + HB_FULL + 8 * i, 1);
        for (int i = 0; i < 4; i++) { mbar_init(sb + HB_FIN + 8 * i, 2); mbar_init(sb + HB_SENT + 8 * i, 8); }
        fence_async_smem();
    }
    __syncthreads();
    if (tid == 352) {
        mbar_expect(sb + HB_U, 65536);
        for (int i = 0; i < 8; i++) { if (EVF & 2) tma2d_once(sb + H_U + i * 8192, &tmU, d0, i * 256, sb + HB_U); else tma2d(sb + H_U + i * 8192, &tmU, d0, i * 256, sb + HB_U); if (U_NS) __nanosleep(U_NS); }
    }
    __syncwarp();
    const int m = lane >> 3, r = lane & 7;
    const uint32_t kw = sb + H_KW + w * KW_BYTES;
    if (w < 8) {
        s4d_kernel(kw, sb + H_KD + w * 1296, d0 + w, lane, logA, Aim, Cre, Cim, logdt);
        bar_sync<1, 384>();
        HSTAMP(1);
        {
            uint4* dst = g_part + ((blockIdx.x % 9) * 16 + (w >> 2) * 8 + blockIdx.x / 9) * 128 + (tid & 127);
#pragma unroll 4
            for (int i = 0; i < RING * 2; i++) dst[(i >> 1) * (9 * 16 * 128) + (i & 1) * 512] = make_uint4(0, 0, 0, 0);
        }
        s4d_expand(kw, sb + H_KD + w * 1296, sb + H_IDX, lane);
        bar_arrive<2, 384>();
        s4d_conv(sb + H_UT + w * UT_PITCH, kw, lane);
        bar_sync<3, 384>();
        s4d_expand(kw, sb + H_KD + w * 1296, sb + H_IDX, lane);
        s4d_conv(sb + H_UT + (8 + w) * UT_PITCH, kw, lane);
    } else {
        for (int l = tid - 256; l < SEQ; l += 128) {
            const int jx = l < 128 ? l : (int)__bfloat16_as_ushort(__float2bfloat16_rn((float)l)) - (133 << 7);
            asm volatile("st.shared.u16 [%0], %1;" ::"r"(sb + H_IDX + l * 2), "h"((unsigned short)(jx * 2)) : "memory");
        }
        for (int i = tid - 256; i < 256; i += 128) sts128(sb + H_UT + (i >> 4) * UT_PITCH + (i & 15) * 16, 0, 0, 0, 0);
        mbar_wait(sb + HB_U, 0);
        const uint32_t src = sb + H_U + ((m & 1) * 8 + r) * 32 + (((m >> 1) ^ (r >> 2)) << 4);
        const uint32_t dst = sb + H_UT + 256 + (lane >> 2) * UT_PITCH + (lane & 3) * 8;
#pragma unroll 4
        for (int grp = w - 8; grp < 128; grp += 4) {
            uint32_t v[4];
            ldsm4t(v, src + grp * 512);
            sts64(dst + grp * 32, v[0], v[1]);
            sts64(dst + 8 * UT_PITCH + grp * 32, v[2], v[3]);
        }
        bar_arrive<1, 384>();
        bar_sync<2, 384>();
#pragma unroll 1
        for (int c = w - 8; c < 8; c += 4) s4d_kernel(sb + H_PAR + (w - 8) * 3072, sb + H_KD + c * 1296, d0 + 8 + c, lane, logA, Aim, Cre, Cim, logdt);
        bar_arrive<3, 384>();
    }
    __syncthreads();
    HSTAMP(2);
    const int cc = blockIdx.x % 9, kq = blockIdx.x / 9;
    {
        const __nv_bfloat162 D0 = *reinterpret_cast<const __nv_bfloat162*>(Dskip + d0 + (lane & 3) * 2);
        const __nv_bfloat162 D1 = *reinterpret_cast<const __nv_bfloat162*>(Dskip + d0 + 8 + (lane & 3) * 2);
        const uint32_t ua = sb + H_U + ((m & 1) * 8 + r) * 32 + (((m >> 1) ^ (r >> 2)) << 4);
        const uint32_t ya = sb + H_UT + 256 + ((m >> 1) * 8 + r) * UT_PITCH + (m & 1) * 16;
        for (int grp = w; grp < 128; grp += 12) {
            uint32_t u[4], y[4];
            ldsm4(u, ua + grp * 512);
            ldsm4t(y, ya + grp * 32);
#pragma unroll
            for (int i = 0; i < 4; i++) {
                const __nv_bfloat162 o = __hadd2_rn(*reinterpret_cast<__nv_bfloat162*>(&y[i]), __hmul2_rn(*reinterpret_cast<__nv_bfloat162*>(&u[i]), i < 2 ? D0 : D1));
                y[i] = *reinterpret_cast<const uint32_t*>(&o);
            }
            stsm4(ua + grp * 512, y[0], y[1], y[2], y[3]);
        }
        fence_async_smem();
        __syncthreads();
        if (tid == 0) {
            mbar_expect(sb + HB_WO, 131072);
            for (int i = 0; i < 8; i++) {
                if (YST) asm volatile("cp.async.bulk.tensor.2d.global.shared::cta.bulk_group [%0, {%1,%2}], [%3];" ::"l"(&tmY), "r"(DM + d0), "r"(i * 256), "r"(sb + H_U + i * 8192) : "memory");
                if (EVF & 2) tma2d_once(sb + 65536 + i * 16384, &tmWo, cc * 64, (kq * 8 + i) * 128, sb + HB_WO);
                else tma2d(sb + 65536 + i * 16384, &tmWo, cc * 64, (kq * 8 + i) * 128, sb + HB_WO);
                if (TRICKLE_NS) __nanosleep(TRICKLE_NS);
            }
            bulk_commit();
            asm volatile("cp.async.bulk.wait_group.read 0;" ::: "memory");
        }
    }
    __syncwarp();
    if (w < 8) {
        asm volatile("setmaxnreg.inc.sync.aligned.u32 208;");
        const int wg = w >> 2;
        uint32_t wo[32][4];
        mbar_wait_long(sb + HB_WO, 0);
        const uint32_t a = sb + 65536 + wg * 65536 + ((m >> 1) * 8 + r) * 128 + (((2 * (w & 3) + (m & 1)) ^ r) << 4);
#pragma unroll
        for (int i = 0; i < 32; i++) ldsm4t(wo[i], a + i * 2048);
        __syncthreads();
        HSTAMP(3);
        const int t = tid & 127;
        int st = 0, ph = 0;
#pragma unroll 1
        for (int s = 0; s < NSEG; s++) {
            const uint32_t desc = (((sb + H_STAGE + st * 65536 + wg * 32768) & 0x3FFFF) >> 4) | (8u << 16);
            float d[16];
#pragma unroll
            for (int q = 0; q < HSPLIT; q++) {
                mbar_wait_long(sb + HB_FULL + ((st * 2 + wg) * 4 + q) * 8, ph);
                wg_fence();
#pragma unroll
                for (int i = q * (32 / HSPLIT); i < (q + 1) * (32 / HSPLIT); i++) {
                    if (i == 0) wg_rs_n32<0, 16, 1>(d, wo[i], desc); else wg_rs_n32<1, 16, 1>(d, wo[i], desc + i * 64);
                }
                wg_commit();
            }
            if (s >= 4) mbar_wait_long(sb + HB_FIN + (s & 3) * 8, ((s - 4) >> 2) & 1);
            const uint32_t ra = sb + H_RED + (s & 1) * 8192 + t * 16;
            uint4* dst = g_part + (((s % RING) * 9 + cc) * 16 + wg * 8 + kq) * 128 + t;
            const uint32_t own = sb + H_OWN + (s & 3) * 2048 + t * 16;
            wg_wait<0>();
#pragma unroll
            for (int i = 0; i < 8; i++) { const float a0 = d[i], a1 = d[8 + i]; d[i] = wg ? a1 : a0; d[8 + i] = wg ? a0 : a1; }
#pragma unroll
            for (int i = 0; i < 2; i++) sts128(ra + wg * 4096 + i * 2048, __float_as_uint(d[8 + 4 * i]), __float_as_uint(d[9 + 4 * i]), __float_as_uint(d[10 + 4 * i]), __float_as_uint(d[11 + 4 * i]));
            mbar_arrive_if0(sb + HB_EMPTY + st * 8, lane);
            bar_sync<4, 256>();
            uint32_t p[8];
#pragma unroll
            for (int i = 0; i < 2; i++) lds128(p + 4 * i, ra + (wg ^ 1) * 4096 + i * 2048);
#pragma unroll
            for (int i = 0; i < 2; i++) {
#pragma unroll
                for (int k = 4 * i; k < 4 * i + 4; k++) p[k] = ((__float_as_uint(__uint_as_float(p[k]) + d[k]) + 64) & ~127u) | (s + 1);
                asm volatile("{.reg .pred q; setp.eq.u32 q, %6, %7;\n"
                             "@!q st.relaxed.gpu.global.v4.u32 [%0], {%2,%3,%4,%5};\n"
                             "@q st.shared.v4.u32 [%1], {%2,%3,%4,%5};}"
                             ::"l"(dst + i * 512), "r"(own), "r"(p[4 * i]), "r"(p[4 * i + 1]), "r"(p[4 * i + 2]), "r"(p[4 * i + 3]), "r"(kq), "r"(2 * wg + i) : "memory");
            }
            __syncwarp();
            mbar_arrive_if0(sb + HB_SENT + (s & 3) * 8, lane);
            HSTAMP4(s);
            if (++st == 3) { st = 0; ph ^= 1; }
        }
        if (tid == 0) bulk_wait0();
    } else {
        asm volatile("setmaxnreg.dec.sync.aligned.u32 88;");
        __syncthreads();
        if (w == 8) {
            const uint64_t pol = evict_first();
            int st = 0, ph = 1, ready = 0;
            for (int s = 0; s < NSEG; s++) {
                unsigned c = 0;
                while (ready <= s) {
                    const unsigned f = ld_acquire(&g_flag[kq * NSEG + min(s + (lane & 3), NSEG - 1)]);
                    ready = s + __ffs(~(__ballot_sync(0xffffffffu, f >= 8) & 15)) - 1;
                    if (++c >= LONG_LIM) break;
                    if (ready <= s && FLAG_NS) __nanosleep(FLAG_NS);
                }
                __syncwarp();
                if (lane == 0) {
                    asm volatile("fence.proxy.async.global;" ::: "memory");
                    HSTAMP3(s);
                    mbar_wait_long(sb + HB_EMPTY + st * 8, ph);
#pragma unroll
                    for (int k = 0; k < 2 * HSPLIT; k++) {
                        const int g = k & 1, q = k >> 1;
                        constexpr uint32_t bytes = 32768 / HSPLIT;
                        const uint32_t bar = sb + HB_FULL + ((st * 2 + g) * 4 + q) * 8;
                        mbar_expect(bar, bytes);
                        asm volatile("cp.async.bulk.shared::cluster.global.mbarrier::complete_tx::bytes.L2::cache_hint [%0], [%1], %2, [%3], %4;"
                                     ::"r"(sb + H_STAGE + st * 65536 + g * 32768 + q * bytes), "l"(g_ox + (s * NH + kq * 8 + g * 4) * 512 + q * (bytes / 16)), "r"(bytes), "r"(bar), "l"(pol) : "memory");
                    }
                }
                __syncwarp();
                if (++st == 3) { st = 0; ph ^= 1; }
            }
        } else if (w < 11) {
            const int f = w - 9;
            const uint32_t fa = sb + H_FIN + f * 512;
            for (int s = 0; s < NSEG; s++) {
                mbar_wait_long(sb + HB_SENT + (s & 3) * 8, (s >> 2) & 1);
                const uint4* src = g_part + (((s % RING) * 9 + cc) * 16 + kq * 4) * 128 + f * 64 + lane;
                uint4 v[8];
                lds128(&v[6].x, sb + H_OWN + (s & 3) * 2048 + (f * 64 + lane) * 16);
                lds128(&v[7].x, sb + H_OWN + (s & 3) * 2048 + (f * 64 + 32 + lane) * 16);
                if (FIN0_NS) __nanosleep(FIN0_NS);
                unsigned c = 0;
                while (true) {
                    uint32_t bad = 0;
#pragma unroll
                    for (int i = 0; i < 6; i++) v[i] = ld_poll(src + ((kq + 1 + (i >> 1)) & 3) * 128 + (i & 1) * 32);
#pragma unroll
                    for (int i = 0; i < 6; i++) bad |= (v[i].x ^ (s + 1)) | (v[i].y ^ (s + 1)) | (v[i].z ^ (s + 1)) | (v[i].w ^ (s + 1));
                    if (!__any_sync(0xffffffffu, (bad & 127) != 0) || ++c >= LONG_LIM) break;
                    if (FIN_NS) __nanosleep(FIN_NS);
                }
                mbar_arrive_if0(sb + HB_FIN + (s & 3) * 8, lane);
                uint32_t pk[4];
#pragma unroll
                for (int u = 0; u < 2; u++) {
                    float o[4] = {0.f, 0.f, 0.f, 0.f};
#pragma unroll
                    for (int k = 0; k < 4; k++) {
                        o[0] += __uint_as_float(v[2 * k + u].x & ~127u); o[1] += __uint_as_float(v[2 * k + u].y & ~127u);
                        o[2] += __uint_as_float(v[2 * k + u].z & ~127u); o[3] += __uint_as_float(v[2 * k + u].w & ~127u);
                    }
                    pk[2 * u] = pack_bf16(o[0], o[1]); pk[2 * u + 1] = pack_bf16(o[2], o[3]);
                }
                stsm4t(fa + r * 64 + ((m ^ (r >> 1)) << 4), pk[0], pk[1], pk[2], pk[3]);
                __syncwarp();
                uint32_t o4[4];
                lds128(o4, fa + (lane >> 2) * 64 + (((lane & 3) ^ (lane >> 3)) << 4));
                *reinterpret_cast<uint4*>(out + (s * SEG + kq * 8 + (lane >> 2)) * OUTW + cc * 64 + f * 32 + (lane & 3) * 8) = make_uint4(o4[0], o4[1], o4[2], o4[3]);
                __syncwarp();
                HSTAMP2(s);
            }
            asm volatile("griddepcontrol.wait;" ::: "memory");
        }
    }
}

typedef CUresult (*EncodeFn)(CUtensorMap*, CUtensorMapDataType, cuuint32_t, void*, const cuuint64_t*, const cuuint64_t*, const cuuint32_t*,
                             const cuuint32_t*, CUtensorMapInterleave, CUtensorMapSwizzle, CUtensorMapL2promotion, CUtensorMapFloatOOBfill);

void make_map(EncodeFn fn, CUtensorMap* m, const void* p, int rank, const cuuint64_t* dims, const cuuint64_t* strides, const cuuint32_t* box,
              CUtensorMapSwizzle sw = CU_TENSOR_MAP_SWIZZLE_128B, CUtensorMapL2promotion pr = CU_TENSOR_MAP_L2_PROMOTION_L2_128B) {
    const cuuint32_t es[3] = {1, 1, 1};
    fn(m, CU_TENSOR_MAP_DATA_TYPE_BFLOAT16, rank, const_cast<void*>(p), dims, strides, box, es, CU_TENSOR_MAP_INTERLEAVE_NONE,
       sw, pr, CU_TENSOR_MAP_FLOAT_OOB_FILL_NONE);
}

}

extern "C" void kernel_launch(void* const* d_in, const int* in_sizes, int n_in, void* d_out, int out_size) {
    const bf16* x = (const bf16*)d_in[0];
    const bf16* mem0 = (const bf16*)d_in[1];
    const bf16* Wo = (const bf16*)d_in[5];
    bf16* out = (bf16*)d_out;

    static EncodeFn enc = nullptr;
    static char* acc = nullptr;
    if (!enc) {
        void* p = nullptr;
        cudaGetSymbolAddress(&p, g_acc);
        acc = reinterpret_cast<char*>((reinterpret_cast<uintptr_t>(p) + 32767) & ~(uintptr_t)32767);
        void* fn = nullptr;
        cudaDriverEntryPointQueryResult st;
        cudaGetDriverEntryPoint("cuTensorMapEncodeTiled", &fn, cudaEnableDefault, &st);
        enc = (EncodeFn)fn;
        cudaFuncSetAttribute(chain_kernel, cudaFuncAttributeMaxDynamicSharedMemorySize, A_SMEM);
        cudaFuncSetAttribute(helper_kernel, cudaFuncAttributeMaxDynamicSharedMemorySize, B_SMEM);
    }
    CUtensorMap tmW[3], tmWo, tmX;
    {
        const cuuint64_t dims[2] = {4096, 576}, str[1] = {8192};
        const cuuint32_t box[2] = {64, 192};
        for (int i = 0; i < 3; i++) make_map(enc, &tmW[i], d_in[2 + i], 2, dims, str, box, CU_TENSOR_MAP_SWIZZLE_128B, W_PROMO);
    }
    {
        const cuuint64_t dims[2] = {576, 4096}, str[1] = {1152};
        const cuuint32_t box[2] = {64, 128};
        make_map(enc, &tmWo, Wo, 2, dims, str, box);
    }
    {
        const cuuint64_t dims[3] = {64, 2048, 9}, str[2] = {1152, 128};
        const cuuint32_t box[3] = {64, 32, 9};
        make_map(enc, &tmX, x, 3, dims, str, box);
    }
    CUtensorMap tmU, tmY;
    {
        const cuuint64_t dimsU[2] = {576, 2048}, strU[1] = {1152}, dimsY[2] = {1152, 2048}, strY[1] = {2304};
        const cuuint32_t box[2] = {16, 256};
        make_map(enc, &tmU, d_in[7], 2, dimsU, strU, box, CU_TENSOR_MAP_SWIZZLE_32B);
        make_map(enc, &tmY, out, 2, dimsY, strY, box, CU_TENSOR_MAP_SWIZZLE_32B, CU_TENSOR_MAP_L2_PROMOTION_NONE);
    }
    cudaStream_t st = cudaStreamPerThread;
    {
        cudaLaunchConfig_t cfg = {};
        cfg.gridDim = dim3(96); cfg.blockDim = dim3(384); cfg.dynamicSmemBytes = A_SMEM; cfg.stream = st;
        cudaLaunchAttribute at[1];
        at[0].id = cudaLaunchAttributeClusterDimension;
        at[0].val.clusterDim.x = 3; at[0].val.clusterDim.y = 1; at[0].val.clusterDim.z = 1;
        cfg.attrs = at; cfg.numAttrs = 1;
        cudaLaunchKernelEx(&cfg, chain_kernel, tmW[0], tmW[1], tmW[2], tmWo, tmX, mem0, acc);
    }
    {
        cudaLaunchConfig_t cfg = {};
        cfg.gridDim = dim3(NHELP); cfg.blockDim = dim3(384); cfg.dynamicSmemBytes = B_SMEM; cfg.stream = st;
        cudaLaunchAttribute at[1];
        at[0].id = cudaLaunchAttributeProgrammaticStreamSerialization;
        at[0].val.programmaticStreamSerializationAllowed = 1;
        cfg.attrs = at; cfg.numAttrs = 1;
        cudaLaunchKernelEx(&cfg, helper_kernel, tmU, tmY, tmWo, (const bf16*)d_in[8], (const bf16*)d_in[9], (const bf16*)d_in[10],
                           (const bf16*)d_in[11], (const bf16*)d_in[12], (const bf16*)d_in[13], out);
    }
}
```

```cpp
#include <cuda_runtime.h>
#include <cuda_bf16.h>
#include <cuda_fp16.h>
#include <cuda.h>
#include <stdint.h>

typedef __nv_bfloat16 bf16;

#define WAITFORM 2
#define EVF 15
namespace {

constexpr int DM = 576, NH = 32, DH = 128, SEG = 32, NSEG = 64, SEQ = 2048, NST = 128;
constexpr int OUTW = 2 * DM;
constexpr unsigned SPIN_LIM = 1u << 15;

__device__ __align__(1024) uint4 g_acc[33 * 2048];
__device__ __align__(128) unsigned g_time[NSEG * 96];
__device__ __align__(1024) uint4 g_ox[NSEG * NH * 512];
__device__ __align__(1024) uint4 g_vx[NH * 2 * 512];
__device__ __align__(128) unsigned g_flag[NSEG * 4];
__device__ unsigned g_zero_cnt;

__device__ __forceinline__ uint32_t smem_u32(const void* p) { return (uint32_t)__cvta_generic_to_shared(p); }
__device__ __forceinline__ unsigned clk() { unsigned c; asm volatile("mov.u32 %0, %%clock;" : "=r"(c)::"memory"); return c; }
__device__ __forceinline__ unsigned gtime() { unsigned t; asm volatile("mov.u32 %0, %%globaltimer_lo;" : "=r"(t)::"memory"); return t; }
__device__ __forceinline__ uint32_t slot_off(int s) { return (s >> 1) * 32768 + (s & 1) * 512; }
__device__ __forceinline__ uint32_t lane_off(uint32_t L16) { return (L16 & 0x180) * 8 + (L16 & 0x40) * 4 + (L16 & 0x30); }
__device__ __forceinline__ uint32_t mapa(uint32_t a, uint32_t r) { uint32_t o; asm("mapa.shared::cluster.u32 %0, %1, %2;" : "=r"(o) : "r"(a), "r"(r)); return o; }
__device__ __forceinline__ void mbar_init(uint32_t b, uint32_t n) { asm volatile("mbarrier.init.shared::cta.b64 [%0], %1;" ::"r"(b), "r"(n) : "memory"); }
__device__ __forceinline__ void mbar_arrive(uint32_t b) { asm volatile("mbarrier.arrive.shared::cta.b64 _, [%0];" ::"r"(b) : "memory"); }
__device__ __forceinline__ void mbar_expect(uint32_t b, uint32_t tx) { asm volatile("mbarrier.arrive.expect_tx.shared::cta.b64 _, [%0], %1;" ::"r"(b), "r"(tx) : "memory"); }
__device__ __forceinline__ bool mbar_try(uint32_t b, uint32_t par) {
    uint32_t ok;
    asm volatile("{.reg .pred p; mbarrier.try_wait.parity.shared::cta.b64 p, [%1], %2; selp.u32 %0, 1, 0, p;}" : "=r"(ok) : "r"(b), "r"(par) : "memory");
    return ok;
}
__device__ __forceinline__ bool mbar_test(uint32_t b, uint32_t par) {
    uint32_t ok;
    asm volatile("{.reg .pred p; mbarrier.test_wait.parity.shared::cta.b64 p, [%1], %2; selp.u32 %0, 1, 0, p;}" : "=r"(ok) : "r"(b), "r"(par) : "memory");
    return ok;
}
__device__ __forceinline__ void mbar_wait(uint32_t b, uint32_t par) {
    asm volatile("{.reg .pred p, q; .reg .u32 c; mov.u32 c, 0;\n"
                 "W: add.u32 c, c, 1; setp.ge.u32 q, c, %2;\n @q bra D;\n mbarrier.try_wait.parity.shared::cta.b64 p, [%0], %1;\n"
                 "@!p bra W;\n D:\n}" ::"r"(b), "r"(par), "n"(SPIN_LIM) : "memory");
}
constexpr unsigned LONG_LIM = 1u << 17;
__device__ __forceinline__ void mbar_wait_long(uint32_t b, uint32_t par) {
    asm volatile("{.reg .pred p, q; .reg .u32 c; mov.u32 c, 0;\n"
                 "W: mbarrier.try_wait.parity.shared::cta.b64 p, [%0], %1;\n"
                 "@p bra D;\n add.u32 c, c, 1; setp.lt.u32 q, c, %2;\n @q bra W;\n D:\n}" ::"r"(b), "r"(par), "n"(LONG_LIM) : "memory");
}
__device__ __forceinline__ void cluster_sync() { asm volatile("barrier.cluster.arrive.aligned; barrier.cluster.wait.aligned;" ::: "memory"); }
__device__ __forceinline__ void fence_async_smem() { asm volatile("fence.proxy.async.shared::cta;" ::: "memory"); }
__device__ __forceinline__ void ldsm4(uint32_t* r, uint32_t a) { asm volatile("ldmatrix.sync.aligned.m8n8.x4.shared.b16 {%0,%1,%2,%3},[%4];" : "=r"(r[0]), "=r"(r[1]), "=r"(r[2]), "=r"(r[3]) : "r"(a) : "memory"); }
__device__ __forceinline__ void ldsm4t(uint32_t* r, uint32_t a) { asm volatile("ldmatrix.sync.aligned.m8n8.x4.trans.shared.b16 {%0,%1,%2,%3},[%4];" : "=r"(r[0]), "=r"(r[1]), "=r"(r[2]), "=r"(r[3]) : "r"(a) : "memory"); }
__device__ __forceinline__ void stsm1(uint32_t a, uint32_t r0) { asm volatile("stmatrix.sync.aligned.m8n8.x1.shared.b16 [%0],{%1};" ::"r"(a), "r"(r0) : "memory"); }
__device__ __forceinline__ void stsm2t(uint32_t a, uint32_t r0, uint32_t r1) { asm volatile("stmatrix.sync.aligned.m8n8.x2.trans.shared.b16 [%0],{%1,%2};" ::"r"(a), "r"(r0), "r"(r1) : "memory"); }
__device__ __forceinline__ void stsm4t(uint32_t a, uint32_t r0, uint32_t r1, uint32_t r2, uint32_t r3) { asm volatile("stmatrix.sync.aligned.m8n8.x4.trans.shared.b16 [%0],{%1,%2,%3,%4};" ::"r"(a), "r"(r0), "r"(r1), "r"(r2), "r"(r3) : "memory"); }
__device__ __forceinline__ void stsm4(uint32_t a, uint32_t r0, uint32_t r1, uint32_t r2, uint32_t r3) { asm volatile("stmatrix.sync.aligned.m8n8.x4.shared.b16 [%0],{%1,%2,%3,%4};" ::"r"(a), "r"(r0), "r"(r1), "r"(r2), "r"(r3) : "memory"); }
__device__ __forceinline__ void sts32(uint32_t a, uint32_t v) { asm volatile("st.shared.b32 [%0], %1;" ::"r"(a), "r"(v) : "memory"); }
__device__ __forceinline__ void sts64(uint32_t a, uint32_t x, uint32_t y) { asm volatile("st.shared.v2.b32 [%0], {%1,%2};" ::"r"(a), "r"(x), "r"(y) : "memory"); }
__device__ __forceinline__ void sts128(uint32_t a, uint32_t x, uint32_t y, uint32_t z, uint32_t w) { asm volatile("st.shared.v4.b32 [%0], {%1,%2,%3,%4};" ::"r"(a), "r"(x), "r"(y), "r"(z), "r"(w) : "memory"); }
__device__ __forceinline__ void lds64(uint32_t* r, uint32_t a) { asm volatile("ld.shared.v2.b32 {%0,%1},[%2];" : "=r"(r[0]), "=r"(r[1]) : "r"(a) : "memory"); }
__device__ __forceinline__ float2 lds64f(uint32_t a) { float2 v; asm volatile("ld.shared.v2.f32 {%0,%1},[%2];" : "=f"(v.x), "=f"(v.y) : "r"(a) : "memory"); return v; }
__device__ __forceinline__ void lds128(uint32_t* r, uint32_t a) { asm volatile("ld.shared.v4.b32 {%0,%1,%2,%3},[%4];" : "=r"(r[0]), "=r"(r[1]), "=r"(r[2]), "=r"(r[3]) : "r"(a) : "memory"); }
__device__ __forceinline__ void st_async64(uint32_t a, uint32_t x, uint32_t y, uint32_t bar) {
    asm volatile("st.async.weak.shared::cluster.mbarrier::complete_tx::bytes.v2.b32 [%0], {%1,%2}, [%3];" ::"r"(a), "r"(x), "r"(y), "r"(bar) : "memory");
}
__device__ __forceinline__ void st_async32(uint32_t a, uint32_t x, uint32_t bar) {
    asm volatile("st.async.weak.shared::cluster.mbarrier::complete_tx::bytes.b32 [%0], %1, [%2];" ::"r"(a), "r"(x), "r"(bar) : "memory");
}
__device__ __forceinline__ void ldsm2(uint32_t* r, uint32_t a) { asm volatile("ldmatrix.sync.aligned.m8n8.x2.shared.b16 {%0,%1},[%2];" : "=r"(r[0]), "=r"(r[1]) : "r"(a) : "memory"); }
__device__ __forceinline__ uint32_t pack_f16_sat(float lo, float hi) { uint32_t r; asm("cvt.rn.satfinite.f16x2.f32 %0, %1, %2;" : "=r"(r) : "f"(hi), "f"(lo)); return r; }
__device__ __forceinline__ __half2 as_h2(uint32_t x) { return *reinterpret_cast<__half2*>(&x); }
__device__ __forceinline__ uint32_t as_u32(__half2 x) { return *reinterpret_cast<uint32_t*>(&x); }
__device__ __forceinline__ uint32_t pack_bf16(float lo, float hi) { uint32_t r; asm("cvt.rn.bf16x2.f32 %0, %1, %2;" : "=r"(r) : "f"(hi), "f"(lo)); return r; }
__device__ __forceinline__ float ex2(float x) { float r; asm("ex2.approx.ftz.f32 %0, %1;" : "=f"(r) : "f"(x)); return r; }
__device__ __forceinline__ float rcp(float x) { float r; asm("rcp.approx.ftz.f32 %0, %1;" : "=f"(r) : "f"(x)); return r; }
__device__ __forceinline__ void mma16(float* d, const uint32_t* a, uint32_t b0, uint32_t b1) {
    asm volatile("mma.sync.aligned.m16n8k16.row.col.f32.bf16.bf16.f32 {%0,%1,%2,%3},{%4,%5,%6,%7},{%8,%9},{%0,%1,%2,%3};"
                 : "+f"(d[0]), "+f"(d[1]), "+f"(d[2]), "+f"(d[3]) : "r"(a[0]), "r"(a[1]), "r"(a[2]), "r"(a[3]), "r"(b0), "r"(b1));
}
__device__ __forceinline__ void mma16z(float* d, const uint32_t* a, uint32_t b0, uint32_t b1) {
    asm volatile("mma.sync.aligned.m16n8k16.row.col.f32.bf16.bf16.f32 {%0,%1,%2,%3},{%4,%5,%6,%7},{%8,%9},{%10,%10,%10,%10};"
                 : "=f"(d[0]), "=f"(d[1]), "=f"(d[2]), "=f"(d[3]) : "r"(a[0]), "r"(a[1]), "r"(a[2]), "r"(a[3]), "r"(b0), "r"(b1), "f"(0.f));
}
__device__ __forceinline__ void mma8(float* d, uint32_t a0, uint32_t a1, uint32_t b0) {
    asm volatile("mma.sync.aligned.m16n8k8.row.col.f32.bf16.bf16.f32 {%0,%1,%2,%3},{%4,%5},{%6},{%0,%1,%2,%3};"
                 : "+f"(d[0]), "+f"(d[1]), "+f"(d[2]), "+f"(d[3]) : "r"(a0), "r"(a1), "r"(b0));
}
template <int ACC>
__device__ __forceinline__ void mma_sp(float* d, const uint32_t* a, const uint32_t* b) {
    if (ACC)
        asm volatile("mma.sp::ordered_metadata.sync.aligned.m16n8k32.row.col.f32.bf16.bf16.f32 {%0,%1,%2,%3},{%4,%5,%6,%7},{%8,%9,%10,%11},{%0,%1,%2,%3},%12,0x0;"
                     : "+f"(d[0]), "+f"(d[1]), "+f"(d[2]), "+f"(d[3])
                     : "r"(a[0]), "r"(a[1]), "r"(a[2]), "r"(a[3]), "r"(b[0]), "r"(b[1]), "r"(b[2]), "r"(b[3]), "r"(0xEEEE4444u));
    else
        asm volatile("mma.sp::ordered_metadata.sync.aligned.m16n8k32.row.col.f32.bf16.bf16.f32 {%0,%1,%2,%3},{%4,%5,%6,%7},{%8,%9,%10,%11},{%13,%13,%13,%13},%12,0x0;"
                     : "=f"(d[0]), "=f"(d[1]), "=f"(d[2]), "=f"(d[3])
                     : "r"(a[0]), "r"(a[1]), "r"(a[2]), "r"(a[3]), "r"(b[0]), "r"(b[1]), "r"(b[2]), "r"(b[3]), "r"(0xEEEE4444u), "f"(0.f));
}
__device__ __forceinline__ void mbar_arrive_if0(uint32_t b, uint32_t z) { asm volatile("{.reg .pred p; setp.eq.u32 p, %1, 0; @p mbarrier.arrive.shared::cta.b64 _, [%0];}" ::"r"(b), "r"(z) : "memory"); }
__device__ __forceinline__ void mbar_expect_if0(uint32_t b, uint32_t tx, uint32_t z) { asm volatile("{.reg .pred p; setp.eq.u32 p, %2, 0; @p mbarrier.arrive.expect_tx.shared::cta.b64 _, [%0], %1;}" ::"r"(b), "r"(tx), "r"(z) : "memory"); }
__device__ __forceinline__ float lds32f(uint32_t a) { float v; asm volatile("ld.shared.f32 %0,[%1];" : "=f"(v) : "r"(a) : "memory"); return v; }
__device__ __forceinline__ void wg_fence() { asm volatile("wgmma.fence.sync.aligned;" ::: "memory"); }
__device__ __forceinline__ void wg_commit() { asm volatile("wgmma.commit_group.sync.aligned;" ::: "memory"); }
template <int N> __device__ __forceinline__ void wg_wait() { asm volatile("wgmma.wait_group.sync.aligned %0;" ::"n"(N) : "memory"); }
__device__ __forceinline__ void delay(unsigned n) { if (n) { const unsigned t0 = clk(); while (clk() - t0 < n) {} } }
template <int ACC, uint32_t DHI = 0x40000040u, int TB = 0>
__device__ __forceinline__ void wg_rs_n32(float* d, const uint32_t* a, uint32_t dlo) {
    if (ACC)
        asm volatile("{.reg .b64 db; mov.b64 db, {%20, %21};\n"
                     "wgmma.mma_async.sync.aligned.m64n32k16.f32.bf16.bf16 {%0,%1,%2,%3,%4,%5,%6,%7,%8,%9,%10,%11,%12,%13,%14,%15},{%16,%17,%18,%19},db,1,1,1,%22;}"
                     : "+f"(d[0]), "+f"(d[1]), "+f"(d[2]), "+f"(d[3]), "+f"(d[4]), "+f"(d[5]), "+f"(d[6]), "+f"(d[7]),
                       "+f"(d[8]), "+f"(d[9]), "+f"(d[10]), "+f"(d[11]), "+f"(d[12]), "+f"(d[13]), "+f"(d[14]), "+f"(d[15])
                     : "r"(a[0]), "r"(a[1]), "r"(a[2]), "r"(a[3]), "r"(dlo), "r"(DHI), "n"(TB));
    else
        asm volatile("{.reg .b64 db; mov.b64 db, {%20, %21};\n"
                     "wgmma.mma_async.sync.aligned.m64n32k16.f32.bf16.bf16 {%0,%1,%2,%3,%4,%5,%6,%7,%8,%9,%10,%11,%12,%13,%14,%15},{%16,%17,%18,%19},db,0,1,1,%22;}"
                     : "=f"(d[0]), "=f"(d[1]), "=f"(d[2]), "=f"(d[3]), "=f"(d[4]), "=f"(d[5]), "=f"(d[6]), "=f"(d[7]),
                       "=f"(d[8]), "=f"(d[9]), "=f"(d[10]), "=f"(d[11]), "=f"(d[12]), "=f"(d[13]), "=f"(d[14]), "=f"(d[15])
                     : "r"(a[0]), "r"(a[1]), "r"(a[2]), "r"(a[3]), "r"(dlo), "r"(DHI), "n"(TB));
}
__device__ __forceinline__ uint32_t desc_lo(uint32_t addr) { return ((addr & 0x3FFFF) >> 4) | (1u << 16); }
__device__ __forceinline__ void tma2d(uint32_t dst, const CUtensorMap* m, int c0, int c1, uint32_t bar) {
    asm volatile("cp.async.bulk.tensor.2d.shared::cluster.global.mbarrier::complete_tx::bytes [%0], [%1, {%2,%3}], [%4];"
                 ::"r"(dst), "l"(m), "r"(c0), "r"(c1), "r"(bar) : "memory");
}
__device__ __forceinline__ uint64_t evict_first() { uint64_t p; asm("createpolicy.fractional.L2::evict_first.b64 %0, 1.0;" : "=l"(p)); return p; }
__device__ __forceinline__ void tma2d_once(uint32_t dst, const CUtensorMap* m, int c0, int c1, uint32_t bar) {
    const uint64_t pol = evict_first();
    asm volatile("cp.async.bulk.tensor.2d.shared::cluster.global.mbarrier::complete_tx::bytes.L2::cache_hint [%0], [%1, {%2,%3}], [%4], %5;"
                 ::"r"(dst), "l"(m), "r"(c0), "r"(c1), "r"(bar), "l"(pol) : "memory");
}
__device__ __forceinline__ void tma3d(uint32_t dst, const CUtensorMap* m, int c0, int c1, int c2, uint32_t bar) {
    asm volatile("cp.async.bulk.tensor.3d.shared::cluster.global.mbarrier::complete_tx::bytes [%0], [%1, {%2,%3,%4}], [%5];"
                 ::"r"(dst), "l"(m), "r"(c0), "r"(c1), "r"(c2), "r"(bar) : "memory");
}
__device__ __forceinline__ void tma3d_mc(uint32_t dst, const CUtensorMap* m, int c0, int c1, int c2, uint32_t bar, uint16_t mask) {
    if (EVF & 8) asm volatile("cp.async.bulk.tensor.3d.shared::cluster.global.mbarrier::complete_tx::bytes.multicast::cluster.L2::cache_hint [%0], [%1, {%2,%3,%4}], [%5], %6, %7;"
                 ::"r"(dst), "l"(m), "r"(c0), "r"(c1), "r"(c2), "r"(bar), "h"(mask), "l"(evict_first()) : "memory");
    else
    asm volatile("cp.async.bulk.tensor.3d.shared::cluster.global.mbarrier::complete_tx::bytes.multicast::cluster [%0], [%1, {%2,%3,%4}], [%5], %6;"
                 ::"r"(dst), "l"(m), "r"(c0), "r"(c1), "r"(c2), "r"(bar), "h"(mask) : "memory");
}
__device__ __forceinline__ void bulk_g2s_mc(uint32_t dst, const void* src, uint32_t bytes, uint32_t bar, uint16_t mask) {
    asm volatile("cp.async.bulk.shared::cluster.global.mbarrier::complete_tx::bytes.multicast::cluster [%0], [%1], %2, [%3], %4;"
                 ::"r"(dst), "l"(src), "r"(bytes), "r"(bar), "h"(mask) : "memory");
}
__device__ __forceinline__ void tma2d_prefetch(const CUtensorMap* m, int c0, int c1) {
    asm volatile("cp.async.bulk.prefetch.tensor.2d.L2.global [%0, {%1,%2}];" ::"l"(m), "r"(c0), "r"(c1) : "memory");
}
__device__ __forceinline__ void bulk_s2c(uint32_t dst, uint32_t src, uint32_t bytes, uint32_t bar) {
    asm volatile("cp.async.bulk.shared::cluster.shared::cta.mbarrier::complete_tx::bytes [%0], [%1], %2, [%3];" ::"r"(dst), "r"(src), "r"(bytes), "r"(bar) : "memory");
}
__device__ __forceinline__ void bulk_s2g(void* dst, uint32_t src, uint32_t bytes) {
    asm volatile("cp.async.bulk.global.shared::cta.bulk_group [%0], [%1], %2;" ::"l"(dst), "r"(src), "r"(bytes) : "memory");
}
__device__ __forceinline__ void bulk_commit() { asm volatile("cp.async.bulk.commit_group;" ::: "memory"); }
__device__ __forceinline__ void bulk_wait0() { asm volatile("cp.async.bulk.wait_group 0;" ::: "memory"); }
__device__ __forceinline__ uint4 ld_poll(const void* p) {
    uint4 v;
    asm volatile("ld.relaxed.gpu.global.v4.u32 {%0,%1,%2,%3},[%4];" : "=r"(v.x), "=r"(v.y), "=r"(v.z), "=r"(v.w) : "l"(p) : "memory");
    return v;
}
template <int IMM>
__device__ __forceinline__ void ld_poll_at(uint4& v, const void* p) {
    asm volatile("ld.relaxed.gpu.global.v4.u32 {%0,%1,%2,%3},[%4+%5];" : "=r"(v.x), "=r"(v.y), "=r"(v.z), "=r"(v.w) : "l"(p), "n"(IMM) : "memory");
}
__device__ __forceinline__ void look(uint4 (&v)[6], const void* p) {
    ld_poll_at<0>(v[0], p); ld_poll_at<16384>(v[1], p); ld_poll_at<64>(v[2], p);
    ld_poll_at<16384 + 64>(v[3], p); ld_poll_at<128>(v[4], p); ld_poll_at<16384 + 128>(v[5], p);
}
__device__ __forceinline__ unsigned ld_acquire(const unsigned* p) { unsigned v; asm volatile("ld.acquire.gpu.global.u32 %0,[%1];" : "=r"(v) : "l"(p) : "memory"); return v; }
__device__ __forceinline__ void red_release(unsigned* p, unsigned v) { asm volatile("red.release.gpu.global.add.u32 [%0], %1;" ::"l"(p), "r"(v) : "memory"); }

template <int ID, int N> __device__ __forceinline__ void bar_sync() { asm volatile("bar.sync %0, %1;" ::"n"(ID), "n"(N) : "memory"); }
template <int ID, int N> __device__ __forceinline__ void bar_arrive() { asm volatile("bar.arrive %0, %1;" ::"n"(ID), "n"(N) : "memory"); }
__device__ __forceinline__ void cluster_arrive() { asm volatile("barrier.cluster.arrive.relaxed.aligned;" ::: "memory"); }
__device__ __forceinline__ void cluster_wait() { asm volatile("barrier.cluster.wait.aligned;" ::: "memory"); }

constexpr uint32_t XB_BYTES = 36864;
constexpr uint32_t S_XB = 0;
constexpr uint32_t S_QM = 73728;
constexpr uint32_t S_KM = 74752;
constexpr uint32_t S_OM = 75776;
constexpr uint32_t S_SP = 77824;
constexpr uint32_t S_SUM = 80384;
constexpr uint32_t S_TGT = 81408;
constexpr uint32_t S_VM = 147456;
constexpr uint32_t S_QX = 86016;
constexpr uint32_t S_PX = S_QX;
constexpr uint32_t S_KX = 94208;
constexpr uint32_t S_VX = 102400;
constexpr uint32_t S_SX = 135168;
constexpr uint32_t S_OX = 155648;
constexpr uint32_t S_MEM = 172032;
constexpr uint32_t S_WO = 181248;
constexpr uint32_t S_BAR = 230400;
constexpr uint32_t S_ZERO = S_BAR + 128;
constexpr uint32_t A_SMEM = S_ZERO + 1024;
__host__ __device__ constexpr uint32_t s_w(int c) { return c == 0 ? S_WO : 73728 + (c - 1) * 49152; }
constexpr uint32_t B_W = S_BAR, B_WO = S_BAR + 24, B_X = S_BAR + 32, B_S = S_BAR + 48, B_VX = S_BAR + 56, B_SX = S_BAR + 72, B_M = S_BAR + 88, B_T = S_BAR + 112;
constexpr int NB_QK = 1, NB_O = 2, NB_RED = 3, NB_P = 4, NB_AUX = 5, NB_PRO = 6, NB_X = 7, NB_GO = 8, NB_L = 9, NB_PV = 10, NB_T0 = 11, NB_PR = 14, NB_VW = 15;

constexpr float SM_SCALE = 0.08838834764831845f * 1.4426950408889634f;
constexpr uint32_t ONES = 0x3F803F80u;
constexpr uint32_t FULL_COUNT = 0x4200u;
#define XLIM NSEG
#define TGT_NS 1028
#define LOOK_NS 100
#define RCP_AT 2
#define NCH 2
#define XTMA_NS 50
#define REG_MAIN0 232
#define REG_MAIN1 232
#define REG_AUX 40

#define HAND_AT 26
#define PUB_EARLY 0
#define W_PROMO CU_TENSOR_MAP_L2_PROMOTION_L2_128B
#define DESCPF 1
#define WO_AFTER 2
#define FIRST_NS 450
#define PACE 1
#define DEP_LATE 1
#define HSPLIT 2
#define FIN_NS 40
#define WO_LOOP 0
#define YST 1
#define TRICKLE_NS 700
#define REFRESH 0
#define U_NS 0
#define FIN0_NS 0
#define XEARLY 1
#define PRCP 1
#define PR_AT 18
#define VXTEST 0
#define ADAPT 3
#define AD_UP 9
#define FLAG_NS 40
static_assert(REG_MAIN0 + REG_MAIN1 + REG_AUX <= 504, "the three warpgroups share 3 x 168 registers");
#define HSTAMP(i) do {} while (0)
#define HSTAMP2(i) do {} while (0)
#define HSTAMP3(i) do {} while (0)
#define HSTAMP4(i) do {} while (0)
#define TSTAMP(i, e) do {} while (0)

__device__ __forceinline__ void load_scores(uint32_t a, __half2 (&hs)[5]) {
    uint32_t r[10];
    ldsm4(r, a);
    ldsm4(r + 4, a + 512);
    ldsm2(r + 8, a + 1024);
    const __half2 hf = as_h2(0x38003800u);
#pragma unroll
    for (int T = 0; T < 5; T++) hs[T] = __hfma2(as_h2(r[2 * T]), hf, __hmul2(as_h2(r[2 * T + 1]), hf));
}
__device__ __forceinline__ void softmax_exp(const __half2 (&hs)[5], float (&ev)[10]) {
    __half2 m = __hmax2(__hmax2(__hmax2(hs[0], hs[1]), __hmax2(hs[2], hs[3])), hs[4]);
    const uint32_t mu = as_u32(m);
    const uint32_t m1 = __shfl_xor_sync(0xffffffffu, mu, 1), m2 = __shfl_xor_sync(0xffffffffu, mu, 2), m3 = __shfl_xor_sync(0xffffffffu, mu, 3);
    m = __hmax2(__hmax2(m, as_h2(m1)), __hmax2(as_h2(m2), as_h2(m3)));
    const float mc = -fmaxf(__low2float(m), __high2float(m)) * (2.f * SM_SCALE);
#pragma unroll
    for (int T = 0; T < 5; T++) {
        ev[2 * T] = ex2(fmaf(__low2float(hs[T]), 2.f * SM_SCALE, mc));
        ev[2 * T + 1] = ex2(fmaf(__high2float(hs[T]), 2.f * SM_SCALE, mc));
    }
}

__device__ __forceinline__ void x_scores(uint32_t sb, int seg, int wq, uint32_t L16, float (&ev)[10]) {
    __half2 hs[5];
    load_scores(sb + S_SX + (seg & 1) * 5120 + wq * 1280 + L16, hs);
    const int dg = (int)(L16 >> 6) - (int)((L16 >> 3) & 6) + 8 * wq;
#pragma unroll
    for (int T = 0; T < 4; T++) {
        uint32_t u = as_u32(hs[T]);
        if (dg < 8 * T + 1) u = (u & 0xFFFFu) | 0xFC000000u;
        if (dg < 8 * T) u = 0xFC00FC00u;
        hs[T] = as_h2(u);
    }
    softmax_exp(hs, ev);
}
__device__ __forceinline__ void x_probs(uint32_t sb, int seg, int wq, uint32_t L16, const float (&ev)[10]) {
    float l = ((ev[0] + ev[1]) + (ev[2] + ev[3])) + ((ev[4] + ev[5]) + (ev[6] + ev[7])) + (ev[8] + ev[9]);
    const float l1 = __shfl_xor_sync(0xffffffffu, l, 1), l2 = __shfl_xor_sync(0xffffffffu, l, 2), l3 = __shfl_xor_sync(0xffffffffu, l, 3);
    const float r = rcp((l + l1) + (l2 + l3));
    const uint32_t a = sb + S_PX + (seg & 1) * 4096 + wq * 640 + (L16 >> 2);
#pragma unroll
    for (int i = 0; i < 5; i++) sts32(a + i * 128, pack_bf16(ev[2 * i] * r, ev[2 * i + 1] * r));
}
__device__ __forceinline__ void x_pv_load(uint32_t sb, int seg, int w, uint32_t L16, uint32_t (&a)[3][4]) {
    lds128(a[0], sb + S_VX + (seg & 3) * 8192 + w * 1024 + L16);
    lds128(a[1], sb + S_VX + (seg & 3) * 8192 + w * 1024 + 512 + L16);
    lds64(a[2], sb + S_VM + (seg & 3) * 2048 + w * 256 + (L16 >> 1));
    a[2][2] = 0; a[2][3] = 0;
}
__device__ __forceinline__ void x_pv_run(uint32_t sb, int seg, const uint32_t (&a)[3][4], uint32_t (&pk)[8]) {
    const uint32_t d = ((sb + S_PX + (seg & 1) * 4096) & 0x3FFFF) >> 4;
    float o[16];
    wg_fence();
    wg_rs_n32<0, 40>(o, a[0], d | (8u << 16));
    wg_rs_n32<1, 40>(o, a[1], (d + 16) | (8u << 16));
    wg_rs_n32<1, 40>(o, a[2], d + 32);
    wg_commit();
    wg_wait<0>();
#pragma unroll
    for (int i = 0; i < 8; i++) pk[i] = pack_bf16(o[2 * i], o[2 * i + 1]);
}
__device__ __forceinline__ void x_pv_store(uint32_t sb, int seg, int w, uint32_t L16, const uint32_t (&pk)[8]) {
    const uint32_t a = sb + S_OX + (seg & 1) * 8192 + w * 1024 + L16;
    stsm4(a, pk[0], pk[1], pk[2], pk[3]);
    stsm4(a + 512, pk[4], pk[5], pk[6], pk[7]);
}
template <int BAR, int CNT>
__device__ __forceinline__ void x_pv_both(uint32_t sb, int seg, int wq, uint32_t L16) {
    uint32_t pva[3][4], pk[8];
    x_pv_load(sb, seg, wq + 4, L16, pva);
    bar_sync<BAR, CNT>();
    x_pv_run(sb, seg, pva, pk);
    x_pv_load(sb, seg, wq, L16, pva);
    x_pv_store(sb, seg, wq + 4, L16, pk);
    x_pv_run(sb, seg, pva, pk);
    x_pv_store(sb, seg, wq, L16, pk);
}
__device__ __forceinline__ void ox_store(uint32_t sb, int seg, uint32_t h) {
    fence_async_smem();
    bulk_s2g(g_ox + (seg * NH + h) * 512, sb + S_OX + (seg & 1) * 8192, 8192);
    bulk_commit();
}
__device__ __forceinline__ void ox_publish(int seg, uint32_t h) {
    bulk_wait0();
    asm volatile("fence.proxy.async.global;" ::: "memory");
    asm volatile("red.relaxed.gpu.global.add.u32 [%0], 1;" ::"l"(&g_flag[(h >> 3) * NSEG + seg]) : "memory");
}
__device__ __forceinline__ void vx_store(uint32_t sb, int seg, uint32_t h) {
    fence_async_smem();
    bulk_s2g(g_vx + (h * 2 + (seg & 1)) * 512, sb + S_VX + (seg & 3) * 8192, 8192);
    bulk_commit();
}
__device__ __forceinline__ void vx_fetch(uint32_t sb, int seg, uint32_t h) {
    bulk_wait0();
    bulk_g2s_mc(sb + S_VX + (seg & 3) * 8192, g_vx + (h * 2 + (seg & 1)) * 512, 8192, sb + B_VX + (seg & 1) * 8, 3);
}

__device__ __forceinline__ void x_pack(const float (&d)[16], uint32_t (&pk)[8]) {
#pragma unroll
    for (int i = 0; i < 8; i++) pk[i] = pack_bf16(d[2 * i], d[2 * i + 1]);
}
__device__ __forceinline__ void x_write(uint32_t sb, const uint32_t (&pk)[8], int seg, bool isv, int w, uint32_t L16) {
    if (!isv) {
        const uint32_t a = sb + S_QX + (w >> 2) * 8192 + (seg & 1) * 4096 + (w & 3) * 256 + (L16 & 0xF0) + (L16 & 0x100) * 4;
        stsm4t(a, pk[0], pk[1], pk[2], pk[3]);
        stsm4t(a + 2048, pk[4], pk[5], pk[6], pk[7]);
    } else {
        const uint32_t a = sb + S_VX + (seg & 3) * 8192 + w * 1024 + L16;
        sts128(a, pk[0], pk[1], pk[2], pk[3]);
        sts128(a + 512, pk[4], pk[5], pk[6], pk[7]);
    }
}

template <int K0, int K1>
__device__ __forceinline__ void x_project(float (&d)[16], const uint32_t (&wA)[36][4], uint32_t desc) {
#pragma unroll
    for (int i = K0; i < K1; i++) {
        const uint32_t db = desc + (((i >> 2) * 4096 + (i & 3) * 32) >> 4);
        if (i == 0) wg_rs_n32<0>(d, wA[i], db); else wg_rs_n32<1>(d, wA[i], db);
    }
}

__device__ __forceinline__ void mem_scores(uint32_t sb, uint32_t peerA, uint32_t peerB, uint32_t off, const uint32_t (&q0)[4], const uint32_t (&q1)[4],
                                           const uint32_t (&k0)[4], const uint32_t (&k1)[4]) {
    float e0[4], o0[4], e1[4], o1[4];
    mma16z(e0, q0, k0[0], k0[1]);
    mma16z(o0, q0, k0[2], k0[3]);
    mma16z(e1, q1, k1[0], k1[1]);
    mma16z(o1, q1, k1[2], k1[3]);
    const uint32_t sc = pack_f16_sat((e0[0] + o0[2]) + (e1[0] + o1[2]), (e0[1] + o0[3]) + (e1[1] + o1[3]));
    st_async32(peerB + off, sc, peerB + B_S);
    st_async32(peerA + off, sc, peerA + B_S);
    sts32(sb + off, sc);
    __syncwarp();
}

__device__ __forceinline__ unsigned post_time(int s, uint32_t L16, unsigned early) {
    delay(1);
    const unsigned t = (gtime() & ~3u) | 1 | (early ? 2 : 0);
    if (L16 == 0) asm volatile("st.relaxed.gpu.global.u32 [%0], %1;" ::"l"(g_time + s * 96 + blockIdx.x), "r"(t) : "memory");
    return t;
}
__device__ __forceinline__ void plan_look(uint32_t sb, int s, uint32_t L16, unsigned t, int& state) {
    const char* p = reinterpret_cast<const char*>(g_time) + s * 384 + (L16 < 384 ? L16 : 0);
    uint4 v;
    unsigned c = 0;
    do { v = ld_poll(p); } while (__any_sync(0xffffffffu, (v.x & v.y & v.z & v.w & 1) == 0) && ++c < SPIN_LIM);
    const int d = max(max((int)(v.x - t), (int)(v.y - t)), max((int)(v.z - t), (int)(v.w - t))) + (s == 0 ? FIRST_NS : 0);
    if (ADAPT && s >= ADAPT) {
        const bool bad = __popc(__ballot_sync(0xffffffffu, (v.x | v.y | v.z | v.w) & 2)) >= 4;
        int e = state & 63, x = state >> 6;
        e = bad ? max(e, 16) + AD_UP : e - 1;
        if (e >= 32) { x = min(x + 32, 256); e = 16; }
        if (e <= 0) { x = max(x - 32, 0); e = 16; }
        state = x * 64 + e;
    }
    t = (t & ~3u) + (state >> 6);
    const unsigned tgt = t + min(__reduce_max_sync(0xffffffffu, d), 20000) + TGT_NS;
    if (L16 < 48) { const uint32_t r = mapa(sb, L16 >> 4); st_async32(r + S_TGT, tgt, r + B_T); }
}

__device__ __forceinline__ void load_wo(uint32_t sb, int w, uint32_t L16, uint32_t (&woA)[8][4], uint32_t (&woB)[4][4]) {
    mbar_wait(sb + B_WO, 0);
    if (w < 4) TSTAMP(73, 0);
    const int m = L16 >> 7, r = (L16 >> 4) & 7;
    const int ca = 3 * w + (m & 1), cb = 3 * w + 2;
    const uint32_t aA = sb + S_WO + (ca >> 3) * 16384 + ((m >> 1) * 8 + r) * 128 + (((ca & 7) ^ r) << 4);
    const int eB = ((m & 2) + ((r >> 1) & 1)) * 8 + 4 * (m & 1) + 2 * (r >> 2) + (r & 1);
    const uint32_t aB = sb + S_WO + (cb >> 3) * 16384 + eB * 128 + (((cb & 7) ^ (eB & 7)) << 4);
#pragma unroll
    for (int i = 0; i < 8; i++) ldsm4t(woA[i], aA + i * 2048);
#pragma unroll
    for (int i = 0; i < 4; i++) ldsm4t(woB[i], aB + i * 4096);
}

template <int ROLE>
__device__ __forceinline__ void chain_main(const uint32_t sb, const uint32_t lane16, const int wq, const uint32_t j, const uint32_t h,
                                           const uint32_t peerA, const uint32_t peerB, char* const acc) {
    uint32_t L16 = lane16;
    constexpr bool isv = ROLE >= 2;
    constexpr int wg = ROLE & 1;
    const int w = wg * 4 + wq;
    const uint32_t xdesc = desc_lo(sb + S_XB);
    const uint32_t zero = h >> 20;
    uint32_t wA[36][4], woA[8][4], woB[4][4];
    float xd[16];
    {
        const int m = L16 >> 7, r = (L16 >> 4) & 7;
        const int blk = (ROLE == 1) ? ((wq & 2) * 2 + (wq & 1) + (m & 1) * 2) : (2 * wq + (m & 1));
        const uint32_t a = sb + wg * 24576 + ((m >> 1) * 8 + r) * 128 + ((blk ^ r) << 4);
        float x0[16];
#pragma unroll
        for (int c = 0; c < 3; c++) {
            mbar_wait(sb + B_W + 8 * c, 0);
            if (wg == 0) TSTAMP(70 + c, 0);
#pragma unroll
            for (int i = 0; i < 12; i++) ldsm4t(wA[12 * c + i], a + s_w(c) + i * 2048);
            if (c == WO_AFTER) bar_arrive<NB_PRO, 288>();
            if (c == 0) { mbar_wait(sb + B_X, 0); mbar_wait(sb + B_X + 8, 0); }
            if (c == 2) { bar_sync<NB_O, 256>(); cluster_arrive(); }
            wg_fence();
            if (c == 0) { x_project<0, 12>(x0, wA, xdesc); x_project<0, 12>(xd, wA, xdesc + (XB_BYTES >> 4)); wg_commit(); wg_wait<0>(); }
            if (c == 1) { x_project<12, 24>(x0, wA, xdesc); x_project<12, 24>(xd, wA, xdesc + (XB_BYTES >> 4)); wg_commit(); wg_wait<0>(); }
            if (c == 2) { x_project<24, 36>(x0, wA, xdesc); wg_commit(); wg_wait<0>(); }
        }
        uint32_t pk[8];
        x_pack(x0, pk);
        x_write(sb, pk, 0, isv, w, L16);
        bar_arrive<NB_AUX, 288>();
        wg_fence();
        x_project<24, 36>(xd, wA, xdesc + (XB_BYTES >> 4));
        wg_commit();
        cluster_wait();
        bar_sync<NB_O, 256>();
        if (wg == 0) TSTAMP(74, 0);
        if (WO_LOOP) {
#pragma unroll
            for (int i = 0; i < 8; i++) woA[i][0] = woA[i][1] = woA[i][2] = woA[i][3] = 0;
#pragma unroll
            for (int i = 0; i < 4; i++) woB[i][0] = woB[i][1] = woB[i][2] = woB[i][3] = 0;
        } else load_wo(sb, w, L16, woA, woB);
    }
    int s = 0;
#pragma unroll 1
    while (true) {
        const uint32_t par = s & 1;
        const uint32_t kx = sb + S_KX + par * 4096;
        asm volatile("" : "+r"(L16));
        uint32_t pk[8];
        if (wg == 0) { wg_wait<0>(); x_pack(xd, pk); x_write(sb, pk, s + 1, isv, w, L16); }
        float c0[4], c1[4];
        uint32_t k0[4], k1[4];
        bool vxready = false;
        {
            const uint32_t a = sb + S_MEM + L16;
            constexpr int CH = 18 / NCH;
            uint32_t b[3][4];
            bool ready = true;
            mbar_wait(sb + B_M, par);
            ldsm4(b[0], a);
            ldsm4(b[1], a + 512);
            if (wg == 1) { wg_wait<0>(); x_pack(xd, pk); }
            bar_arrive<NB_GO, 288>();
#pragma unroll
            for (int i = 0; i < 18; i++) {
                if ((i + 4) % CH == 0 && i + 4 < 18) ready = mbar_test(sb + B_M + ((i + 4) / CH) * 8, par);
                if ((i + 2) % CH == 0 && i + 2 < 18) { if (__builtin_expect(!ready, 0)) mbar_wait(sb + B_M + ((i + 2) / CH) * 8, par); }
                if (i + 2 < 18) ldsm4(b[(i + 2) % 3], a + (i + 2) * 512);
                if (ROLE == 0 && i == 16) ldsm4(k0, kx + wq * 1024 + L16);
                if (ROLE == 0 && i == 17) ldsm4(k1, kx + wq * 1024 + 512 + L16);
                if (ROLE == 2 && i == PR_AT) bar_arrive<NB_PR, 256>();
                if (i == 0) { mma16z(c0, wA[0], b[0][0], b[0][1]); mma16z(c1, wA[1], b[0][2], b[0][3]); }
                else { mma16(c0, wA[2 * i], b[i % 3][0], b[i % 3][1]); mma16(c1, wA[2 * i + 1], b[i % 3][2], b[i % 3][3]); }
            }
        }
        const uint32_t p0 = pack_bf16(c0[0] + c1[0], c0[1] + c1[1]), p1 = pack_bf16(c0[2] + c1[2], c0[3] + c1[3]);
        if (!isv) {
            stsm2t(sb + S_QM + w * 256 + L16, p0, p1);
            bar_sync<NB_QK, 384>();
            if (ROLE == 0) {
                uint32_t q0[4], q1[4];
                ldsm4(q0, sb + S_QM + L16);
                ldsm4(q1, sb + S_QM + 512 + L16);
                if (VXTEST) vxready = mbar_test(sb + B_VX + par * 8, (s >> 1) & 1);
                mem_scores(sb, peerA, peerB, S_SP + j * 128 + wq * 256 + (L16 >> 2), q0, q1, k0, k1);
                mbar_arrive_if0(sb + B_S, L16);
            } else {
                if (s + 2 < XLIM) mbar_wait(sb + B_X + par * 8, ((s + 2) >> 1) & 1);
                x_write(sb, pk, s + 1, isv, w, L16);
                if (wq != 0) {
                    const int rt = (wq == 3) ? 0 : 1;
                    const uint32_t qa = sb + S_QX + par * 4096 + rt * 2048 + (L16 & 0x80) * 8 + (L16 & 0x170);
                    const uint32_t kb0 = (wq == 2 ? kx + 2048 : sb + S_KM) + L16;
                    const uint32_t kb1 = (wq == 2 ? kx + 3072 : kx) + L16;
                    const uint32_t kb2 = kx + 1024 + L16;
                    float a0[4], a1[4], a2[4];
#pragma unroll
                    for (int hf = 0; hf < 2; hf++) {
                        uint32_t qa0[4], qa1[4], b[4];
                        ldsm4(qa0, qa + hf * 512);
                        ldsm4(qa1, qa + hf * 512 + 128);
                        ldsm4(b, kb0 + hf * 512);
                        if (hf == 0) mma16z(a0, qa0, b[0], b[1]); else mma16(a0, qa0, b[0], b[1]);
                        mma16(a0, qa1, b[2], b[3]);
                        ldsm4(b, kb1 + hf * 512);
                        if (hf == 0) mma16z(a1, qa0, b[0], b[1]); else mma16(a1, qa0, b[0], b[1]);
                        mma16(a1, qa1, b[2], b[3]);
                        ldsm4(b, kb2 + hf * 512);
                        if (hf == 0) mma16z(a2, qa0, b[0], b[1]); else mma16(a2, qa0, b[0], b[1]);
                        mma16(a2, qa1, b[2], b[3]);
                    }
                    if (s < NSEG - 1) mbar_wait(sb + B_S, par);
                    const uint32_t dst = peerB + S_SX + par * 5120 + j * 128 + rt * 2560 + (L16 >> 2);
                    const uint32_t bar = peerB + B_SX + par * 8;
                    const uint32_t T0 = (wq == 2 ? 2 : 4) * 256, T1 = (wq == 2 ? 3 : 0) * 256;
                    st_async32(dst + T0, pack_f16_sat(a0[0], a0[1]), bar);
                    st_async32(dst + 1280 + T0, pack_f16_sat(a0[2], a0[3]), bar);
                    if (wq != 2) st_async32(dst + T1, pack_f16_sat(a1[0], a1[1]), bar);
                    st_async32(dst + 1280 + T1, pack_f16_sat(a1[2], a1[3]), bar);
                    if (wq == 1) st_async32(dst + 256, pack_f16_sat(a2[0], a2[1]), bar);
                    if (wq != 2) st_async32(dst + 1280 + 256, pack_f16_sat(a2[2], a2[3]), bar);
                }
            }
        } else {
            const uint32_t off = S_VM + (s & 3) * 2048 + w * 256 + (L16 >> 1);
            st_async64(peerA + off, p0, p1, peerA + B_S);
            st_async64(peerB + off, p0, p1, peerB + B_S);
            sts64(sb + off, p0, p1);
            __syncwarp();
            mbar_expect_if0(sb + B_S, 160, L16);
            if (ROLE == 2) bar_arrive<NB_P, 384>();
            else {
                if (s == NSEG - 1) break;
                x_write(sb, pk, s + 1, isv, w, L16);
                if (PR_AT < 18) bar_arrive<NB_VW, 160>();
                x_pv_both<NB_P, 384>(sb, s + 2, wq, L16);
                bar_arrive<NB_PV, 160>();
                if (s + 2 < XLIM) mbar_wait(sb + B_X + par * 8, ((s + 2) >> 1) & 1);
            }
        }
        if (WO_LOOP == 0 && s == NSEG - 1) break;
        if (WO_LOOP && ((s + 1) & (NSEG - 1)) <= 1) {
            if (s) break;
            load_wo(sb, w, L16, woA, woB);
        }
        if (wg == 0) {
            if (!isv && !vxready) mbar_wait(sb + B_VX + par * 8, (s >> 1) & 1);
            uint32_t va[4][4];
            const uint32_t vx = sb + S_VX + (s & 3) * 8192 + wq * 2048 + L16;
            const uint32_t vm = sb + S_VM + (s & 3) * 2048 + wq * 512 + (L16 >> 1);
            lds128(va[0], vx);
            lds128(va[2], vx + 1024);
            mbar_wait(sb + B_S, par);
            __half2 hs[5];
            load_scores(sb + S_SP + L16, hs);
            float ev[10];
            softmax_exp(hs, ev);
            lds128(va[1], vx + 512);
            lds128(va[3], vx + 1536);
            uint32_t p[5];
#pragma unroll
            for (int i = 0; i < 5; i++) p[i] = pack_bf16(ev[2 * i], ev[2 * i + 1]);
            uint32_t vm0[2], vm1[2];
            const uint32_t ones[4] = {ONES, ONES, ONES, ONES};
            float sum[4], o0[4], o1[4];
            mma16z(o0, va[0], p[0], p[1]);
            mma16z(o1, va[2], p[0], p[1]);
            mma16z(sum, ones, p[0], p[1]);
            lds64(vm0, vm);
            lds64(vm1, vm + 256);
            mma16(o0, va[1], p[2], p[3]);
            mma16(o1, va[3], p[2], p[3]);
            mma16(sum, ones, p[2], p[3]);
            if (PRCP) mma8(sum, ONES, ONES, p[4]);
            mma8(o0, vm0[0], vm0[1], p[4]);
            mma8(o1, vm1[0], vm1[1], p[4]);
            if (!PRCP) mma8(sum, ONES, ONES, p[4]);
            stsm4t(sb + S_OM + wq * 512 + L16, pack_bf16(o0[0], o0[1]), pack_bf16(o0[2], o0[3]), pack_bf16(o1[0], o1[1]), pack_bf16(o1[2], o1[3]));
            sts64(sb + S_SUM + wq * 256 + (L16 >> 1), __float_as_uint(PRCP ? rcp(sum[0]) : sum[0]), __float_as_uint(PRCP ? rcp(sum[1]) : sum[1]));
        }
        bar_sync<NB_O, 256>();
        {
            float a0[4], a1[4], e[4];
            float2 sc;
            float sr, r0, r1, rr;
#pragma unroll
            for (int i = 0; i < 4; i++) {
                uint32_t b[4];
                ldsm4(b, sb + S_OM + i * 512 + L16);
                if (i == 0) {
                    mma16z(a0, woA[0], b[0], b[1]); mma16z(a1, woA[1], b[2], b[3]);
                    mma_sp<0>(e, b, woB[0]);
                } else {
                    if (i == 1) { sc = lds64f(sb + S_SUM + (L16 >> 1)); sr = lds32f(sb + S_SUM + ((L16 >> 4) & 0x1C)); }
                    const uint32_t z = __float_as_uint(a0[0]) & zero;
                    mma16(a0, woA[2 * i], b[0], b[1]); mma16(a1, woA[2 * i + 1], b[2], b[3]);
                    mma_sp<1>(e, b, woB[i]);
                    if (PRCP) { r0 = sc.x; r1 = sc.y; rr = sr; }
                    else if (i == RCP_AT) {
                        r0 = rcp(__uint_as_float(__float_as_uint(sc.x) | z));
                        r1 = rcp(__uint_as_float(__float_as_uint(sc.y) | z));
                        rr = rcp(__uint_as_float(__float_as_uint(sr) | z));
                    }
                }
            }
            if (XEARLY && wg == 1) bar_arrive<NB_X, 256>();
            asm volatile("" : "+r"(L16));
            char* const rslot = acc + (slot_off(s + 1) + j * 64 + w * 4096) + lane_off(L16);
            asm volatile("red.relaxed.gpu.global.add.noftz.v4.bf16x2 [%0], {%1,%2,%3,%4};"
                         ::"l"(rslot), "r"(pack_bf16((a0[0] + a1[0]) * r0, (a0[1] + a1[1]) * r1)), "r"(pack_bf16((a0[2] + a1[2]) * r0, (a0[3] + a1[3]) * r1)),
                           "r"(pack_bf16((e[0] + e[2]) * rr, (e[1] + e[3]) * rr)), "r"(0x3F80u) : "memory");
        }
        bar_arrive<NB_RED, 384>();
        if (wg == 0) {
            bar_sync<NB_X, 256>();
            wg_fence();
            x_project<0, HAND_AT>(xd, wA, xdesc + par * (XB_BYTES >> 4));
            bar_arrive<NB_L, 256>();
            x_project<HAND_AT, 36>(xd, wA, xdesc + par * (XB_BYTES >> 4));
            wg_commit();
        } else {
            if (!XEARLY) bar_arrive<NB_X, 256>();
            if (s < NSEG - 2) {
                bar_sync<NB_L, 256>();
                wg_fence();
                x_project<0, 36>(xd, wA, xdesc + par * (XB_BYTES >> 4));
                wg_commit();
            } else {
                if (isv) {
                    x_pv_both<NB_T0, 256>(sb, NSEG - 3, wq, L16);
                    bar_sync<NB_AUX, 128>();
                    if (wq == 0 && L16 == 0) ox_store(sb, NSEG - 3, h);
                    __syncwarp();
                    x_pv_both<NB_T0 + 1, 256>(sb, NSEG - 2, wq, L16);
                    bar_sync<NB_AUX, 128>();
                    if (L16 == 0) {
                        if (wq == 0) ox_publish(NSEG - 3, h);
                        if (wq == 1) ox_store(sb, NSEG - 2, h);
                    }
                    __syncwarp();
                }
                wg_fence();
                x_project<0, 1>(xd, wA, xdesc);
                wg_commit();
            }
        }
        s++;
    }
    if (isv) {
        if (w == 5 && L16 == 0) ox_publish(NSEG - 2, h);
        __syncwarp();
        uint32_t pva[3][4], pk[8];
        x_pv_load(sb, NSEG - 1, w, L16, pva);
        bar_sync<NB_T0 + 2, 384>();
        x_pv_run(sb, NSEG - 1, pva, pk);
        x_pv_store(sb, NSEG - 1, w, L16, pk);
        bar_sync<NB_O, 256>();
        if (w == 0 && L16 == 0) { ox_store(sb, NSEG - 1, h); ox_publish(NSEG - 1, h); }
        __syncwarp();
    }
}

template <bool isv>
__device__ __forceinline__ void chain_aux(const uint32_t sb, const uint32_t lane16, const int wq, const uint32_t j, const uint32_t h,
                                          const uint32_t peerA, const uint32_t peerB, const CUtensorMap* tmWo, const CUtensorMap* tmX,
                                          char* const acc, const CUtensorMap* m0, const CUtensorMap* m1) {
    const int t = wq * 32 + (lane16 >> 4);
    cluster_arrive();
    {
        for (int c2 = 0; c2 < 3; c2++) mbar_arrive_if0(sb + B_M + c2 * 8, lane16);
        if (wq == 0) {
            if (PACE) {
                mbar_wait(sb + B_W, 0);
                if (t == 0) {
                    mbar_expect(sb + B_W + 16, 49152);
                    tma2d_once(sb + s_w(2), m0, h * 128 + (isv ? 0 : 64 * j), 384, sb + B_W + 16);
                    tma2d_once(sb + s_w(2) + 24576, m1, h * 128 + (isv ? 64 : 64 * j), 384, sb + B_W + 16);
                }
                __syncwarp();
            }
            bar_sync<NB_PRO, 288>();
            if (t == 0) {
                fence_async_smem();
                mbar_expect(sb + B_WO, 49152);
                for (int b = 0; b < 3; b++) tma2d(sb + S_WO + b * 16384, tmWo, 192 * j + 64 * b, h * 128, sb + B_WO);
            }
        } else if (wq == 3) {
            bulk_wait0();
            asm volatile("fence.proxy.async.global;" ::: "memory");
            __syncwarp();
            if (lane16 == 0) {
                if (h == 0) asm volatile("red.relaxed.gpu.global.add.u32 [%0], 1;" ::"l"(&g_zero_cnt) : "memory");
            }
            __syncwarp();
            unsigned c = 0;
            while (ld_acquire(&g_zero_cnt) < 3 && ++c < SPIN_LIM) __nanosleep(100);
            TSTAMP(76, 0);
            if (DEP_LATE) mbar_wait(sb + B_W + 16, 0);
            asm volatile("griddepcontrol.launch_dependents;" ::: "memory");
        }
        __syncwarp();
        cluster_wait();
        if (wq == 0) bar_sync<NB_AUX, 288>();
        if (t == 0) {
            fence_async_smem();
            if (!isv) mbar_expect(sb + B_VX, 8192);
            else {
                bulk_s2c(peerA + S_VX, sb + S_VX, 8192, peerA + B_VX);
                bulk_s2c(peerB + S_VX, sb + S_VX, 8192, peerB + B_VX);
            }
            mbar_expect(sb + B_X, XB_BYTES);
            tma3d(sb + S_XB, tmX, 0, 64, 0, sb + B_X);
        }
        __syncwarp();
    }
    TSTAMP(0, 0);
    uint32_t L16 = lane16;
    const char* slot = acc + wq * 4096 + lane_off(L16);
    float ev[10];
    unsigned early = 0;
    int state = 16;
    int s = 0;
#pragma unroll 1
    while (true) {
        const uint32_t par = s & 1;
        asm volatile("" : "+r"(L16));
        if (!isv) {
            if (wq == 0) {
                bar_sync<NB_QK, 384>();
                uint32_t q0[4], q1[4], k0[4], k1[4];
                ldsm4(q0, sb + S_QM + L16);
                ldsm4(k0, sb + S_KM + L16);
                ldsm4(q1, sb + S_QM + 512 + L16);
                ldsm4(k1, sb + S_KM + 512 + L16);
                mem_scores(sb, peerA, peerB, S_SP + j * 128 + 1024 + (L16 >> 2), q0, q1, k0, k1);
                mbar_expect_if0(sb + B_S, 640 + 2048, L16);
            } else if (wq == 3) {
                bar_sync<NB_GO, 288>();
                const unsigned t = post_time(s, L16, early);
                bar_sync<NB_QK, 384>();
                if (j == 0 && s < NSEG - 1) {
                    if (LOOK_NS) __nanosleep(LOOK_NS);
                    plan_look(sb, s, L16, t, state);
                }
            } else {
                bar_arrive<NB_QK, 384>();
                if (wq == 2) {
                    if (L16 == 0) {
                        if (s + 3 < XLIM) mbar_expect(sb + B_X + (par ^ 1) * 8, XB_BYTES);
                        mbar_expect(sb + B_VX + (par ^ 1) * 8, 8192);
                        mbar_expect(sb + B_T, 4);
                        if (s == 2 && h == 0 && j == 0) g_zero_cnt = 0;
                        if (REFRESH && s + REFRESH == 2 * h) asm volatile("cp.async.bulk.prefetch.L2.global [%0], %1;" ::"l"(acc + h * 32768 + j * 16384), "r"(16384) : "memory");
                    }
                } else if (s + 3 < XLIM && j == 1) {
                    mbar_wait(sb + B_S, par);
                    if (XTMA_NS) __nanosleep(XTMA_NS);
                    if (L16 == 0) tma3d_mc(sb + S_XB + (par ^ 1) * XB_BYTES, tmX, 0, (s + 3) * SEG, 0, sb + B_X + (par ^ 1) * 8, 7);
                }
                __syncwarp();
            }
        } else {
            if (wq == 3) {
                bar_sync<NB_GO, 288>();
                post_time(s, L16, early);
            } else if (L16 == 0) {
                if (wq == 0) {
                    if (s >= 1) vx_fetch(sb, s, h);
                } else if (wq == 1) {
                    if (!PUB_EARLY && s >= 3 && s < NSEG - 1) ox_publish(s - 3, h);
                } else {
                    mbar_expect(sb + B_SX + par * 8, 3584);
                    mbar_expect(sb + B_T, 4);
                    if (s + 3 < XLIM) mbar_expect(sb + B_X + (par ^ 1) * 8, XB_BYTES);
                }
            }
            __syncwarp();
            if (s == NSEG - 1) break;
            if (s >= 1) mbar_wait(sb + B_SX + (par ^ 1) * 8, ((s - 1) >> 1) & 1);
            fence_async_smem();
            if (PR_AT < 18) {
                bar_arrive<NB_P, 384>();
                bar_sync<NB_PR, 256>();
                x_scores(sb, s + 1, wq, L16, ev);
                x_probs(sb, s + 1, wq, L16, ev);
                if (wq == 0) { bar_sync<NB_VW, 160>(); if (L16 == 0) vx_store(sb, s + 1, h); __syncwarp(); }
                if (wq == 1) {
                    bar_sync<NB_PV, 160>();
                    if (L16 == 0 && s >= 2) ox_store(sb, s - 2, h);
                    __syncwarp();
                }
            } else {
            bar_sync<NB_P, 384>();
            if (wq == 0) { if (L16 == 0) vx_store(sb, s + 1, h); __syncwarp(); }
            x_scores(sb, s + 1, wq, L16, ev);
            if (wq == 1) {
                bar_sync<NB_PV, 160>();
                if (L16 == 0 && s >= 2) ox_store(sb, s - 2, h);
                __syncwarp();
            }
            x_probs(sb, s + 1, wq, L16, ev);
            }
        }
        if (s == NSEG - 1) break;
        mbar_wait(sb + B_T, par);
        const unsigned tgt = __float_as_uint(lds32f(sb + S_TGT));
        if (isv && s == NSEG - 2) { fence_async_smem(); bar_arrive<NB_T0, 256>(); }
        bar_sync<NB_RED, 384>();
        if (isv) {
            if (wq == 1 && (PUB_EARLY || s == NSEG - 2)) {
                if (PUB_EARLY > 1) while ((int)(gtime() - tgt) < -PUB_EARLY) {}
                if (L16 == 0 && s >= 2) ox_publish(s - 2, h);
                __syncwarp();
            }
            if (s == NSEG - 2) {
                mbar_wait(sb + B_SX, (s >> 1) & 1);
                x_scores(sb, s, wq, L16, ev);
                x_probs(sb, s, wq, L16, ev);
                fence_async_smem();
                bar_arrive<NB_T0 + 1, 256>();
            }
        }
        asm volatile("" : "+r"(L16));
        slot += par ? 32768 - 512 : 512;
        while ((int)(gtime() - tgt) < 0) {}
        uint4 v[6];
        look(v, slot);
        s++;
        const uint32_t ma = sb + S_MEM + wq * 384 + L16;
        unsigned c = 0;
        constexpr int CW = 6 / NCH;
        int done = NCH;
#pragma unroll
        for (int k = 0; k < NCH; k++) {
            uint32_t bad = 0;
#pragma unroll
            for (int i = CW * k; i < CW * k + CW; i++) { stsm2t(ma + i * 1536, v[i].x, v[i].y); stsm1(ma + i * 1536 + 256, v[i].z); bad |= v[i].w ^ FULL_COUNT; }
            const bool again = __any_sync(0xffffffffu, bad != 0);
            mbar_arrive_if0(sb + B_M + k * 8, L16 | (uint32_t)again);
            if (again) { done = k; break; }
        }
        if (done < NCH) {
            uint32_t bad;
            do {
                look(v, slot);
                bad = 0;
#pragma unroll
                for (int i = 0; i < 6; i++) { stsm2t(ma + i * 1536, v[i].x, v[i].y); stsm1(ma + i * 1536 + 256, v[i].z); bad |= v[i].w ^ FULL_COUNT; }
            } while (++c < SPIN_LIM && __any_sync(0xffffffffu, bad != 0));
            __syncwarp();
#pragma unroll
            for (int k = 0; k < NCH; k++) if (k >= done) mbar_arrive_if0(sb + B_M + k * 8, L16);
        }
        early = c;
        TSTAMP(s, c | t_pack);
    }
    if (!isv) {
        mbar_wait(sb + B_VX + 8, ((NSEG - 1) >> 1) & 1);
        mbar_wait(sb + B_S, 1);
    } else {
        mbar_wait(sb + B_SX + 8, ((NSEG - 1) >> 1) & 1);
        x_scores(sb, NSEG - 1, wq, L16, ev);
        x_probs(sb, NSEG - 1, wq, L16, ev);
        fence_async_smem();
        bar_arrive<NB_T0 + 2, 384>();
        mbar_wait(sb + B_S, 1);
    }
}

__global__ void __launch_bounds__(384, 1)
chain_kernel(const __grid_constant__ CUtensorMap tmWq, const __grid_constant__ CUtensorMap tmWk, const __grid_constant__ CUtensorMap tmWv,
             const __grid_constant__ CUtensorMap tmWo, const __grid_constant__ CUtensorMap tmX, const bf16* __restrict__ mem0, char* const acc) {
    extern __shared__ __align__(1024) uint8_t smem[];
    const uint32_t sb = smem_u32(smem);
    const int tid = threadIdx.x;
    const uint32_t L16 = __shfl_sync(0xffffffffu, (tid & 31) * 16, tid & 31);
    const int w = __shfl_sync(0xffffffffu, tid >> 5, 0), wg = w >> 2, wq = w & 3;
    uint32_t j, h;
    asm("mov.u32 %0, %%cluster_ctarank;" : "=r"(j));
    asm("mov.u32 %0, %%clusterid.x;" : "=r"(h));
    const bool isv = (j == 2);
    const uint32_t peerA = mapa(sb, isv ? 0 : (j ^ 1)), peerB = mapa(sb, isv ? 1 : 2);
    if (DESCPF && w == 10 && L16 < 64) {
        const CUtensorMap* m = L16 == 0 ? &tmX : L16 == 16 ? (isv ? &tmWv : &tmWq) : L16 == 32 ? &tmWk : &tmWo;
        asm volatile("prefetch.tensormap [%0];" ::"l"(m) : "memory");
    }
    if (w == 11) {
        sts128(sb + S_ZERO + L16, 0, 0, 0, 0);
        sts128(sb + S_ZERO + 512 + L16, 0, 0, 0, 0);
        fence_async_smem();
        __syncwarp();
        const int i = L16 >> 4, kb = j * 11 + i;
        if (i < 11 && kb < 32) bulk_s2g(acc + h * 32768 + kb * 1024, sb + S_ZERO, 1024);
        if (i == 11) bulk_s2g(g_time + blockIdx.x * 64, sb + S_ZERO, 256);
        if (i == 12 && blockIdx.x == 0) bulk_s2g(g_flag, sb + S_ZERO, 1024);
        bulk_commit();
    }
    if (tid == 256) {
        for (int c = 0; c < 3; c++) { mbar_init(sb + B_W + 8 * c, 1); mbar_init(sb + B_M + 8 * c, 4); }
        mbar_init(sb + B_WO, 1); mbar_init(sb + B_T, 1);
        mbar_init(sb + B_X, 1); mbar_init(sb + B_X + 8, 1);
        mbar_init(sb + B_S, isv ? 8 : 5);
        mbar_init(sb + B_VX, 1); mbar_init(sb + B_VX + 8, 1);
        mbar_init(sb + B_SX, 1); mbar_init(sb + B_SX + 8, 1);
        asm volatile("fence.mbarrier_init.release.cluster;" ::: "memory");
        const CUtensorMap* m0 = isv ? &tmWv : &tmWq;
        const CUtensorMap* m1 = isv ? &tmWv : &tmWk;
        const int c0 = h * 128 + (isv ? 0 : 64 * j), c1 = h * 128 + (isv ? 64 : 64 * j);
        mbar_expect(sb + B_X, XB_BYTES);
        tma3d(sb + S_XB, &tmX, 0, 0, 0, sb + B_X);
        mbar_expect(sb + B_X + 8, XB_BYTES);
        tma3d(sb + S_XB + XB_BYTES, &tmX, 0, 32, 0, sb + B_X + 8);
#pragma unroll 1
        for (int c = 0; c < (PACE ? 2 : 3); c++) {
            mbar_expect(sb + B_W + 8 * c, 49152);
            tma2d_once(sb + s_w(c), m0, c0, c * 192, sb + B_W + 8 * c);
            tma2d_once(sb + s_w(c) + 24576, m1, c1, c * 192, sb + B_W + 8 * c);
        }
    } else if (tid < 256) {
        uint4 v0, v1, v2;
        v0 = *reinterpret_cast<const uint4*>(mem0 + (tid & 7) * DM + (tid >> 3) * 8);
        v1 = *reinterpret_cast<const uint4*>(mem0 + (tid & 7) * DM + (tid >> 3) * 8 + 256);
        if (tid < 64) v2 = *reinterpret_cast<const uint4*>(mem0 + (tid & 7) * DM + (tid >> 3) * 8 + 512);
        sts128(sb + S_MEM + tid * 16, v0.x, v0.y, v0.z, v0.w);
        sts128(sb + S_MEM + 4096 + tid * 16, v1.x, v1.y, v1.z, v1.w);
        if (tid < 64) sts128(sb + S_MEM + 8192 + tid * 16, v2.x, v2.y, v2.z, v2.w);
    }
    __syncthreads();
    if (wg == 2) {
        asm volatile("setmaxnreg.dec.sync.aligned.u32 %0;" ::"n"(REG_AUX));
        if (!isv) chain_aux<false>(sb, L16, wq, j, h, peerA, peerB, &tmWo, &tmX, acc, &tmWq, &tmWk);
        else chain_aux<true>(sb, L16, wq, j, h, peerA, peerB, &tmWo, &tmX, acc, &tmWv, &tmWv);
        __syncwarp();
        cluster_arrive(); cluster_wait();
        TSTAMP(65, 0);
    } else if (wg == 0) {
        asm volatile("setmaxnreg.inc.sync.aligned.u32 %0;" ::"n"(REG_MAIN0));
        if (!isv) chain_main<0>(sb, L16, wq, j, h, peerA, peerB, acc);
        else chain_main<2>(sb, L16, wq, j, h, peerA, peerB, acc);
        cluster_arrive(); cluster_wait();
    } else {
        asm volatile("setmaxnreg.inc.sync.aligned.u32 %0;" ::"n"(REG_MAIN1));
        if (!isv) chain_main<1>(sb, L16, wq, j, h, peerA, peerB, acc);
        else chain_main<3>(sb, L16, wq, j, h, peerA, peerB, acc);
        cluster_arrive(); cluster_wait();
    }
}

constexpr int NHELP = 36;
constexpr uint32_t H_U = 0;
constexpr uint32_t UT_PITCH = 4368;
constexpr uint32_t H_UT = 65536;
constexpr uint32_t KW_BYTES = 8320;
constexpr uint32_t H_KW = 135424;
constexpr uint32_t H_PAR = 201984;
constexpr uint32_t H_KD = 214272;
constexpr uint32_t H_IDX = 224640;
constexpr uint32_t H_STAGE = 0;
constexpr uint32_t H_RED = 196608;
constexpr uint32_t H_FIN = 212992;
constexpr uint32_t H_OWN = 214016;
constexpr uint32_t H_BAR = 229376;
constexpr uint32_t B_SMEM = H_BAR + 384;
constexpr uint32_t HB_U = H_BAR, HB_WO = H_BAR + 8, HB_EMPTY = H_BAR + 16, HB_FIN = H_BAR + 96, HB_FULL = H_BAR + 128, HB_SENT = H_BAR + 320;
constexpr int RING = 8;
__device__ __align__(1024) uint4 g_part[RING * 9 * 4 * 4 * 128];

__device__ __forceinline__ float2 cmul(float2 a, float2 b) { return make_float2(fmaf(a.x, b.x, -a.y * b.y), fmaf(a.x, b.y, a.y * b.x)); }
__device__ __forceinline__ float2 csqr(float2 a) { return make_float2(fmaf(a.x, a.x, -a.y * a.y), (a.x + a.x) * a.y); }
__device__ __forceinline__ float2 cexp(float zr, float zi, float p) {
    const float m = ex2(zr * p);
    const float r = zi * p;
    const float a = (fabsf(r) < 4194304.f ? r - ((r + 12582912.f) - 12582912.f) : 0.f) * 6.283185307179586f;
    return make_float2(m * __cosf(a), m * __sinf(a));
}
__device__ __forceinline__ uint32_t pack_f16(float lo, float hi) { uint32_t r; asm("cvt.rn.f16x2.f32 %0, %1, %2;" : "=r"(r) : "f"(hi), "f"(lo)); return r; }
__device__ __forceinline__ void mma16h(float* d, const uint32_t* a, uint32_t b0, uint32_t b1) {
    asm volatile("mma.sync.aligned.m16n8k16.row.col.f32.f16.f16.f32 {%0,%1,%2,%3},{%4,%5,%6,%7},{%8,%9},{%0,%1,%2,%3};"
                 : "+f"(d[0]), "+f"(d[1]), "+f"(d[2]), "+f"(d[3]) : "r"(a[0]), "r"(a[1]), "r"(a[2]), "r"(a[3]), "r"(b0), "r"(b1));
}
__device__ __forceinline__ float bf_round(float x) { return __bfloat162float(__float2bfloat16_rn(x)); }
__device__ __forceinline__ uint32_t lds32(uint32_t a) { uint32_t v; asm volatile("ld.shared.b32 %0,[%1];" : "=r"(v) : "r"(a) : "memory"); return v; }
__device__ __forceinline__ uint32_t lds16(uint32_t a) { uint16_t v; asm volatile("ld.shared.u16 %0,[%1];" : "=h"(v) : "r"(a) : "memory"); return v; }

__device__ __forceinline__ void s4d_kernel(uint32_t par, uint32_t kd, int d, int lane, const bf16* __restrict__ logA, const bf16* __restrict__ Aim,
                                           const bf16* __restrict__ Cre, const bf16* __restrict__ Cim, const bf16* __restrict__ logdt) {
    const float dt = bf_round(expf(__bfloat162float(logdt[d])));
    float4 q[4];
    float cmax = 0.f, last = 0.f;
#pragma unroll
    for (int i = 0; i < 4; i++) {
        const int n = d * NST + i * 32 + lane;
        q[i].x = -bf_round(expf(__bfloat162float(logA[n]))) * dt * 1.4426950408889634f;
        q[i].y = __bfloat162float(Aim[n]) * dt * 0.15915494309189535f;
        q[i].z = 2.f * (__bfloat162float(Cre[n]) * dt);
        q[i].w = 2.f * (__bfloat162float(Cim[n]) * dt);
        cmax = fmaxf(cmax, fmaxf(fabsf(q[i].z), fabsf(q[i].w)));
        const float2 e = cexp(q[i].x, q[i].y, 2048.f);
        last += q[i].z * e.x - q[i].w * e.y;
        const float2 w64 = cexp(q[i].x, q[i].y, 64.f);
        sts64(par + 2048 + (i * 32 + lane) * 8, __float_as_uint(w64.x), __float_as_uint(w64.y));
    }
#pragma unroll
    for (int o = 16; o; o >>= 1) { cmax = fmaxf(cmax, __shfl_xor_sync(0xffffffffu, cmax, o)); last += __shfl_xor_sync(0xffffffffu, last, o); }
    const float cs = __uint_as_float(max(__float_as_uint(cmax) & 0x7F800000u, 0x00800000u));
    const float ci = 1.f / cs;
#pragma unroll
    for (int i = 0; i < 4; i++) sts128(par + (i * 32 + lane) * 16, __float_as_uint(q[i].x), __float_as_uint(q[i].y), __float_as_uint(q[i].z * ci), __float_as_uint(q[i].w * ci));
    __syncwarp();
    float acc[5][4];
#pragma unroll
    for (int i = 0; i < 5; i++) acc[i][0] = acc[i][1] = acc[i][2] = acc[i][3] = 0.f;
    const float g = (float)(lane >> 2);
#pragma unroll 2
    for (int ks = 0; ks < 16; ks++) {
        uint32_t A[5][4], B[4][2];
#pragma unroll
        for (int hf = 0; hf < 2; hf++) {
            uint32_t r[4];
            const int n = ks * 8 + hf * 4 + (lane & 3);
            lds128(r, par + n * 16);
            const float2 w64 = lds64f(par + 2048 + n * 8);
            const float2 c = make_float2(__uint_as_float(r[2]), __uint_as_float(r[3]));
            float2 y = cexp(__uint_as_float(r[0]), __uint_as_float(r[1]), g);
#pragma unroll
            for (int k = 0; k < 4; k++) {
                const float2 cy = cmul(c, y);
                B[k][hf] = pack_f16(cy.x, -cy.y);
                if (k < 3) y = csqr(y);
            }
            const float2 xl = cmul(y, w64);
            float2 x0 = cmul(xl, w64), x1 = cmul(x0, w64);
            A[0][2 * hf] = pack_f16(y.x, y.y);
            A[0][2 * hf + 1] = pack_f16(xl.x, xl.y);
#pragma unroll
            for (int k = 0; k < 4; k++) {
                A[k + 1][2 * hf] = pack_f16(x0.x, x0.y);
                A[k + 1][2 * hf + 1] = pack_f16(x1.x, x1.y);
                if (k < 3) { x0 = csqr(x0); x1 = csqr(x1); }
            }
        }
        mma16h(acc[0], A[0], B[0][0], B[0][1]);
#pragma unroll
        for (int k = 0; k < 4; k++) mma16h(acc[k + 1], A[k + 1], B[k][0], B[k][1]);
    }
    __syncwarp();
#pragma unroll
    for (int i = 0; i < 5; i++) {
        sts32(kd + i * 256 + lane * 4, pack_bf16(acc[i][0] * cs, acc[i][1] * cs));
        sts32(kd + i * 256 + 128 + lane * 4, pack_bf16(acc[i][2] * cs, acc[i][3] * cs));
    }
    if (lane == 0) sts32(kd + 1280, pack_bf16(last, 0.f));
    __syncwarp();
}
__device__ __forceinline__ void s4d_expand(uint32_t kw, uint32_t kd, uint32_t idx, int lane) {
    if (lane < 16) sts32(kw + lane * 4, 0);
#pragma unroll 4
    for (int it = 0; it < 16; it++) {
        const int l = (it * 32 + lane) * 4;
        uint32_t j[2];
        lds64(j, idx + l * 2);
        const uint32_t jm = l ? lds16(idx + l * 2 - 2) : 1282;
        const uint32_t vm = lds16(kd + jm), v0 = lds16(kd + (j[0] & 0xFFFF)), v1 = lds16(kd + (j[0] >> 16)), v2 = lds16(kd + (j[1] & 0xFFFF)), v3 = lds16(kd + (j[1] >> 16));
        sts128(kw + 64 + l * 4, v0 | (vm << 16), v1 | (v0 << 16), v2 | (v1 << 16), v3 | (v2 << 16));
    }
    __syncwarp();
}

__device__ __forceinline__ void s4d_conv(uint32_t ut, uint32_t kw, int lane) {
    float acc[16][4];
#pragma unroll
    for (int i = 0; i < 16; i++) acc[i][0] = acc[i][1] = acc[i][2] = acc[i][3] = 0.f;
    const uint32_t ka = kw + 64 + ((lane >> 2) - 2 * (lane & 3)) * 4;
    const uint32_t ua = ut + 256 + lane * 8;
#pragma unroll 1
    for (int rho = 0; rho < 8; rho++) {
        uint32_t B[16][2];
#pragma unroll
        for (int q = 0; q < 16; q++) lds64(B[q], ua + q * 256 - rho * 32);
#pragma unroll
        for (int m = 0; m < 16; m++) {
            uint32_t A[4];
            const uint32_t x = ka + m * 512 + rho * 64;
            A[0] = lds32(x); A[1] = lds32(x + 32); A[2] = lds32(x - 32); A[3] = A[0];
#pragma unroll
            for (int i = m; i < 16; i++) mma16(acc[i], A, B[i - m][0], B[i - m][1]);
        }
    }
    __syncwarp();
    const uint32_t ya = ut + 256 + (lane & 7) * 32 + ((lane >> 3) & 1) * 16 + (lane >> 4) * 256;
#pragma unroll
    for (int i = 0; i < 16; i += 2)
        stsm4t(ya + i * 256, pack_bf16(acc[i][0], acc[i][1]), pack_bf16(acc[i][2], acc[i][3]),
               pack_bf16(acc[i + 1][0], acc[i + 1][1]), pack_bf16(acc[i + 1][2], acc[i + 1][3]));
}

__global__ void __launch_bounds__(384, 1)
helper_kernel(const __grid_constant__ CUtensorMap tmU, const __grid_constant__ CUtensorMap tmY, const __grid_constant__ CUtensorMap tmWo,
              const bf16* __restrict__ logA, const bf16* __restrict__ Aim, const bf16* __restrict__ Cre, const bf16* __restrict__ Cim,
              const bf16* __restrict__ logdt, const bf16* __restrict__ Dskip, bf16* __restrict__ out) {
    extern __shared__ __align__(1024) uint8_t smem[];
    const uint32_t sb = smem_u32(smem);
    const int tid = threadIdx.x, lane = tid & 31;
    const int w = __shfl_sync(0xffffffffu, tid >> 5, 0);
    const int d0 = blockIdx.x * 16;
    HSTAMP(0);
    if (tid == 0) {
        mbar_init(sb + HB_U, 1); mbar_init(sb + HB_WO, 1);
        for (int i = 0; i < 3; i++) mbar_init(sb + HB_EMPTY + 8 * i, 8);
        for (int i = 0; i < 24; i++) mbar_init(sb + HB_FULL + 8 * i, 1);
        for (int i = 0; i < 4; i++) { mbar_init(sb + HB_FIN + 8 * i, 2); mbar_init(sb + HB_SENT + 8 * i, 8); }
        fence_async_smem();
    }
    __syncthreads();
    if (tid == 352) {
        mbar_expect(sb + HB_U, 65536);
        for (int i = 0; i < 8; i++) { if (EVF & 2) tma2d_once(sb + H_U + i * 8192, &tmU, d0, i * 256, sb + HB_U); else tma2d(sb + H_U + i * 8192, &tmU, d0, i * 256, sb + HB_U); if (U_NS) __nanosleep(U_NS); }
    }
    __syncwarp();
    const int m = lane >> 3, r = lane & 7;
    const uint32_t kw = sb + H_KW + w * KW_BYTES;
    if (w < 8) {
        s4d_kernel(kw, sb + H_KD + w * 1296, d0 + w, lane, logA, Aim, Cre, Cim, logdt);
        bar_sync<1, 384>();
        HSTAMP(1);
        {
            uint4* dst = g_part + ((blockIdx.x % 9) * 16 + (w >> 2) * 8 + blockIdx.x / 9) * 128 + (tid & 127);
#pragma unroll 4
            for (int i = 0; i < RING * 2; i++) dst[(i >> 1) * (9 * 16 * 128) + (i & 1) * 512] = make_uint4(0, 0, 0, 0);
        }
        s4d_expand(kw, sb + H_KD + w * 1296, sb + H_IDX, lane);
        bar_arrive<2, 384>();
        s4d_conv(sb + H_UT + w * UT_PITCH, kw, lane);
        bar_sync<3, 384>();
        s4d_expand(kw, sb + H_KD + w * 1296, sb + H_IDX, lane);
        s4d_conv(sb + H_UT + (8 + w) * UT_PITCH, kw, lane);
    } else {
        for (int l = tid - 256; l < SEQ; l += 128) {
            const int jx = l < 128 ? l : (int)__bfloat16_as_ushort(__float2bfloat16_rn((float)l)) - (133 << 7);
            asm volatile("st.shared.u16 [%0], %1;" ::"r"(sb + H_IDX + l * 2), "h"((unsigned short)(jx * 2)) : "memory");
        }
        for (int i = tid - 256; i < 256; i += 128) sts128(sb + H_UT + (i >> 4) * UT_PITCH + (i & 15) * 16, 0, 0, 0, 0);
        mbar_wait(sb + HB_U, 0);
        const uint32_t src = sb + H_U + ((m & 1) * 8 + r) * 32 + (((m >> 1) ^ (r >> 2)) << 4);
        const uint32_t dst = sb + H_UT + 256 + (lane >> 2) * UT_PITCH + (lane & 3) * 8;
#pragma unroll 4
        for (int grp = w - 8; grp < 128; grp += 4) {
            uint32_t v[4];
            ldsm4t(v, src + grp * 512);
            sts64(dst + grp * 32, v[0], v[1]);
            sts64(dst + 8 * UT_PITCH + grp * 32, v[2], v[3]);
        }
        bar_arrive<1, 384>();
        bar_sync<2, 384>();
#pragma unroll 1
        for (int c = w - 8; c < 8; c += 4) s4d_kernel(sb + H_PAR + (w - 8) * 3072, sb + H_KD + c * 1296, d0 + 8 + c, lane, logA, Aim, Cre, Cim, logdt);
        bar_arrive<3, 384>();
    }
    __syncthreads();
    HSTAMP(2);
    const int cc = blockIdx.x % 9, kq = blockIdx.x / 9;
    {
        const __nv_bfloat162 D0 = *reinterpret_cast<const __nv_bfloat162*>(Dskip + d0 + (lane & 3) * 2);
        const __nv_bfloat162 D1 = *reinterpret_cast<const __nv_bfloat162*>(Dskip + d0 + 8 + (lane & 3) * 2);
        const uint32_t ua = sb + H_U + ((m & 1) * 8 + r) * 32 + (((m >> 1) ^ (r >> 2)) << 4);
        const uint32_t ya = sb + H_UT + 256 + ((m >> 1) * 8 + r) * UT_PITCH + (m & 1) * 16;
        for (int grp = w; grp < 128; grp += 12) {
            uint32_t u[4], y[4];
            ldsm4(u, ua + grp * 512);
            ldsm4t(y, ya + grp * 32);
#pragma unroll
            for (int i = 0; i < 4; i++) {
                const __nv_bfloat162 o = __hadd2_rn(*reinterpret_cast<__nv_bfloat162*>(&y[i]), __hmul2_rn(*reinterpret_cast<__nv_bfloat162*>(&u[i]), i < 2 ? D0 : D1));
                y[i] = *reinterpret_cast<const uint32_t*>(&o);
            }
            stsm4(ua + grp * 512, y[0], y[1], y[2], y[3]);
        }
        fence_async_smem();
        __syncthreads();
        if (tid == 0) {
            mbar_expect(sb + HB_WO, 131072);
            for (int i = 0; i < 8; i++) {
                if (YST) asm volatile("cp.async.bulk.tensor.2d.global.shared::cta.bulk_group [%0, {%1,%2}], [%3];" ::"l"(&tmY), "r"(DM + d0), "r"(i * 256), "r"(sb + H_U + i * 8192) : "memory");
                if (EVF & 2) tma2d_once(sb + 65536 + i * 16384, &tmWo, cc * 64, (kq * 8 + i) * 128, sb + HB_WO);
                else tma2d(sb + 65536 + i * 16384, &tmWo, cc * 64, (kq * 8 + i) * 128, sb + HB_WO);
                if (TRICKLE_NS) __nanosleep(TRICKLE_NS);
            }
            bulk_commit();
            asm volatile("cp.async.bulk.wait_group.read 0;" ::: "memory");
        }
    }
    __syncwarp();
    if (w < 8) {
        asm volatile("setmaxnreg.inc.sync.aligned.u32 208;");
        const int wg = w >> 2;
        uint32_t wo[32][4];
        mbar_wait_long(sb + HB_WO, 0);
        const uint32_t a = sb + 65536 + wg * 65536 + ((m >> 1) * 8 + r) * 128 + (((2 * (w & 3) + (m & 1)) ^ r) << 4);
#pragma unroll
        for (int i = 0; i < 32; i++) ldsm4t(wo[i], a + i * 2048);
        __syncthreads();
        HSTAMP(3);
        const int t = tid & 127;
        int st = 0, ph = 0;
#pragma unroll 1
        for (int s = 0; s < NSEG; s++) {
            const uint32_t desc = (((sb + H_STAGE + st * 65536 + wg * 32768) & 0x3FFFF) >> 4) | (8u << 16);
            float d[16];
#pragma unroll
            for (int q = 0; q < HSPLIT; q++) {
                mbar_wait_long(sb + HB_FULL + ((st * 2 + wg) * 4 + q) * 8, ph);
                wg_fence();
#pragma unroll
                for (int i = q * (32 / HSPLIT); i < (q + 1) * (32 / HSPLIT); i++) {
                    if (i == 0) wg_rs_n32<0, 16, 1>(d, wo[i], desc); else wg_rs_n32<1, 16, 1>(d, wo[i], desc + i * 64);
                }
                wg_commit();
            }
            if (s >= 4) mbar_wait_long(sb + HB_FIN + (s & 3) * 8, ((s - 4) >> 2) & 1);
            const uint32_t ra = sb + H_RED + (s & 1) * 8192 + t * 16;
            uint4* dst = g_part + (((s % RING) * 9 + cc) * 16 + wg * 8 + kq) * 128 + t;
            const uint32_t own = sb + H_OWN + (s & 3) * 2048 + t * 16;
            wg_wait<0>();
#pragma unroll
            for (int i = 0; i < 8; i++) { const float a0 = d[i], a1 = d[8 + i]; d[i] = wg ? a1 : a0; d[8 + i] = wg ? a0 : a1; }
#pragma unroll
            for (int i = 0; i < 2; i++) sts128(ra + wg * 4096 + i * 2048, __float_as_uint(d[8 + 4 * i]), __float_as_uint(d[9 + 4 * i]), __float_as_uint(d[10 + 4 * i]), __float_as_uint(d[11 + 4 * i]));
            mbar_arrive_if0(sb + HB_EMPTY + st * 8, lane);
            bar_sync<4, 256>();
            uint32_t p[8];
#pragma unroll
            for (int i = 0; i < 2; i++) lds128(p + 4 * i, ra + (wg ^ 1) * 4096 + i * 2048);
#pragma unroll
            for (int i = 0; i < 2; i++) {
#pragma unroll
                for (int k = 4 * i; k < 4 * i + 4; k++) p[k] = ((__float_as_uint(__uint_as_float(p[k]) + d[k]) + 64) & ~127u) | (s + 1);
                asm volatile("{.reg .pred q; setp.eq.u32 q, %6, %7;\n"
                             "@!q st.relaxed.gpu.global.v4.u32 [%0], {%2,%3,%4,%5};\n"
                             "@q st.shared.v4.u32 [%1], {%2,%3,%4,%5};}"
                             ::"l"(dst + i * 512), "r"(own), "r"(p[4 * i]), "r"(p[4 * i + 1]), "r"(p[4 * i + 2]), "r"(p[4 * i + 3]), "r"(kq), "r"(2 * wg + i) : "memory");
            }
            __syncwarp();
            mbar_arrive_if0(sb + HB_SENT + (s & 3) * 8, lane);
            HSTAMP4(s);
            if (++st == 3) { st = 0; ph ^= 1; }
        }
        if (tid == 0) bulk_wait0();
    } else {
        asm volatile("setmaxnreg.dec.sync.aligned.u32 88;");
        __syncthreads();
        if (w == 8) {
            const uint64_t pol = evict_first();
            int st = 0, ph = 1, ready = 0;
            for (int s = 0; s < NSEG; s++) {
                unsigned c = 0;
                while (ready <= s) {
                    const unsigned f = ld_acquire(&g_flag[kq * NSEG + min(s + (lane & 3), NSEG - 1)]);
                    ready = s + __ffs(~(__ballot_sync(0xffffffffu, f >= 8) & 15)) - 1;
                    if (++c >= LONG_LIM) break;
                    if (ready <= s && FLAG_NS) __nanosleep(FLAG_NS);
                }
                __syncwarp();
                if (lane == 0) {
                    asm volatile("fence.proxy.async.global;" ::: "memory");
                    HSTAMP3(s);
                    mbar_wait_long(sb + HB_EMPTY + st * 8, ph);
#pragma unroll
                    for (int k = 0; k < 2 * HSPLIT; k++) {
                        const int g = k & 1, q = k >> 1;
                        constexpr uint32_t bytes = 32768 / HSPLIT;
                        const uint32_t bar = sb + HB_FULL + ((st * 2 + g) * 4 + q) * 8;
                        mbar_expect(bar, bytes);
                        asm volatile("cp.async.bulk.shared::cluster.global.mbarrier::complete_tx::bytes.L2::cache_hint [%0], [%1], %2, [%3], %4;"
                                     ::"r"(sb + H_STAGE + st * 65536 + g * 32768 + q * bytes), "l"(g_ox + (s * NH + kq * 8 + g * 4) * 512 + q * (bytes / 16)), "r"(bytes), "r"(bar), "l"(pol) : "memory");
                    }
                }
                __syncwarp();
                if (++st == 3) { st = 0; ph ^= 1; }
            }
        } else if (w < 11) {
            const int f = w - 9;
            const uint32_t fa = sb + H_FIN + f * 512;
            for (int s = 0; s < NSEG; s++) {
                mbar_wait_long(sb + HB_SENT + (s & 3) * 8, (s >> 2) & 1);
                const uint4* src = g_part + (((s % RING) * 9 + cc) * 16 + kq * 4) * 128 + f * 64 + lane;
                uint4 v[8];
                lds128(&v[6].x, sb + H_OWN + (s & 3) * 2048 + (f * 64 + lane) * 16);
                lds128(&v[7].x, sb + H_OWN + (s & 3) * 2048 + (f * 64 + 32 + lane) * 16);
                if (FIN0_NS) __nanosleep(FIN0_NS);
                unsigned c = 0;
                while (true) {
                    uint32_t bad = 0;
#pragma unroll
                    for (int i = 0; i < 6; i++) v[i] = ld_poll(src + ((kq + 1 + (i >> 1)) & 3) * 128 + (i & 1) * 32);
#pragma unroll
                    for (int i = 0; i < 6; i++) bad |= (v[i].x ^ (s + 1)) | (v[i].y ^ (s + 1)) | (v[i].z ^ (s + 1)) | (v[i].w ^ (s + 1));
                    if (!__any_sync(0xffffffffu, (bad & 127) != 0) || ++c >= LONG_LIM) break;
                    if (FIN_NS) __nanosleep(FIN_NS);
                }
                mbar_arrive_if0(sb + HB_FIN + (s & 3) * 8, lane);
                uint32_t pk[4];
#pragma unroll
                for (int u = 0; u < 2; u++) {
                    float o[4] = {0.f, 0.f, 0.f, 0.f};
#pragma unroll
                    for (int k = 0; k < 4; k++) {
                        o[0] += __uint_as_float(v[2 * k + u].x & ~127u); o[1] += __uint_as_float(v[2 * k + u].y & ~127u);
                        o[2] += __uint_as_float(v[2 * k + u].z & ~127u); o[3] += __uint_as_float(v[2 * k + u].w & ~127u);
                    }
                    pk[2 * u] = pack_bf16(o[0], o[1]); pk[2 * u + 1] = pack_bf16(o[2], o[3]);
                }
                stsm4t(fa + r * 64 + ((m ^ (r >> 1)) << 4), pk[0], pk[1], pk[2], pk[3]);
                __syncwarp();
                uint32_t o4[4];
                lds128(o4, fa + (lane >> 2) * 64 + (((lane & 3) ^ (lane >> 3)) << 4));
                *reinterpret_cast<uint4*>(out + (s * SEG + kq * 8 + (lane >> 2)) * OUTW + cc * 64 + f * 32 + (lane & 3) * 8) = make_uint4(o4[0], o4[1], o4[2], o4[3]);
                __syncwarp();
                HSTAMP2(s);
            }
            asm volatile("griddepcontrol.wait;" ::: "memory");
        }
    }
}

typedef CUresult (*EncodeFn)(CUtensorMap*, CUtensorMapDataType, cuuint32_t, void*, const cuuint64_t*, const cuuint64_t*, const cuuint32_t*,
                             const cuuint32_t*, CUtensorMapInterleave, CUtensorMapSwizzle, CUtensorMapL2promotion, CUtensorMapFloatOOBfill);

void make_map(EncodeFn fn, CUtensorMap* m, const void* p, int rank, const cuuint64_t* dims, const cuuint64_t* strides, const cuuint32_t* box,
              CUtensorMapSwizzle sw = CU_TENSOR_MAP_SWIZZLE_128B, CUtensorMapL2promotion pr = CU_TENSOR_MAP_L2_PROMOTION_L2_128B) {
    const cuuint32_t es[3] = {1, 1, 1};
    fn(m, CU_TENSOR_MAP_DATA_TYPE_BFLOAT16, rank, const_cast<void*>(p), dims, strides, box, es, CU_TENSOR_MAP_INTERLEAVE_NONE,
       sw, pr, CU_TENSOR_MAP_FLOAT_OOB_FILL_NONE);
}

}

extern "C" void kernel_launch(void* const* d_in, const int* in_sizes, int n_in, void* d_out, int out_size) {
    const bf16* x = (const bf16*)d_in[0];
    const bf16* mem0 = (const bf16*)d_in[1];
    const bf16* Wo = (const bf16*)d_in[5];
    bf16* out = (bf16*)d_out;

    static EncodeFn enc = nullptr;
    static char* acc = nullptr;
    if (!enc) {
        void* p = nullptr;
        cudaGetSymbolAddress(&p, g_acc);
        acc = reinterpret_cast<char*>((reinterpret_cast<uintptr_t>(p) + 32767) & ~(uintptr_t)32767);
        void* fn = nullptr;
        cudaDriverEntryPointQueryResult st;
        cudaGetDriverEntryPoint("cuTensorMapEncodeTiled", &fn, cudaEnableDefault, &st);
        enc = (EncodeFn)fn;
        cudaFuncSetAttribute(chain_kernel, cudaFuncAttributeMaxDynamicSharedMemorySize, A_SMEM);
        cudaFuncSetAttribute(helper_kernel, cudaFuncAttributeMaxDynamicSharedMemorySize, B_SMEM);
    }
    CUtensorMap tmW[3], tmWo, tmX;
    {
        const cuuint64_t dims[2] = {4096, 576}, str[1] = {8192};
        const cuuint32_t box[2] = {64, 192};
        for (int i = 0; i < 3; i++) make_map(enc, &tmW[i], d_in[2 + i], 2, dims, str, box, CU_TENSOR_MAP_SWIZZLE_128B, W_PROMO);
    }
    {
        const cuuint64_t dims[2] = {576, 4096}, str[1] = {1152};
        const cuuint32_t box[2] = {64, 128};
        make_map(enc, &tmWo, Wo, 2, dims, str, box);
    }
    {
        const cuuint64_t dims[3] = {64, 2048, 9}, str[2] = {1152, 128};
        const cuuint32_t box[3] = {64, 32, 9};
        make_map(enc, &tmX, x, 3, dims, str, box);
    }
    CUtensorMap tmU, tmY;
    {
        const cuuint64_t dimsU[2] = {576, 2048}, strU[1] = {1152}, dimsY[2] = {1152, 2048}, strY[1] = {2304};
        const cuuint32_t box[2] = {16, 256};
        make_map(enc, &tmU, d_in[7], 2, dimsU, strU, box, CU_TENSOR_MAP_SWIZZLE_32B);
        make_map(enc, &tmY, out, 2, dimsY, strY, box, CU_TENSOR_MAP_SWIZZLE_32B, CU_TENSOR_MAP_L2_PROMOTION_NONE);
    }
    cudaStream_t st = cudaStreamPerThread;
    {
        cudaLaunchConfig_t cfg = {};
        cfg.gridDim = dim3(96); cfg.blockDim = dim3(384); cfg.dynamicSmemBytes = A_SMEM; cfg.stream = st;
        cudaLaunchAttribute at[1];
        at[0].id = cudaLaunchAttributeClusterDimension;
        at[0].val.clusterDim.x = 3; at[0].val.clusterDim.y = 1; at[0].val.clusterDim.z = 1;
        cfg.attrs = at; cfg.numAttrs = 1;
        cudaLaunchKernelEx(&cfg, chain_kernel, tmW[0], tmW[1], tmW[2], tmWo, tmX, mem0, acc);
    }
    {
        cudaLaunchConfig_t cfg = {};
        cfg.gridDim = dim3(NHELP); cfg.blockDim = dim3(384); cfg.dynamicSmemBytes = B_SMEM; cfg.stream = st;
        cudaLaunchAttribute at[1];
        at[0].id = cudaLaunchAttributeProgrammaticStreamSerialization;
        at[0].val.programmaticStreamSerializationAllowed = 1;
        cfg.attrs = at; cfg.numAttrs = 1;
        cudaLaunchKernelEx(&cfg, helper_kernel, tmU, tmY, tmWo, (const bf16*)d_in[8], (const bf16*)d_in[9], (const bf16*)d_in[10],
                           (const bf16*)d_in[11], (const bf16*)d_in[12], (const bf16*)d_in[13], out);
    }
}
```

```cpp
#include <cuda_runtime.h>
#include <cuda_bf16.h>
#include <cuda_fp16.h>
#include <cuda.h>
#include <stdint.h>

typedef __nv_bfloat16 bf16;

#define WAITFORM 2
#define EVF 15
namespace {

constexpr int DM = 576, NH = 32, DH = 128, SEG = 32, NSEG = 64, SEQ = 2048, NST = 128;
constexpr int OUTW = 2 * DM;
constexpr unsigned SPIN_LIM = 1u << 15;

__device__ __align__(1024) uint4 g_acc[33 * 2048];
__device__ __align__(128) unsigned g_time[NSEG * 96];
__device__ __align__(1024) uint4 g_ox[NSEG * NH * 512];
__device__ __align__(1024) uint4 g_vx[NH * 2 * 512];
__device__ __align__(128) unsigned g_flag[NSEG * 4];
__device__ unsigned g_done_cnt;
__device__ unsigned g_zero_cnt;

__device__ __forceinline__ uint32_t smem_u32(const void* p) { return (uint32_t)__cvta_generic_to_shared(p); }
__device__ __forceinline__ unsigned clk() { unsigned c; asm volatile("mov.u32 %0, %%clock;" : "=r"(c)::"memory"); return c; }
__device__ __forceinline__ unsigned gtime() { unsigned t; asm volatile("mov.u32 %0, %%globaltimer_lo;" : "=r"(t)::"memory"); return t; }
__device__ __forceinline__ uint32_t slot_off(int s) { return (s >> 1) * 32768 + (s & 1) * 512; }
__device__ __forceinline__ uint32_t lane_off(uint32_t L16) { return (L16 & 0x180) * 8 + (L16 & 0x40) * 4 + (L16 & 0x30); }
__device__ __forceinline__ uint32_t mapa(uint32_t a, uint32_t r) { uint32_t o; asm("mapa.shared::cluster.u32 %0, %1, %2;" : "=r"(o) : "r"(a), "r"(r)); return o; }
__device__ __forceinline__ void mbar_init(uint32_t b, uint32_t n) { asm volatile("mbarrier.init.shared::cta.b64 [%0], %1;" ::"r"(b), "r"(n) : "memory"); }
__device__ __forceinline__ void mbar_arrive(uint32_t b) { asm volatile("mbarrier.arrive.shared::cta.b64 _, [%0];" ::"r"(b) : "memory"); }
__device__ __forceinline__ void mbar_expect(uint32_t b, uint32_t tx) { asm volatile("mbarrier.arrive.expect_tx.shared::cta.b64 _, [%0], %1;" ::"r"(b), "r"(tx) : "memory"); }
__device__ __forceinline__ bool mbar_try(uint32_t b, uint32_t par) {
    uint32_t ok;
    asm volatile("{.reg .pred p; mbarrier.try_wait.parity.shared::cta.b64 p, [%1], %2; selp.u32 %0, 1, 0, p;}" : "=r"(ok) : "r"(b), "r"(par) : "memory");
    return ok;
}
__device__ __forceinline__ bool mbar_test(uint32_t b, uint32_t par) {
    uint32_t ok;
    asm volatile("{.reg .pred p; mbarrier.test_wait.parity.shared::cta.b64 p, [%1], %2; selp.u32 %0, 1, 0, p;}" : "=r"(ok) : "r"(b), "r"(par) : "memory");
    return ok;
}
__device__ __forceinline__ void mbar_wait(uint32_t b, uint32_t par) {
    asm volatile("{.reg .pred p, q; .reg .u32 c; mov.u32 c, 0;\n"
                 "W: add.u32 c, c, 1; setp.ge.u32 q, c, %2;\n @q bra D;\n mbarrier.try_wait.parity.shared::cta.b64 p, [%0], %1;\n"
                 "@!p bra W;\n D:\n}" ::"r"(b), "r"(par), "n"(SPIN_LIM) : "memory");
}
constexpr unsigned LONG_LIM = 1u << 17;
__device__ __forceinline__ void mbar_wait_long(uint32_t b, uint32_t par) {
    asm volatile("{.reg .pred p, q; .reg .u32 c; mov.u32 c, 0;\n"
                 "W: mbarrier.try_wait.parity.shared::cta.b64 p, [%0], %1;\n"
                 "@p bra D;\n add.u32 c, c, 1; setp.lt.u32 q, c, %2;\n @q bra W;\n D:\n}" ::"r"(b), "r"(par), "n"(LONG_LIM) : "memory");
}
__device__ __forceinline__ void cluster_sync() { asm volatile("barrier.cluster.arrive.aligned; barrier.cluster.wait.aligned;" ::: "memory"); }
__device__ __forceinline__ void fence_async_smem() { asm volatile("fence.proxy.async.shared::cta;" ::: "memory"); }
__device__ __forceinline__ void ldsm4(uint32_t* r, uint32_t a) { asm volatile("ldmatrix.sync.aligned.m8n8.x4.shared.b16 {%0,%1,%2,%3},[%4];" : "=r"(r[0]), "=r"(r[1]), "=r"(r[2]), "=r"(r[3]) : "r"(a) : "memory"); }
__device__ __forceinline__ void ldsm4t(uint32_t* r, uint32_t a) { asm volatile("ldmatrix.sync.aligned.m8n8.x4.trans.shared.b16 {%0,%1,%2,%3},[%4];" : "=r"(r[0]), "=r"(r[1]), "=r"(r[2]), "=r"(r[3]) : "r"(a) : "memory"); }
__device__ __forceinline__ void stsm1(uint32_t a, uint32_t r0) { asm volatile("stmatrix.sync.aligned.m8n8.x1.shared.b16 [%0],{%1};" ::"r"(a), "r"(r0) : "memory"); }
__device__ __forceinline__ void stsm2t(uint32_t a, uint32_t r0, uint32_t r1) { asm volatile("stmatrix.sync.aligned.m8n8.x2.trans.shared.b16 [%0],{%1,%2};" ::"r"(a), "r"(r0), "r"(r1) : "memory"); }
__device__ __forceinline__ void stsm4t(uint32_t a, uint32_t r0, uint32_t r1, uint32_t r2, uint32_t r3) { asm volatile("stmatrix.sync.aligned.m8n8.x4.trans.shared.b16 [%0],{%1,%2,%3,%4};" ::"r"(a), "r"(r0), "r"(r1), "r"(r2), "r"(r3) : "memory"); }
__device__ __forceinline__ void stsm4(uint32_t a, uint32_t r0, uint32_t r1, uint32_t r2, uint32_t r3) { asm volatile("stmatrix.sync.aligned.m8n8.x4.shared.b16 [%0],{%1,%2,%3,%4};" ::"r"(a), "r"(r0), "r"(r1), "r"(r2), "r"(r3) : "memory"); }
__device__ __forceinline__ void sts32(uint32_t a, uint32_t v) { asm volatile("st.shared.b32 [%0], %1;" ::"r"(a), "r"(v) : "memory"); }
__device__ __forceinline__ void sts64(uint32_t a, uint32_t x, uint32_t y) { asm volatile("st.shared.v2.b32 [%0], {%1,%2};" ::"r"(a), "r"(x), "r"(y) : "memory"); }
__device__ __forceinline__ void sts128(uint32_t a, uint32_t x, uint32_t y, uint32_t z, uint32_t w) { asm volatile("st.shared.v4.b32 [%0], {%1,%2,%3,%4};" ::"r"(a), "r"(x), "r"(y), "r"(z), "r"(w) : "memory"); }
__device__ __forceinline__ void lds64(uint32_t* r, uint32_t a) { asm volatile("ld.shared.v2.b32 {%0,%1},[%2];" : "=r"(r[0]), "=r"(r[1]) : "r"(a) : "memory"); }
__device__ __forceinline__ float2 lds64f(uint32_t a) { float2 v; asm volatile("ld.shared.v2.f32 {%0,%1},[%2];" : "=f"(v.x), "=f"(v.y) : "r"(a) : "memory"); return v; }
__device__ __forceinline__ void lds128(uint32_t* r, uint32_t a) { asm volatile("ld.shared.v4.b32 {%0,%1,%2,%3},[%4];" : "=r"(r[0]), "=r"(r[1]), "=r"(r[2]), "=r"(r[3]) : "r"(a) : "memory"); }
__device__ __forceinline__ void st_async64(uint32_t a, uint32_t x, uint32_t y, uint32_t bar) {
    asm volatile("st.async.weak.shared::cluster.mbarrier::complete_tx::bytes.v2.b32 [%0], {%1,%2}, [%3];" ::"r"(a), "r"(x), "r"(y), "r"(bar) : "memory");
}
__device__ __forceinline__ void st_async32(uint32_t a, uint32_t x, uint32_t bar) {
    asm volatile("st.async.weak.shared::cluster.mbarrier::complete_tx::bytes.b32 [%0], %1, [%2];" ::"r"(a), "r"(x), "r"(bar) : "memory");
}
__device__ __forceinline__ void ldsm2(uint32_t* r, uint32_t a) { asm volatile("ldmatrix.sync.aligned.m8n8.x2.shared.b16 {%0,%1},[%2];" : "=r"(r[0]), "=r"(r[1]) : "r"(a) : "memory"); }
__device__ __forceinline__ uint32_t pack_f16_sat(float lo, float hi) { uint32_t r; asm("cvt.rn.satfinite.f16x2.f32 %0, %1, %2;" : "=r"(r) : "f"(hi), "f"(lo)); return r; }
__device__ __forceinline__ __half2 as_h2(uint32_t x) { return *reinterpret_cast<__half2*>(&x); }
__device__ __forceinline__ uint32_t as_u32(__half2 x) { return *reinterpret_cast<uint32_t*>(&x); }
__device__ __forceinline__ uint32_t pack_bf16(float lo, float hi) { uint32_t r; asm("cvt.rn.bf16x2.f32 %0, %1, %2;" : "=r"(r) : "f"(hi), "f"(lo)); return r; }
__device__ __forceinline__ float ex2(float x) { float r; asm("ex2.approx.ftz.f32 %0, %1;" : "=f"(r) : "f"(x)); return r; }
__device__ __forceinline__ float rcp(float x) { float r; asm("rcp.approx.ftz.f32 %0, %1;" : "=f"(r) : "f"(x)); return r; }
__device__ __forceinline__ void mma16(float* d, const uint32_t* a, uint32_t b0, uint32_t b1) {
    asm volatile("mma.sync.aligned.m16n8k16.row.col.f32.bf16.bf16.f32 {%0,%1,%2,%3},{%4,%5,%6,%7},{%8,%9},{%0,%1,%2,%3};"
                 : "+f"(d[0]), "+f"(d[1]), "+f"(d[2]), "+f"(d[3]) : "r"(a[0]), "r"(a[1]), "r"(a[2]), "r"(a[3]), "r"(b0), "r"(b1));
}
__device__ __forceinline__ void mma16z(float* d, const uint32_t* a, uint32_t b0, uint32_t b1) {
    asm volatile("mma.sync.aligned.m16n8k16.row.col.f32.bf16.bf16.f32 {%0,%1,%2,%3},{%4,%5,%6,%7},{%8,%9},{%10,%10,%10,%10};"
                 : "=f"(d[0]), "=f"(d[1]), "=f"(d[2]), "=f"(d[3]) : "r"(a[0]), "r"(a[1]), "r"(a[2]), "r"(a[3]), "r"(b0), "r"(b1), "f"(0.f));
}
__device__ __forceinline__ void mma8(float* d, uint32_t a0, uint32_t a1, uint32_t b0) {
    asm volatile("mma.sync.aligned.m16n8k8.row.col.f32.bf16.bf16.f32 {%0,%1,%2,%3},{%4,%5},{%6},{%0,%1,%2,%3};"
                 : "+f"(d[0]), "+f"(d[1]), "+f"(d[2]), "+f"(d[3]) : "r"(a0), "r"(a1), "r"(b0));
}
template <int ACC>
__device__ __forceinline__ void mma_sp(float* d, const uint32_t* a, const uint32_t* b) {
    if (ACC)
        asm volatile("mma.sp::ordered_metadata.sync.aligned.m16n8k32.row.col.f32.bf16.bf16.f32 {%0,%1,%2,%3},{%4,%5,%6,%7},{%8,%9,%10,%11},{%0,%1,%2,%3},%12,0x0;"
                     : "+f"(d[0]), "+f"(d[1]), "+f"(d[2]), "+f"(d[3])
                     : "r"(a[0]), "r"(a[1]), "r"(a[2]), "r"(a[3]), "r"(b[0]), "r"(b[1]), "r"(b[2]), "r"(b[3]), "r"(0xEEEE4444u));
    else
        asm volatile("mma.sp::ordered_metadata.sync.aligned.m16n8k32.row.col.f32.bf16.bf16.f32 {%0,%1,%2,%3},{%4,%5,%6,%7},{%8,%9,%10,%11},{%13,%13,%13,%13},%12,0x0;"
                     : "=f"(d[0]), "=f"(d[1]), "=f"(d[2]), "=f"(d[3])
                     : "r"(a[0]), "r"(a[1]), "r"(a[2]), "r"(a[3]), "r"(b[0]), "r"(b[1]), "r"(b[2]), "r"(b[3]), "r"(0xEEEE4444u), "f"(0.f));
}
__device__ __forceinline__ void mbar_arrive_if0(uint32_t b, uint32_t z) { asm volatile("{.reg .pred p; setp.eq.u32 p, %1, 0; @p mbarrier.arrive.shared::cta.b64 _, [%0];}" ::"r"(b), "r"(z) : "memory"); }
__device__ __forceinline__ void mbar_expect_if0(uint32_t b, uint32_t tx, uint32_t z) { asm volatile("{.reg .pred p; setp.eq.u32 p, %2, 0; @p mbarrier.arrive.expect_tx.shared::cta.b64 _, [%0], %1;}" ::"r"(b), "r"(tx), "r"(z) : "memory"); }
__device__ __forceinline__ float lds32f(uint32_t a) { float v; asm volatile("ld.shared.f32 %0,[%1];" : "=f"(v) : "r"(a) : "memory"); return v; }
__device__ __forceinline__ void wg_fence() { asm volatile("wgmma.fence.sync.aligned;" ::: "memory"); }
__device__ __forceinline__ void wg_commit() { asm volatile("wgmma.commit_group.sync.aligned;" ::: "memory"); }
template <int N> __device__ __forceinline__ void wg_wait() { asm volatile("wgmma.wait_group.sync.aligned %0;" ::"n"(N) : "memory"); }
__device__ __forceinline__ void delay(unsigned n) { if (n) { const unsigned t0 = clk(); while (clk() - t0 < n) {} } }
template <int ACC, uint32_t DHI = 0x40000040u, int TB = 0>
__device__ __forceinline__ void wg_rs_n32(float* d, const uint32_t* a, uint32_t dlo) {
    if (ACC)
        asm volatile("{.reg .b64 db; mov.b64 db, {%20, %21};\n"
                     "wgmma.mma_async.sync.aligned.m64n32k16.f32.bf16.bf16 {%0,%1,%2,%3,%4,%5,%6,%7,%8,%9,%10,%11,%12,%13,%14,%15},{%16,%17,%18,%19},db,1,1,1,%22;}"
                     : "+f"(d[0]), "+f"(d[1]), "+f"(d[2]), "+f"(d[3]), "+f"(d[4]), "+f"(d[5]), "+f"(d[6]), "+f"(d[7]),
                       "+f"(d[8]), "+f"(d[9]), "+f"(d[10]), "+f"(d[11]), "+f"(d[12]), "+f"(d[13]), "+f"(d[14]), "+f"(d[15])
                     : "r"(a[0]), "r"(a[1]), "r"(a[2]), "r"(a[3]), "r"(dlo), "r"(DHI), "n"(TB));
    else
        asm volatile("{.reg .b64 db; mov.b64 db, {%20, %21};\n"
                     "wgmma.mma_async.sync.aligned.m64n32k16.f32.bf16.bf16 {%0,%1,%2,%3,%4,%5,%6,%7,%8,%9,%10,%11,%12,%13,%14,%15},{%16,%17,%18,%19},db,0,1,1,%22;}"
                     : "=f"(d[0]), "=f"(d[1]), "=f"(d[2]), "=f"(d[3]), "=f"(d[4]), "=f"(d[5]), "=f"(d[6]), "=f"(d[7]),
                       "=f"(d[8]), "=f"(d[9]), "=f"(d[10]), "=f"(d[11]), "=f"(d[12]), "=f"(d[13]), "=f"(d[14]), "=f"(d[15])
                     : "r"(a[0]), "r"(a[1]), "r"(a[2]), "r"(a[3]), "r"(dlo), "r"(DHI), "n"(TB));
}
__device__ __forceinline__ uint32_t desc_lo(uint32_t addr) { return ((addr & 0x3FFFF) >> 4) | (1u << 16); }
__device__ __forceinline__ void tma2d(uint32_t dst, const CUtensorMap* m, int c0, int c1, uint32_t bar) {
    asm volatile("cp.async.bulk.tensor.2d.shared::cluster.global.mbarrier::complete_tx::bytes [%0], [%1, {%2,%3}], [%4];"
                 ::"r"(dst), "l"(m), "r"(c0), "r"(c1), "r"(bar) : "memory");
}
__device__ __forceinline__ uint64_t evict_first() { uint64_t p; asm("createpolicy.fractional.L2::evict_first.b64 %0, 1.0;" : "=l"(p)); return p; }
__device__ __forceinline__ void tma2d_once(uint32_t dst, const CUtensorMap* m, int c0, int c1, uint32_t bar) {
    const uint64_t pol = evict_first();
    asm volatile("cp.async.bulk.tensor.2d.shared::cluster.global.mbarrier::complete_tx::bytes.L2::cache_hint [%0], [%1, {%2,%3}], [%4], %5;"
                 ::"r"(dst), "l"(m), "r"(c0), "r"(c1), "r"(bar), "l"(pol) : "memory");
}
__device__ __forceinline__ void tma3d(uint32_t dst, const CUtensorMap* m, int c0, int c1, int c2, uint32_t bar) {
    asm volatile("cp.async.bulk.tensor.3d.shared::cluster.global.mbarrier::complete_tx::bytes [%0], [%1, {%2,%3,%4}], [%5];"
                 ::"r"(dst), "l"(m), "r"(c0), "r"(c1), "r"(c2), "r"(bar) : "memory");
}
__device__ __forceinline__ void tma3d_mc(uint32_t dst, const CUtensorMap* m, int c0, int c1, int c2, uint32_t bar, uint16_t mask) {
    if (EVF & 8) asm volatile("cp.async.bulk.tensor.3d.shared::cluster.global.mbarrier::complete_tx::bytes.multicast::cluster.L2::cache_hint [%0], [%1, {%2,%3,%4}], [%5], %6, %7;"
                 ::"r"(dst), "l"(m), "r"(c0), "r"(c1), "r"(c2), "r"(bar), "h"(mask), "l"(evict_first()) : "memory");
    else
    asm volatile("cp.async.bulk.tensor.3d.shared::cluster.global.mbarrier::complete_tx::bytes.multicast::cluster [%0], [%1, {%2,%3,%4}], [%5], %6;"
                 ::"r"(dst), "l"(m), "r"(c0), "r"(c1), "r"(c2), "r"(bar), "h"(mask) : "memory");
}
__device__ __forceinline__ void bulk_g2s_mc(uint32_t dst, const void* src, uint32_t bytes, uint32_t bar, uint16_t mask) {
    asm volatile("cp.async.bulk.shared::cluster.global.mbarrier::complete_tx::bytes.multicast::cluster [%0], [%1], %2, [%3], %4;"
                 ::"r"(dst), "l"(src), "r"(bytes), "r"(bar), "h"(mask) : "memory");
}
__device__ __forceinline__ void tma2d_prefetch(const CUtensorMap* m, int c0, int c1) {
    asm volatile("cp.async.bulk.prefetch.tensor.2d.L2.global [%0, {%1,%2}];" ::"l"(m), "r"(c0), "r"(c1) : "memory");
}
__device__ __forceinline__ void bulk_s2c(uint32_t dst, uint32_t src, uint32_t bytes, uint32_t bar) {
    asm volatile("cp.async.bulk.shared::cluster.shared::cta.mbarrier::complete_tx::bytes [%0], [%1], %2, [%3];" ::"r"(dst), "r"(src), "r"(bytes), "r"(bar) : "memory");
}
__device__ __forceinline__ void bulk_s2g(void* dst, uint32_t src, uint32_t bytes) {
    asm volatile("cp.async.bulk.global.shared::cta.bulk_group [%0], [%1], %2;" ::"l"(dst), "r"(src), "r"(bytes) : "memory");
}
__device__ __forceinline__ void bulk_commit() { asm volatile("cp.async.bulk.commit_group;" ::: "memory"); }
__device__ __forceinline__ void bulk_wait0() { asm volatile("cp.async.bulk.wait_group 0;" ::: "memory"); }
__device__ __forceinline__ uint4 ld_poll(const void* p) {
    uint4 v;
    asm volatile("ld.relaxed.gpu.global.v4.u32 {%0,%1,%2,%3},[%4];" : "=r"(v.x), "=r"(v.y), "=r"(v.z), "=r"(v.w) : "l"(p) : "memory");
    return v;
}
template <int IMM>
__device__ __forceinline__ void ld_poll_at(uint4& v, const void* p) {
    asm volatile("ld.relaxed.gpu.global.v4.u32 {%0,%1,%2,%3},[%4+%5];" : "=r"(v.x), "=r"(v.y), "=r"(v.z), "=r"(v.w) : "l"(p), "n"(IMM) : "memory");
}
__device__ __forceinline__ void look(uint4 (&v)[6], const void* p) {
    ld_poll_at<0>(v[0], p); ld_poll_at<16384>(v[1], p); ld_poll_at<64>(v[2], p);
    ld_poll_at<16384 + 64>(v[3], p); ld_poll_at<128>(v[4], p); ld_poll_at<16384 + 128>(v[5], p);
}
__device__ __forceinline__ unsigned ld_acquire(const unsigned* p) { unsigned v; asm volatile("ld.acquire.gpu.global.u32 %0,[%1];" : "=r"(v) : "l"(p) : "memory"); return v; }
__device__ __forceinline__ void red_release(unsigned* p, unsigned v) { asm volatile("red.release.gpu.global.add.u32 [%0], %1;" ::"l"(p), "r"(v) : "memory"); }

template <int ID, int N> __device__ __forceinline__ void bar_sync() { asm volatile("bar.sync %0, %1;" ::"n"(ID), "n"(N) : "memory"); }
template <int ID, int N> __device__ __forceinline__ void bar_arrive() { asm volatile("bar.arrive %0, %1;" ::"n"(ID), "n"(N) : "memory"); }
__device__ __forceinline__ void cluster_arrive() { asm volatile("barrier.cluster.arrive.relaxed.aligned;" ::: "memory"); }
__device__ __forceinline__ void cluster_wait() { asm volatile("barrier.cluster.wait.aligned;" ::: "memory"); }

constexpr uint32_t XB_BYTES = 36864;
constexpr uint32_t S_XB = 0;
constexpr uint32_t S_QM = 73728;
constexpr uint32_t S_KM = 74752;
constexpr uint32_t S_OM = 75776;
constexpr uint32_t S_SP = 77824;
constexpr uint32_t S_SUM = 80384;
constexpr uint32_t S_TGT = 81408;
constexpr uint32_t S_VM = 147456;
constexpr uint32_t S_QX = 86016;
constexpr uint32_t S_PX = S_QX;
constexpr uint32_t S_KX = 94208;
constexpr uint32_t S_VX = 102400;
constexpr uint32_t S_SX = 135168;
constexpr uint32_t S_OX = 155648;
constexpr uint32_t S_MEM = 172032;
constexpr uint32_t S_WO = 181248;
constexpr uint32_t S_BAR = 230400;
constexpr uint32_t S_ZERO = S_BAR + 128;
constexpr uint32_t A_SMEM = S_ZERO + 1024;
__host__ __device__ constexpr uint32_t s_w(int c) { return c == 0 ? S_WO : 73728 + (c - 1) * 49152; }
constexpr uint32_t B_W = S_BAR, B_WO = S_BAR + 24, B_X = S_BAR + 32, B_S = S_BAR + 48, B_VX = S_BAR + 56, B_SX = S_BAR + 72, B_M = S_BAR + 88, B_T = S_BAR + 112;
constexpr int NB_QK = 1, NB_O = 2, NB_RED = 3, NB_P = 4, NB_AUX = 5, NB_PRO = 6, NB_X = 7, NB_GO = 8, NB_L = 9, NB_PV = 10, NB_T0 = 11, NB_PR = 14, NB_VW = 15;

constexpr float SM_SCALE = 0.08838834764831845f * 1.4426950408889634f;
constexpr uint32_t ONES = 0x3F803F80u;
constexpr uint32_t FULL_COUNT = 0x4200u;
#define XLIM NSEG
#define TGT_NS 1028
#define LOOK_NS 100
#define RCP_AT 2
#define NCH 2
#define XTMA_NS 50
#define REG_MAIN0 232
#define REG_MAIN1 232
#define REG_AUX 40

#define HAND_AT 26
#define PUB_EARLY 0
#define W_PROMO CU_TENSOR_MAP_L2_PROMOTION_L2_128B
#define DESCPF 1
#define WO_AFTER 2
#define FIRST_NS 250
#define PACE 1
#define U0_NS 4500
#define HSPLIT 2
#define FIN_NS 40
#define WO_LOOP 0
#define YST 1
#define TRICKLE_NS 700
#define REFRESH 0
#define U_NS 0
#define FIN0_NS 0
#define XEARLY 1
#define PRCP 1
#define PR_AT 18
#define VXTEST 0
#define ADAPT 3
#define AD_UP 9
#define WO_DELAY 0
#define U_PROMO CU_TENSOR_MAP_L2_PROMOTION_L2_128B
#define DEP_AT 1
#define FLAG_NS 40
static_assert(REG_MAIN0 + REG_MAIN1 + REG_AUX <= 504, "the three warpgroups share 3 x 168 registers");
#define HSTAMP(i) do {} while (0)
#define HSTAMP2(i) do {} while (0)
#define HSTAMP3(i) do {} while (0)
#define HSTAMP4(i) do {} while (0)
#define TSTAMP(i, e) do {} while (0)

__device__ __forceinline__ void load_scores(uint32_t a, __half2 (&hs)[5]) {
    uint32_t r[10];
    ldsm4(r, a);
    ldsm4(r + 4, a + 512);
    ldsm2(r + 8, a + 1024);
    const __half2 hf = as_h2(0x38003800u);
#pragma unroll
    for (int T = 0; T < 5; T++) hs[T] = __hfma2(as_h2(r[2 * T]), hf, __hmul2(as_h2(r[2 * T + 1]), hf));
}
__device__ __forceinline__ void softmax_exp(const __half2 (&hs)[5], float (&ev)[10]) {
    __half2 m = __hmax2(__hmax2(__hmax2(hs[0], hs[1]), __hmax2(hs[2], hs[3])), hs[4]);
    const uint32_t mu = as_u32(m);
    const uint32_t m1 = __shfl_xor_sync(0xffffffffu, mu, 1), m2 = __shfl_xor_sync(0xffffffffu, mu, 2), m3 = __shfl_xor_sync(0xffffffffu, mu, 3);
    m = __hmax2(__hmax2(m, as_h2(m1)), __hmax2(as_h2(m2), as_h2(m3)));
    const float mc = -fmaxf(__low2float(m), __high2float(m)) * (2.f * SM_SCALE);
#pragma unroll
    for (int T = 0; T < 5; T++) {
        ev[2 * T] = ex2(fmaf(__low2float(hs[T]), 2.f * SM_SCALE, mc));
        ev[2 * T + 1] = ex2(fmaf(__high2float(hs[T]), 2.f * SM_SCALE, mc));
    }
}

__device__ __forceinline__ void x_scores(uint32_t sb, int seg, int wq, uint32_t L16, float (&ev)[10]) {
    __half2 hs[5];
    load_scores(sb + S_SX + (seg & 1) * 5120 + wq * 1280 + L16, hs);
    const int dg = (int)(L16 >> 6) - (int)((L16 >> 3) & 6) + 8 * wq;
#pragma unroll
    for (int T = 0; T < 4; T++) {
        uint32_t u = as_u32(hs[T]);
        if (dg < 8 * T + 1) u = (u & 0xFFFFu) | 0xFC000000u;
        if (dg < 8 * T) u = 0xFC00FC00u;
        hs[T] = as_h2(u);
    }
    softmax_exp(hs, ev);
}
__device__ __forceinline__ void x_probs(uint32_t sb, int seg, int wq, uint32_t L16, const float (&ev)[10]) {
    float l = ((ev[0] + ev[1]) + (ev[2] + ev[3])) + ((ev[4] + ev[5]) + (ev[6] + ev[7])) + (ev[8] + ev[9]);
    const float l1 = __shfl_xor_sync(0xffffffffu, l, 1), l2 = __shfl_xor_sync(0xffffffffu, l, 2), l3 = __shfl_xor_sync(0xffffffffu, l, 3);
    const float r = rcp((l + l1) + (l2 + l3));
    const uint32_t a = sb + S_PX + (seg & 1) * 4096 + wq * 640 + (L16 >> 2);
#pragma unroll
    for (int i = 0; i < 5; i++) sts32(a + i * 128, pack_bf16(ev[2 * i] * r, ev[2 * i + 1] * r));
}
__device__ __forceinline__ void x_pv_load(uint32_t sb, int seg, int w, uint32_t L16, uint32_t (&a)[3][4]) {
    lds128(a[0], sb + S_VX + (seg & 3) * 8192 + w * 1024 + L16);
    lds128(a[1], sb + S_VX + (seg & 3) * 8192 + w * 1024 + 512 + L16);
    lds64(a[2], sb + S_VM + (seg & 3) * 2048 + w * 256 + (L16 >> 1));
    a[2][2] = 0; a[2][3] = 0;
}
__device__ __forceinline__ void x_pv_run(uint32_t sb, int seg, const uint32_t (&a)[3][4], uint32_t (&pk)[8]) {
    const uint32_t d = ((sb + S_PX + (seg & 1) * 4096) & 0x3FFFF) >> 4;
    float o[16];
    wg_fence();
    wg_rs_n32<0, 40>(o, a[0], d | (8u << 16));
    wg_rs_n32<1, 40>(o, a[1], (d + 16) | (8u << 16));
    wg_rs_n32<1, 40>(o, a[2], d + 32);
    wg_commit();
    wg_wait<0>();
#pragma unroll
    for (int i = 0; i < 8; i++) pk[i] = pack_bf16(o[2 * i], o[2 * i + 1]);
}
__device__ __forceinline__ void x_pv_store(uint32_t sb, int seg, int w, uint32_t L16, const uint32_t (&pk)[8]) {
    const uint32_t a = sb + S_OX + (seg & 1) * 8192 + w * 1024 + L16;
    stsm4(a, pk[0], pk[1], pk[2], pk[3]);
    stsm4(a + 512, pk[4], pk[5], pk[6], pk[7]);
}
template <int BAR, int CNT>
__device__ __forceinline__ void x_pv_both(uint32_t sb, int seg, int wq, uint32_t L16) {
    uint32_t pva[3][4], pk[8];
    x_pv_load(sb, seg, wq + 4, L16, pva);
    bar_sync<BAR, CNT>();
    x_pv_run(sb, seg, pva, pk);
    x_pv_load(sb, seg, wq, L16, pva);
    x_pv_store(sb, seg, wq + 4, L16, pk);
    x_pv_run(sb, seg, pva, pk);
    x_pv_store(sb, seg, wq, L16, pk);
}
__device__ __forceinline__ void ox_store(uint32_t sb, int seg, uint32_t h) {
    fence_async_smem();
    bulk_s2g(g_ox + (seg * NH + h) * 512, sb + S_OX + (seg & 1) * 8192, 8192);
    bulk_commit();
}
__device__ __forceinline__ void ox_publish(int seg, uint32_t h) {
    bulk_wait0();
    asm volatile("fence.proxy.async.global;" ::: "memory");
    asm volatile("red.relaxed.gpu.global.add.u32 [%0], 1;" ::"l"(&g_flag[(h >> 3) * NSEG + seg]) : "memory");
}
__device__ __forceinline__ void vx_store(uint32_t sb, int seg, uint32_t h) {
    fence_async_smem();
    bulk_s2g(g_vx + (h * 2 + (seg & 1)) * 512, sb + S_VX + (seg & 3) * 8192, 8192);
    bulk_commit();
}
__device__ __forceinline__ void vx_fetch(uint32_t sb, int seg, uint32_t h) {
    bulk_wait0();
    bulk_g2s_mc(sb + S_VX + (seg & 3) * 8192, g_vx + (h * 2 + (seg & 1)) * 512, 8192, sb + B_VX + (seg & 1) * 8, 3);
}

__device__ __forceinline__ void x_pack(const float (&d)[16], uint32_t (&pk)[8]) {
#pragma unroll
    for (int i = 0; i < 8; i++) pk[i] = pack_bf16(d[2 * i], d[2 * i + 1]);
}
__device__ __forceinline__ void x_write(uint32_t sb, const uint32_t (&pk)[8], int seg, bool isv, int w, uint32_t L16) {
    if (!isv) {
        const uint32_t a = sb + S_QX + (w >> 2) * 8192 + (seg & 1) * 4096 + (w & 3) * 256 + (L16 & 0xF0) + (L16 & 0x100) * 4;
        stsm4t(a, pk[0], pk[1], pk[2], pk[3]);
        stsm4t(a + 2048, pk[4], pk[5], pk[6], pk[7]);
    } else {
        const uint32_t a = sb + S_VX + (seg & 3) * 8192 + w * 1024 + L16;
        sts128(a, pk[0], pk[1], pk[2], pk[3]);
        sts128(a + 512, pk[4], pk[5], pk[6], pk[7]);
    }
}

template <int K0, int K1>
__device__ __forceinline__ void x_project(float (&d)[16], const uint32_t (&wA)[36][4], uint32_t desc) {
#pragma unroll
    for (int i = K0; i < K1; i++) {
        const uint32_t db = desc + (((i >> 2) * 4096 + (i & 3) * 32) >> 4);
        if (i == 0) wg_rs_n32<0>(d, wA[i], db); else wg_rs_n32<1>(d, wA[i], db);
    }
}

__device__ __forceinline__ void mem_scores(uint32_t sb, uint32_t peerA, uint32_t peerB, uint32_t off, const uint32_t (&q0)[4], const uint32_t (&q1)[4],
                                           const uint32_t (&k0)[4], const uint32_t (&k1)[4]) {
    float e0[4], o0[4], e1[4], o1[4];
    mma16z(e0, q0, k0[0], k0[1]);
    mma16z(o0, q0, k0[2], k0[3]);
    mma16z(e1, q1, k1[0], k1[1]);
    mma16z(o1, q1, k1[2], k1[3]);
    const uint32_t sc = pack_f16_sat((e0[0] + o0[2]) + (e1[0] + o1[2]), (e0[1] + o0[3]) + (e1[1] + o1[3]));
    st_async32(peerB + off, sc, peerB + B_S);
    st_async32(peerA + off, sc, peerA + B_S);
    sts32(sb + off, sc);
    __syncwarp();
}

__device__ __forceinline__ unsigned post_time(int s, uint32_t L16, unsigned early) {
    delay(1);
    const unsigned t = (gtime() & ~3u) | 1 | (early ? 2 : 0);
    if (L16 == 0) asm volatile("st.relaxed.gpu.global.u32 [%0], %1;" ::"l"(g_time + s * 96 + blockIdx.x), "r"(t) : "memory");
    return t;
}
__device__ __forceinline__ void plan_look(uint32_t sb, int s, uint32_t L16, unsigned t, int& state) {
    const char* p = reinterpret_cast<const char*>(g_time) + s * 384 + (L16 < 384 ? L16 : 0);
    uint4 v;
    unsigned c = 0;
    do { v = ld_poll(p); } while (__any_sync(0xffffffffu, (v.x & v.y & v.z & v.w & 1) == 0) && ++c < SPIN_LIM);
    const int d = max(max((int)(v.x - t), (int)(v.y - t)), max((int)(v.z - t), (int)(v.w - t))) + (s == 0 ? FIRST_NS : 0);
    if (ADAPT && s >= ADAPT) {
        const bool bad = __popc(__ballot_sync(0xffffffffu, (v.x | v.y | v.z | v.w) & 2)) >= 4;
        int e = state & 63, x = state >> 6;
        e = bad ? max(e, 16) + AD_UP : e - 1;
        if (e >= 32) { x = min(x + 32, 256); e = 16; }
        if (e <= 0) { x = max(x - 32, 0); e = 16; }
        state = x * 64 + e;
    }
    t = (t & ~3u) + (state >> 6);
    const unsigned tgt = t + min(__reduce_max_sync(0xffffffffu, d), 20000) + TGT_NS;
    if (L16 < 48) { const uint32_t r = mapa(sb, L16 >> 4); st_async32(r + S_TGT, tgt, r + B_T); }
}

__device__ __forceinline__ void load_wo(uint32_t sb, int w, uint32_t L16, uint32_t (&woA)[8][4], uint32_t (&woB)[4][4]) {
    mbar_wait(sb + B_WO, 0);
    if (w < 4) TSTAMP(73, 0);
    const int m = L16 >> 7, r = (L16 >> 4) & 7;
    const int ca = 3 * w + (m & 1), cb = 3 * w + 2;
    const uint32_t aA = sb + S_WO + (ca >> 3) * 16384 + ((m >> 1) * 8 + r) * 128 + (((ca & 7) ^ r) << 4);
    const int eB = ((m & 2) + ((r >> 1) & 1)) * 8 + 4 * (m & 1) + 2 * (r >> 2) + (r & 1);
    const uint32_t aB = sb + S_WO + (cb >> 3) * 16384 + eB * 128 + (((cb & 7) ^ (eB & 7)) << 4);
#pragma unroll
    for (int i = 0; i < 8; i++) ldsm4t(woA[i], aA + i * 2048);
#pragma unroll
    for (int i = 0; i < 4; i++) ldsm4t(woB[i], aB + i * 4096);
}

template <int ROLE>
__device__ __forceinline__ void chain_main(const uint32_t sb, const uint32_t lane16, const int wq, const uint32_t j, const uint32_t h,
                                           const uint32_t peerA, const uint32_t peerB, char* const acc) {
    uint32_t L16 = lane16;
    constexpr bool isv = ROLE >= 2;
    constexpr int wg = ROLE & 1;
    const int w = wg * 4 + wq;
    const uint32_t xdesc = desc_lo(sb + S_XB);
    const uint32_t zero = h >> 20;
    uint32_t wA[36][4], woA[8][4], woB[4][4];
    float xd[16];
    {
        const int m = L16 >> 7, r = (L16 >> 4) & 7;
        const int blk = (ROLE == 1) ? ((wq & 2) * 2 + (wq & 1) + (m & 1) * 2) : (2 * wq + (m & 1));
        const uint32_t a = sb + wg * 24576 + ((m >> 1) * 8 + r) * 128 + ((blk ^ r) << 4);
        float x0[16];
#pragma unroll
        for (int c = 0; c < 3; c++) {
            mbar_wait(sb + B_W + 8 * c, 0);
            if (wg == 0) TSTAMP(70 + c, 0);
#pragma unroll
            for (int i = 0; i < 12; i++) ldsm4t(wA[12 * c + i], a + s_w(c) + i * 2048);
            if (c == WO_AFTER) bar_arrive<NB_PRO, 288>();
            if (c == 0) { mbar_wait(sb + B_X, 0); mbar_wait(sb + B_X + 8, 0); }
            if (c == 2) { bar_sync<NB_O, 256>(); cluster_arrive(); }
            wg_fence();
            if (c == 0) { x_project<0, 12>(x0, wA, xdesc); x_project<0, 12>(xd, wA, xdesc + (XB_BYTES >> 4)); wg_commit(); wg_wait<0>(); }
            if (c == 1) { x_project<12, 24>(x0, wA, xdesc); x_project<12, 24>(xd, wA, xdesc + (XB_BYTES >> 4)); wg_commit(); wg_wait<0>(); }
            if (c == 2) { x_project<24, 36>(x0, wA, xdesc); wg_commit(); wg_wait<0>(); }
        }
        uint32_t pk[8];
        x_pack(x0, pk);
        x_write(sb, pk, 0, isv, w, L16);
        bar_arrive<NB_AUX, 288>();
        wg_fence();
        x_project<24, 36>(xd, wA, xdesc + (XB_BYTES >> 4));
        wg_commit();
        cluster_wait();
        bar_sync<NB_O, 256>();
        if (wg == 0) TSTAMP(74, 0);
        if (WO_LOOP) {
#pragma unroll
            for (int i = 0; i < 8; i++) woA[i][0] = woA[i][1] = woA[i][2] = woA[i][3] = 0;
#pragma unroll
            for (int i = 0; i < 4; i++) woB[i][0] = woB[i][1] = woB[i][2] = woB[i][3] = 0;
        } else load_wo(sb, w, L16, woA, woB);
    }
    int s = 0;
#pragma unroll 1
    while (true) {
        const uint32_t par = s & 1;
        const uint32_t kx = sb + S_KX + par * 4096;
        asm volatile("" : "+r"(L16));
        uint32_t pk[8];
        if (wg == 0) { wg_wait<0>(); x_pack(xd, pk); x_write(sb, pk, s + 1, isv, w, L16); }
        float c0[4], c1[4];
        uint32_t k0[4], k1[4];
        bool vxready = false;
        {
            const uint32_t a = sb + S_MEM + L16;
            constexpr int CH = 18 / NCH;
            uint32_t b[3][4];
            bool ready = true;
            mbar_wait(sb + B_M, par);
            ldsm4(b[0], a);
            ldsm4(b[1], a + 512);
            if (wg == 1) { wg_wait<0>(); x_pack(xd, pk); }
            bar_arrive<NB_GO, 288>();
#pragma unroll
            for (int i = 0; i < 18; i++) {
                if ((i + 4) % CH == 0 && i + 4 < 18) ready = mbar_test(sb + B_M + ((i + 4) / CH) * 8, par);
                if ((i + 2) % CH == 0 && i + 2 < 18) { if (__builtin_expect(!ready, 0)) mbar_wait(sb + B_M + ((i + 2) / CH) * 8, par); }
                if (i + 2 < 18) ldsm4(b[(i + 2) % 3], a + (i + 2) * 512);
                if (ROLE == 0 && i == 16) ldsm4(k0, kx + wq * 1024 + L16);
                if (ROLE == 0 && i == 17) ldsm4(k1, kx + wq * 1024 + 512 + L16);
                if (ROLE == 2 && i == PR_AT) bar_arrive<NB_PR, 256>();
                if (i == 0) { mma16z(c0, wA[0], b[0][0], b[0][1]); mma16z(c1, wA[1], b[0][2], b[0][3]); }
                else { mma16(c0, wA[2 * i], b[i % 3][0], b[i % 3][1]); mma16(c1, wA[2 * i + 1], b[i % 3][2], b[i % 3][3]); }
            }
        }
        const uint32_t p0 = pack_bf16(c0[0] + c1[0], c0[1] + c1[1]), p1 = pack_bf16(c0[2] + c1[2], c0[3] + c1[3]);
        if (!isv) {
            stsm2t(sb + S_QM + w * 256 + L16, p0, p1);
            bar_sync<NB_QK, 384>();
            if (ROLE == 0) {
                uint32_t q0[4], q1[4];
                ldsm4(q0, sb + S_QM + L16);
                ldsm4(q1, sb + S_QM + 512 + L16);
                if (VXTEST) vxready = mbar_test(sb + B_VX + par * 8, (s >> 1) & 1);
                mem_scores(sb, peerA, peerB, S_SP + j * 128 + wq * 256 + (L16 >> 2), q0, q1, k0, k1);
                mbar_arrive_if0(sb + B_S, L16);
            } else {
                if (s + 2 < XLIM) mbar_wait(sb + B_X + par * 8, ((s + 2) >> 1) & 1);
                x_write(sb, pk, s + 1, isv, w, L16);
                if (wq != 0) {
                    const int rt = (wq == 3) ? 0 : 1;
                    const uint32_t qa = sb + S_QX + par * 4096 + rt * 2048 + (L16 & 0x80) * 8 + (L16 & 0x170);
                    const uint32_t kb0 = (wq == 2 ? kx + 2048 : sb + S_KM) + L16;
                    const uint32_t kb1 = (wq == 2 ? kx + 3072 : kx) + L16;
                    const uint32_t kb2 = kx + 1024 + L16;
                    float a0[4], a1[4], a2[4];
#pragma unroll
                    for (int hf = 0; hf < 2; hf++) {
                        uint32_t qa0[4], qa1[4], b[4];
                        ldsm4(qa0, qa + hf * 512);
                        ldsm4(qa1, qa + hf * 512 + 128);
                        ldsm4(b, kb0 + hf * 512);
                        if (hf == 0) mma16z(a0, qa0, b[0], b[1]); else mma16(a0, qa0, b[0], b[1]);
                        mma16(a0, qa1, b[2], b[3]);
                        ldsm4(b, kb1 + hf * 512);
                        if (hf == 0) mma16z(a1, qa0, b[0], b[1]); else mma16(a1, qa0, b[0], b[1]);
                        mma16(a1, qa1, b[2], b[3]);
                        ldsm4(b, kb2 + hf * 512);
                        if (hf == 0) mma16z(a2, qa0, b[0], b[1]); else mma16(a2, qa0, b[0], b[1]);
                        mma16(a2, qa1, b[2], b[3]);
                    }
                    if (s < NSEG - 1) mbar_wait(sb + B_S, par);
                    const uint32_t dst = peerB + S_SX + par * 5120 + j * 128 + rt * 2560 + (L16 >> 2);
                    const uint32_t bar = peerB + B_SX + par * 8;
                    const uint32_t T0 = (wq == 2 ? 2 : 4) * 256, T1 = (wq == 2 ? 3 : 0) * 256;
                    st_async32(dst + T0, pack_f16_sat(a0[0], a0[1]), bar);
                    st_async32(dst + 1280 + T0, pack_f16_sat(a0[2], a0[3]), bar);
                    if (wq != 2) st_async32(dst + T1, pack_f16_sat(a1[0], a1[1]), bar);
                    st_async32(dst + 1280 + T1, pack_f16_sat(a1[2], a1[3]), bar);
                    if (wq == 1) st_async32(dst + 256, pack_f16_sat(a2[0], a2[1]), bar);
                    if (wq != 2) st_async32(dst + 1280 + 256, pack_f16_sat(a2[2], a2[3]), bar);
                }
            }
        } else {
            const uint32_t off = S_VM + (s & 3) * 2048 + w * 256 + (L16 >> 1);
            st_async64(peerA + off, p0, p1, peerA + B_S);
            st_async64(peerB + off, p0, p1, peerB + B_S);
            sts64(sb + off, p0, p1);
            __syncwarp();
            mbar_expect_if0(sb + B_S, 160, L16);
            if (ROLE == 2) bar_arrive<NB_P, 384>();
            else {
                if (s == NSEG - 1) break;
                x_write(sb, pk, s + 1, isv, w, L16);
                if (PR_AT < 18) bar_arrive<NB_VW, 160>();
                x_pv_both<NB_P, 384>(sb, s + 2, wq, L16);
                bar_arrive<NB_PV, 160>();
                if (s + 2 < XLIM) mbar_wait(sb + B_X + par * 8, ((s + 2) >> 1) & 1);
            }
        }
        if (WO_LOOP == 0 && s == NSEG - 1) break;
        if (WO_LOOP && ((s + 1) & (NSEG - 1)) <= 1) {
            if (s) break;
            load_wo(sb, w, L16, woA, woB);
        }
        if (wg == 0) {
            if (!isv && !vxready) mbar_wait(sb + B_VX + par * 8, (s >> 1) & 1);
            uint32_t va[4][4];
            const uint32_t vx = sb + S_VX + (s & 3) * 8192 + wq * 2048 + L16;
            const uint32_t vm = sb + S_VM + (s & 3) * 2048 + wq * 512 + (L16 >> 1);
            lds128(va[0], vx);
            lds128(va[2], vx + 1024);
            mbar_wait(sb + B_S, par);
            __half2 hs[5];
            load_scores(sb + S_SP + L16, hs);
            float ev[10];
            softmax_exp(hs, ev);
            lds128(va[1], vx + 512);
            lds128(va[3], vx + 1536);
            uint32_t p[5];
#pragma unroll
            for (int i = 0; i < 5; i++) p[i] = pack_bf16(ev[2 * i], ev[2 * i + 1]);
            uint32_t vm0[2], vm1[2];
            const uint32_t ones[4] = {ONES, ONES, ONES, ONES};
            float sum[4], o0[4], o1[4];
            mma16z(o0, va[0], p[0], p[1]);
            mma16z(o1, va[2], p[0], p[1]);
            mma16z(sum, ones, p[0], p[1]);
            lds64(vm0, vm);
            lds64(vm1, vm + 256);
            mma16(o0, va[1], p[2], p[3]);
            mma16(o1, va[3], p[2], p[3]);
            mma16(sum, ones, p[2], p[3]);
            if (PRCP) mma8(sum, ONES, ONES, p[4]);
            mma8(o0, vm0[0], vm0[1], p[4]);
            mma8(o1, vm1[0], vm1[1], p[4]);
            if (!PRCP) mma8(sum, ONES, ONES, p[4]);
            stsm4t(sb + S_OM + wq * 512 + L16, pack_bf16(o0[0], o0[1]), pack_bf16(o0[2], o0[3]), pack_bf16(o1[0], o1[1]), pack_bf16(o1[2], o1[3]));
            sts64(sb + S_SUM + wq * 256 + (L16 >> 1), __float_as_uint(PRCP ? rcp(sum[0]) : sum[0]), __float_as_uint(PRCP ? rcp(sum[1]) : sum[1]));
        }
        bar_sync<NB_O, 256>();
        {
            float a0[4], a1[4], e[4];
            float2 sc;
            float sr, r0, r1, rr;
#pragma unroll
            for (int i = 0; i < 4; i++) {
                uint32_t b[4];
                ldsm4(b, sb + S_OM + i * 512 + L16);
                if (i == 0) {
                    mma16z(a0, woA[0], b[0], b[1]); mma16z(a1, woA[1], b[2], b[3]);
                    mma_sp<0>(e, b, woB[0]);
                } else {
                    if (i == 1) { sc = lds64f(sb + S_SUM + (L16 >> 1)); sr = lds32f(sb + S_SUM + ((L16 >> 4) & 0x1C)); }
                    const uint32_t z = __float_as_uint(a0[0]) & zero;
                    mma16(a0, woA[2 * i], b[0], b[1]); mma16(a1, woA[2 * i + 1], b[2], b[3]);
                    mma_sp<1>(e, b, woB[i]);
                    if (PRCP) { r0 = sc.x; r1 = sc.y; rr = sr; }
                    else if (i == RCP_AT) {
                        r0 = rcp(__uint_as_float(__float_as_uint(sc.x) | z));
                        r1 = rcp(__uint_as_float(__float_as_uint(sc.y) | z));
                        rr = rcp(__uint_as_float(__float_as_uint(sr) | z));
                    }
                }
            }
            if (XEARLY && wg == 1) bar_arrive<NB_X, 256>();
            asm volatile("" : "+r"(L16));
            char* const rslot = acc + (slot_off(s + 1) + j * 64 + w * 4096) + lane_off(L16);
            asm volatile("red.relaxed.gpu.global.add.noftz.v4.bf16x2 [%0], {%1,%2,%3,%4};"
                         ::"l"(rslot), "r"(pack_bf16((a0[0] + a1[0]) * r0, (a0[1] + a1[1]) * r1)), "r"(pack_bf16((a0[2] + a1[2]) * r0, (a0[3] + a1[3]) * r1)),
                           "r"(pack_bf16((e[0] + e[2]) * rr, (e[1] + e[3]) * rr)), "r"(0x3F80u) : "memory");
        }
        bar_arrive<NB_RED, 384>();
        if (wg == 0) {
            bar_sync<NB_X, 256>();
            wg_fence();
            x_project<0, HAND_AT>(xd, wA, xdesc + par * (XB_BYTES >> 4));
            bar_arrive<NB_L, 256>();
            x_project<HAND_AT, 36>(xd, wA, xdesc + par * (XB_BYTES >> 4));
            wg_commit();
        } else {
            if (!XEARLY) bar_arrive<NB_X, 256>();
            if (s < NSEG - 2) {
                bar_sync<NB_L, 256>();
                wg_fence();
                x_project<0, 36>(xd, wA, xdesc + par * (XB_BYTES >> 4));
                wg_commit();
            } else {
                if (isv) {
                    x_pv_both<NB_T0, 256>(sb, NSEG - 3, wq, L16);
                    bar_sync<NB_AUX, 128>();
                    if (wq == 0 && L16 == 0) ox_store(sb, NSEG - 3, h);
                    __syncwarp();
                    x_pv_both<NB_T0 + 1, 256>(sb, NSEG - 2, wq, L16);
                    bar_sync<NB_AUX, 128>();
                    if (L16 == 0) {
                        if (wq == 0) ox_publish(NSEG - 3, h);
                        if (wq == 1) ox_store(sb, NSEG - 2, h);
                    }
                    __syncwarp();
                }
                wg_fence();
                x_project<0, 1>(xd, wA, xdesc);
                wg_commit();
            }
        }
        s++;
    }
    if (isv) {
        if (w == 5 && L16 == 0) ox_publish(NSEG - 2, h);
        __syncwarp();
        uint32_t pva[3][4], pk[8];
        x_pv_load(sb, NSEG - 1, w, L16, pva);
        bar_sync<NB_T0 + 2, 384>();
        x_pv_run(sb, NSEG - 1, pva, pk);
        x_pv_store(sb, NSEG - 1, w, L16, pk);
        bar_sync<NB_O, 256>();
        if (w == 0 && L16 == 0) { ox_store(sb, NSEG - 1, h); ox_publish(NSEG - 1, h); }
        __syncwarp();
    }
}

template <bool isv>
__device__ __forceinline__ void chain_aux(const uint32_t sb, const uint32_t lane16, const int wq, const uint32_t j, const uint32_t h,
                                          const uint32_t peerA, const uint32_t peerB, const CUtensorMap* tmWo, const CUtensorMap* tmX,
                                          char* const acc, const CUtensorMap* m0, const CUtensorMap* m1) {
    const int t = wq * 32 + (lane16 >> 4);
    cluster_arrive();
    {
        for (int c2 = 0; c2 < 3; c2++) mbar_arrive_if0(sb + B_M + c2 * 8, lane16);
        if (DEP_AT == 1) asm volatile("griddepcontrol.launch_dependents;" ::: "memory");
        if (wq == 0) {
            if (PACE) {
                mbar_wait(sb + B_W, 0);
                if (t == 0) {
                    mbar_expect(sb + B_W + 16, 49152);
                    tma2d_once(sb + s_w(2), m0, h * 128 + (isv ? 0 : 64 * j), 384, sb + B_W + 16);
                    tma2d_once(sb + s_w(2) + 24576, m1, h * 128 + (isv ? 64 : 64 * j), 384, sb + B_W + 16);
                }
                __syncwarp();
            }
            if (DEP_AT == 2) asm volatile("griddepcontrol.launch_dependents;" ::: "memory");
            bar_sync<NB_PRO, 288>();
            if (WO_DELAY) {
                const unsigned t0 = clk();
                while (!mbar_test(sb + B_W + 16, 0) && clk() - t0 < WO_DELAY) {}
            }
            if (t == 0) {
                fence_async_smem();
                mbar_expect(sb + B_WO, 49152);
                for (int b = 0; b < 3; b++) tma2d(sb + S_WO + b * 16384, tmWo, 192 * j + 64 * b, h * 128, sb + B_WO);
            }
        } else if (wq == 3) {
            bulk_wait0();
            asm volatile("fence.proxy.async.global;" ::: "memory");
            __syncwarp();
            if (lane16 == 0) {
                if (h == 0) asm volatile("red.relaxed.gpu.global.add.u32 [%0], 1;" ::"l"(&g_zero_cnt) : "memory");
            }
            __syncwarp();
            unsigned c = 0;
            while (ld_acquire(&g_zero_cnt) < 3 && ++c < SPIN_LIM) __nanosleep(100);
            TSTAMP(76, 0);
        }
        __syncwarp();
        cluster_wait();
        if (wq == 0) bar_sync<NB_AUX, 288>();
        if (t == 0) {
            fence_async_smem();
            if (!isv) mbar_expect(sb + B_VX, 8192);
            else {
                bulk_s2c(peerA + S_VX, sb + S_VX, 8192, peerA + B_VX);
                bulk_s2c(peerB + S_VX, sb + S_VX, 8192, peerB + B_VX);
            }
            mbar_expect(sb + B_X, XB_BYTES);
            tma3d(sb + S_XB, tmX, 0, 64, 0, sb + B_X);
        }
        __syncwarp();
    }
    TSTAMP(0, 0);
    uint32_t L16 = lane16;
    const char* slot = acc + wq * 4096 + lane_off(L16);
    float ev[10];
    unsigned early = 0;
    int state = 16;
    int s = 0;
#pragma unroll 1
    while (true) {
        const uint32_t par = s & 1;
        asm volatile("" : "+r"(L16));
        if (!isv) {
            if (wq == 0) {
                bar_sync<NB_QK, 384>();
                uint32_t q0[4], q1[4], k0[4], k1[4];
                ldsm4(q0, sb + S_QM + L16);
                ldsm4(k0, sb + S_KM + L16);
                ldsm4(q1, sb + S_QM + 512 + L16);
                ldsm4(k1, sb + S_KM + 512 + L16);
                mem_scores(sb, peerA, peerB, S_SP + j * 128 + 1024 + (L16 >> 2), q0, q1, k0, k1);
                mbar_expect_if0(sb + B_S, 640 + 2048, L16);
            } else if (wq == 3) {
                bar_sync<NB_GO, 288>();
                const unsigned t = post_time(s, L16, early);
                bar_sync<NB_QK, 384>();
                if (j == 0 && s < NSEG - 1) {
                    if (LOOK_NS) __nanosleep(LOOK_NS);
                    plan_look(sb, s, L16, t, state);
                }
            } else {
                bar_arrive<NB_QK, 384>();
                if (wq == 2) {
                    if (L16 == 0) {
                        if (s + 3 < XLIM) mbar_expect(sb + B_X + (par ^ 1) * 8, XB_BYTES);
                        mbar_expect(sb + B_VX + (par ^ 1) * 8, 8192);
                        mbar_expect(sb + B_T, 4);
                        if (s == 2 && h == 0 && j == 0) g_zero_cnt = 0;
                        if (REFRESH && s + REFRESH == 2 * h) asm volatile("cp.async.bulk.prefetch.L2.global [%0], %1;" ::"l"(acc + h * 32768 + j * 16384), "r"(16384) : "memory");
                    }
                } else if (s + 3 < XLIM && j == 1) {
                    mbar_wait(sb + B_S, par);
                    if (XTMA_NS) __nanosleep(XTMA_NS);
                    if (L16 == 0) tma3d_mc(sb + S_XB + (par ^ 1) * XB_BYTES, tmX, 0, (s + 3) * SEG, 0, sb + B_X + (par ^ 1) * 8, 7);
                }
                __syncwarp();
            }
        } else {
            if (wq == 3) {
                bar_sync<NB_GO, 288>();
                post_time(s, L16, early);
            } else if (L16 == 0) {
                if (wq == 0) {
                    if (s >= 1) vx_fetch(sb, s, h);
                } else if (wq == 1) {
                    if (!PUB_EARLY && s >= 3 && s < NSEG - 1) ox_publish(s - 3, h);
                } else {
                    mbar_expect(sb + B_SX + par * 8, 3584);
                    mbar_expect(sb + B_T, 4);
                    if (s + 3 < XLIM) mbar_expect(sb + B_X + (par ^ 1) * 8, XB_BYTES);
                }
            }
            __syncwarp();
            if (s == NSEG - 1) break;
            if (s >= 1) mbar_wait(sb + B_SX + (par ^ 1) * 8, ((s - 1) >> 1) & 1);
            fence_async_smem();
            if (PR_AT < 18) {
                bar_arrive<NB_P, 384>();
                bar_sync<NB_PR, 256>();
                x_scores(sb, s + 1, wq, L16, ev);
                x_probs(sb, s + 1, wq, L16, ev);
                if (wq == 0) { bar_sync<NB_VW, 160>(); if (L16 == 0) vx_store(sb, s + 1, h); __syncwarp(); }
                if (wq == 1) {
                    bar_sync<NB_PV, 160>();
                    if (L16 == 0 && s >= 2) ox_store(sb, s - 2, h);
                    __syncwarp();
                }
            } else {
            bar_sync<NB_P, 384>();
            if (wq == 0) { if (L16 == 0) vx_store(sb, s + 1, h); __syncwarp(); }
            x_scores(sb, s + 1, wq, L16, ev);
            if (wq == 1) {
                bar_sync<NB_PV, 160>();
                if (L16 == 0 && s >= 2) ox_store(sb, s - 2, h);
                __syncwarp();
            }
            x_probs(sb, s + 1, wq, L16, ev);
            }
        }
        if (s == NSEG - 1) break;
        mbar_wait(sb + B_T, par);
        const unsigned tgt = __float_as_uint(lds32f(sb + S_TGT));
        if (isv && s == NSEG - 2) { fence_async_smem(); bar_arrive<NB_T0, 256>(); }
        bar_sync<NB_RED, 384>();
        if (isv) {
            if (wq == 1 && (PUB_EARLY || s == NSEG - 2)) {
                if (PUB_EARLY > 1) while ((int)(gtime() - tgt) < -PUB_EARLY) {}
                if (L16 == 0 && s >= 2) ox_publish(s - 2, h);
                __syncwarp();
            }
            if (s == NSEG - 2) {
                mbar_wait(sb + B_SX, (s >> 1) & 1);
                x_scores(sb, s, wq, L16, ev);
                x_probs(sb, s, wq, L16, ev);
                fence_async_smem();
                bar_arrive<NB_T0 + 1, 256>();
            }
        }
        asm volatile("" : "+r"(L16));
        slot += par ? 32768 - 512 : 512;
        while ((int)(gtime() - tgt) < 0) {}
        uint4 v[6];
        look(v, slot);
        s++;
        const uint32_t ma = sb + S_MEM + wq * 384 + L16;
        unsigned c = 0;
        constexpr int CW = 6 / NCH;
        int done = NCH;
#pragma unroll
        for (int k = 0; k < NCH; k++) {
            uint32_t bad = 0;
#pragma unroll
            for (int i = CW * k; i < CW * k + CW; i++) { stsm2t(ma + i * 1536, v[i].x, v[i].y); stsm1(ma + i * 1536 + 256, v[i].z); bad |= v[i].w ^ FULL_COUNT; }
            const bool again = __any_sync(0xffffffffu, bad != 0);
            mbar_arrive_if0(sb + B_M + k * 8, L16 | (uint32_t)again);
            if (again) { done = k; break; }
        }
        if (done < NCH) {
            uint32_t bad;
            do {
                look(v, slot);
                bad = 0;
#pragma unroll
                for (int i = 0; i < 6; i++) { stsm2t(ma + i * 1536, v[i].x, v[i].y); stsm1(ma + i * 1536 + 256, v[i].z); bad |= v[i].w ^ FULL_COUNT; }
            } while (++c < SPIN_LIM && __any_sync(0xffffffffu, bad != 0));
            __syncwarp();
#pragma unroll
            for (int k = 0; k < NCH; k++) if (k >= done) mbar_arrive_if0(sb + B_M + k * 8, L16);
        }
        early = c;
        TSTAMP(s, c | t_pack);
    }
    if (!isv) {
        mbar_wait(sb + B_VX + 8, ((NSEG - 1) >> 1) & 1);
        mbar_wait(sb + B_S, 1);
    } else {
        mbar_wait(sb + B_SX + 8, ((NSEG - 1) >> 1) & 1);
        x_scores(sb, NSEG - 1, wq, L16, ev);
        x_probs(sb, NSEG - 1, wq, L16, ev);
        fence_async_smem();
        bar_arrive<NB_T0 + 2, 384>();
        mbar_wait(sb + B_S, 1);
    }
}

__global__ void __launch_bounds__(384, 1)
chain_kernel(const __grid_constant__ CUtensorMap tmWq, const __grid_constant__ CUtensorMap tmWk, const __grid_constant__ CUtensorMap tmWv,
             const __grid_constant__ CUtensorMap tmWo, const __grid_constant__ CUtensorMap tmX, const bf16* __restrict__ mem0, char* const acc) {
    extern __shared__ __align__(1024) uint8_t smem[];
    const uint32_t sb = smem_u32(smem);
    const int tid = threadIdx.x;
    const uint32_t L16 = __shfl_sync(0xffffffffu, (tid & 31) * 16, tid & 31);
    const int w = __shfl_sync(0xffffffffu, tid >> 5, 0), wg = w >> 2, wq = w & 3;
    uint32_t j, h;
    asm("mov.u32 %0, %%cluster_ctarank;" : "=r"(j));
    asm("mov.u32 %0, %%clusterid.x;" : "=r"(h));
    const bool isv = (j == 2);
    const uint32_t peerA = mapa(sb, isv ? 0 : (j ^ 1)), peerB = mapa(sb, isv ? 1 : 2);
    if (DEP_AT == 0) asm volatile("griddepcontrol.launch_dependents;" ::: "memory");
    if (DESCPF && w == 10 && L16 < 64) {
        const CUtensorMap* m = L16 == 0 ? &tmX : L16 == 16 ? (isv ? &tmWv : &tmWq) : L16 == 32 ? &tmWk : &tmWo;
        asm volatile("prefetch.tensormap [%0];" ::"l"(m) : "memory");
    }
    if (w == 11) {
        sts128(sb + S_ZERO + L16, 0, 0, 0, 0);
        sts128(sb + S_ZERO + 512 + L16, 0, 0, 0, 0);
        fence_async_smem();
        __syncwarp();
        const int i = L16 >> 4, kb = j * 11 + i;
        if (i < 11 && kb < 32) bulk_s2g(acc + h * 32768 + kb * 1024, sb + S_ZERO, 1024);
        if (i == 11) bulk_s2g(g_time + blockIdx.x * 64, sb + S_ZERO, 256);
        bulk_commit();
    }
    if (tid == 256) {
        for (int c = 0; c < 3; c++) { mbar_init(sb + B_W + 8 * c, 1); mbar_init(sb + B_M + 8 * c, 4); }
        mbar_init(sb + B_WO, 1); mbar_init(sb + B_T, 1);
        mbar_init(sb + B_X, 1); mbar_init(sb + B_X + 8, 1);
        mbar_init(sb + B_S, isv ? 8 : 5);
        mbar_init(sb + B_VX, 1); mbar_init(sb + B_VX + 8, 1);
        mbar_init(sb + B_SX, 1); mbar_init(sb + B_SX + 8, 1);
        asm volatile("fence.mbarrier_init.release.cluster;" ::: "memory");
        const CUtensorMap* m0 = isv ? &tmWv : &tmWq;
        const CUtensorMap* m1 = isv ? &tmWv : &tmWk;
        const int c0 = h * 128 + (isv ? 0 : 64 * j), c1 = h * 128 + (isv ? 64 : 64 * j);
        mbar_expect(sb + B_X, XB_BYTES);
        tma3d(sb + S_XB, &tmX, 0, 0, 0, sb + B_X);
        mbar_expect(sb + B_X + 8, XB_BYTES);
        tma3d(sb + S_XB + XB_BYTES, &tmX, 0, 32, 0, sb + B_X + 8);
#pragma unroll 1
        for (int c = 0; c < (PACE ? 2 : 3); c++) {
            mbar_expect(sb + B_W + 8 * c, 49152);
            tma2d_once(sb + s_w(c), m0, c0, c * 192, sb + B_W + 8 * c);
            tma2d_once(sb + s_w(c) + 24576, m1, c1, c * 192, sb + B_W + 8 * c);
        }
    } else if (tid < 256) {
        uint4 v0, v1, v2;
        v0 = *reinterpret_cast<const uint4*>(mem0 + (tid & 7) * DM + (tid >> 3) * 8);
        v1 = *reinterpret_cast<const uint4*>(mem0 + (tid & 7) * DM + (tid >> 3) * 8 + 256);
        if (tid < 64) v2 = *reinterpret_cast<const uint4*>(mem0 + (tid & 7) * DM + (tid >> 3) * 8 + 512);
        sts128(sb + S_MEM + tid * 16, v0.x, v0.y, v0.z, v0.w);
        sts128(sb + S_MEM + 4096 + tid * 16, v1.x, v1.y, v1.z, v1.w);
        if (tid < 64) sts128(sb + S_MEM + 8192 + tid * 16, v2.x, v2.y, v2.z, v2.w);
    }
    __syncthreads();
    if (wg == 2) {
        asm volatile("setmaxnreg.dec.sync.aligned.u32 %0;" ::"n"(REG_AUX));
        if (!isv) chain_aux<false>(sb, L16, wq, j, h, peerA, peerB, &tmWo, &tmX, acc, &tmWq, &tmWk);
        else chain_aux<true>(sb, L16, wq, j, h, peerA, peerB, &tmWo, &tmX, acc, &tmWv, &tmWv);
        __syncwarp();
        cluster_arrive(); cluster_wait();
        TSTAMP(65, 0);
    } else if (wg == 0) {
        asm volatile("setmaxnreg.inc.sync.aligned.u32 %0;" ::"n"(REG_MAIN0));
        if (!isv) chain_main<0>(sb, L16, wq, j, h, peerA, peerB, acc);
        else chain_main<2>(sb, L16, wq, j, h, peerA, peerB, acc);
        cluster_arrive(); cluster_wait();
    } else {
        asm volatile("setmaxnreg.inc.sync.aligned.u32 %0;" ::"n"(REG_MAIN1));
        if (!isv) chain_main<1>(sb, L16, wq, j, h, peerA, peerB, acc);
        else chain_main<3>(sb, L16, wq, j, h, peerA, peerB, acc);
        cluster_arrive(); cluster_wait();
    }
}

constexpr int NHELP = 36;
constexpr uint32_t H_U = 0;
constexpr uint32_t UT_PITCH = 4368;
constexpr uint32_t H_UT = 65536;
constexpr uint32_t KW_BYTES = 8320;
constexpr uint32_t H_KW = 135424;
constexpr uint32_t H_PAR = 201984;
constexpr uint32_t H_KD = 214272;
constexpr uint32_t H_IDX = 224640;
constexpr uint32_t H_STAGE = 0;
constexpr uint32_t H_RED = 196608;
constexpr uint32_t H_FIN = 212992;
constexpr uint32_t H_OWN = 214016;
constexpr uint32_t H_BAR = 229376;
constexpr uint32_t B_SMEM = H_BAR + 384;
constexpr uint32_t HB_U = H_BAR, HB_WO = H_BAR + 8, HB_EMPTY = H_BAR + 16, HB_FIN = H_BAR + 96, HB_FULL = H_BAR + 128, HB_SENT = H_BAR + 320;
constexpr int RING = 8;
__device__ __align__(1024) uint4 g_part[RING * 9 * 4 * 4 * 128];

__device__ __forceinline__ float2 cmul(float2 a, float2 b) { return make_float2(fmaf(a.x, b.x, -a.y * b.y), fmaf(a.x, b.y, a.y * b.x)); }
__device__ __forceinline__ float2 csqr(float2 a) { return make_float2(fmaf(a.x, a.x, -a.y * a.y), (a.x + a.x) * a.y); }
__device__ __forceinline__ float2 cexp(float zr, float zi, float p) {
    const float m = ex2(zr * p);
    const float r = zi * p;
    const float a = (fabsf(r) < 4194304.f ? r - ((r + 12582912.f) - 12582912.f) : 0.f) * 6.283185307179586f;
    return make_float2(m * __cosf(a), m * __sinf(a));
}
__device__ __forceinline__ uint32_t pack_f16(float lo, float hi) { uint32_t r; asm("cvt.rn.f16x2.f32 %0, %1, %2;" : "=r"(r) : "f"(hi), "f"(lo)); return r; }
__device__ __forceinline__ void mma16h(float* d, const uint32_t* a, uint32_t b0, uint32_t b1) {
    asm volatile("mma.sync.aligned.m16n8k16.row.col.f32.f16.f16.f32 {%0,%1,%2,%3},{%4,%5,%6,%7},{%8,%9},{%0,%1,%2,%3};"
                 : "+f"(d[0]), "+f"(d[1]), "+f"(d[2]), "+f"(d[3]) : "r"(a[0]), "r"(a[1]), "r"(a[2]), "r"(a[3]), "r"(b0), "r"(b1));
}
__device__ __forceinline__ float bf_round(float x) { return __bfloat162float(__float2bfloat16_rn(x)); }
__device__ __forceinline__ uint32_t lds32(uint32_t a) { uint32_t v; asm volatile("ld.shared.b32 %0,[%1];" : "=r"(v) : "r"(a) : "memory"); return v; }
__device__ __forceinline__ uint32_t lds16(uint32_t a) { uint16_t v; asm volatile("ld.shared.u16 %0,[%1];" : "=h"(v) : "r"(a) : "memory"); return v; }

__device__ __forceinline__ void s4d_kernel(uint32_t par, uint32_t kd, int d, int lane, const bf16* __restrict__ logA, const bf16* __restrict__ Aim,
                                           const bf16* __restrict__ Cre, const bf16* __restrict__ Cim, const bf16* __restrict__ logdt) {
    const float dt = bf_round(expf(__bfloat162float(logdt[d])));
    float4 q[4];
    float cmax = 0.f, last = 0.f;
#pragma unroll
    for (int i = 0; i < 4; i++) {
        const int n = d * NST + i * 32 + lane;
        q[i].x = -bf_round(expf(__bfloat162float(logA[n]))) * dt * 1.4426950408889634f;
        q[i].y = __bfloat162float(Aim[n]) * dt * 0.15915494309189535f;
        q[i].z = 2.f * (__bfloat162float(Cre[n]) * dt);
        q[i].w = 2.f * (__bfloat162float(Cim[n]) * dt);
        cmax = fmaxf(cmax, fmaxf(fabsf(q[i].z), fabsf(q[i].w)));
        const float2 e = cexp(q[i].x, q[i].y, 2048.f);
        last += q[i].z * e.x - q[i].w * e.y;
        const float2 w64 = cexp(q[i].x, q[i].y, 64.f);
        sts64(par + 2048 + (i * 32 + lane) * 8, __float_as_uint(w64.x), __float_as_uint(w64.y));
    }
#pragma unroll
    for (int o = 16; o; o >>= 1) { cmax = fmaxf(cmax, __shfl_xor_sync(0xffffffffu, cmax, o)); last += __shfl_xor_sync(0xffffffffu, last, o); }
    const float cs = __uint_as_float(max(__float_as_uint(cmax) & 0x7F800000u, 0x00800000u));
    const float ci = 1.f / cs;
#pragma unroll
    for (int i = 0; i < 4; i++) sts128(par + (i * 32 + lane) * 16, __float_as_uint(q[i].x), __float_as_uint(q[i].y), __float_as_uint(q[i].z * ci), __float_as_uint(q[i].w * ci));
    __syncwarp();
    float acc[5][4];
#pragma unroll
    for (int i = 0; i < 5; i++) acc[i][0] = acc[i][1] = acc[i][2] = acc[i][3] = 0.f;
    const float g = (float)(lane >> 2);
#pragma unroll 2
    for (int ks = 0; ks < 16; ks++) {
        uint32_t A[5][4], B[4][2];
#pragma unroll
        for (int hf = 0; hf < 2; hf++) {
            uint32_t r[4];
            const int n = ks * 8 + hf * 4 + (lane & 3);
            lds128(r, par + n * 16);
            const float2 w64 = lds64f(par + 2048 + n * 8);
            const float2 c = make_float2(__uint_as_float(r[2]), __uint_as_float(r[3]));
            float2 y = cexp(__uint_as_float(r[0]), __uint_as_float(r[1]), g);
#pragma unroll
            for (int k = 0; k < 4; k++) {
                const float2 cy = cmul(c, y);
                B[k][hf] = pack_f16(cy.x, -cy.y);
                if (k < 3) y = csqr(y);
            }
            const float2 xl = cmul(y, w64);
            float2 x0 = cmul(xl, w64), x1 = cmul(x0, w64);
            A[0][2 * hf] = pack_f16(y.x, y.y);
            A[0][2 * hf + 1] = pack_f16(xl.x, xl.y);
#pragma unroll
            for (int k = 0; k < 4; k++) {
                A[k + 1][2 * hf] = pack_f16(x0.x, x0.y);
                A[k + 1][2 * hf + 1] = pack_f16(x1.x, x1.y);
                if (k < 3) { x0 = csqr(x0); x1 = csqr(x1); }
            }
        }
        mma16h(acc[0], A[0], B[0][0], B[0][1]);
#pragma unroll
        for (int k = 0; k < 4; k++) mma16h(acc[k + 1], A[k + 1], B[k][0], B[k][1]);
    }
    __syncwarp();
#pragma unroll
    for (int i = 0; i < 5; i++) {
        sts32(kd + i * 256 + lane * 4, pack_bf16(acc[i][0] * cs, acc[i][1] * cs));
        sts32(kd + i * 256 + 128 + lane * 4, pack_bf16(acc[i][2] * cs, acc[i][3] * cs));
    }
    if (lane == 0) sts32(kd + 1280, pack_bf16(last, 0.f));
    __syncwarp();
}
__device__ __forceinline__ void s4d_expand(uint32_t kw, uint32_t kd, uint32_t idx, int lane) {
    if (lane < 16) sts32(kw + lane * 4, 0);
#pragma unroll 4
    for (int it = 0; it < 16; it++) {
        const int l = (it * 32 + lane) * 4;
        uint32_t j[2];
        lds64(j, idx + l * 2);
        const uint32_t jm = l ? lds16(idx + l * 2 - 2) : 1282;
        const uint32_t vm = lds16(kd + jm), v0 = lds16(kd + (j[0] & 0xFFFF)), v1 = lds16(kd + (j[0] >> 16)), v2 = lds16(kd + (j[1] & 0xFFFF)), v3 = lds16(kd + (j[1] >> 16));
        sts128(kw + 64 + l * 4, v0 | (vm << 16), v1 | (v0 << 16), v2 | (v1 << 16), v3 | (v2 << 16));
    }
    __syncwarp();
}

template <bool CLEAR>
__device__ __forceinline__ void s4d_conv(uint32_t ut, uint32_t kw, int lane, uint4* clr) {
    float acc[16][4];
#pragma unroll
    for (int i = 0; i < 16; i++) acc[i][0] = acc[i][1] = acc[i][2] = acc[i][3] = 0.f;
    const uint32_t ka = kw + 64 + ((lane >> 2) - 2 * (lane & 3)) * 4;
    const uint32_t ua = ut + 256 + lane * 8;
#pragma unroll 1
    for (int rho = 0; rho < 8; rho++) {
        if (CLEAR) { clr[rho * (9 * 16 * 128)] = make_uint4(0, 0, 0, 0); clr[rho * (9 * 16 * 128) + 512] = make_uint4(0, 0, 0, 0); }
        uint32_t B[16][2];
#pragma unroll
        for (int q = 0; q < 16; q++) lds64(B[q], ua + q * 256 - rho * 32);
#pragma unroll
        for (int m = 0; m < 16; m++) {
            uint32_t A[4];
            const uint32_t x = ka + m * 512 + rho * 64;
            A[0] = lds32(x); A[1] = lds32(x + 32); A[2] = lds32(x - 32); A[3] = A[0];
#pragma unroll
            for (int i = m; i < 16; i++) mma16(acc[i], A, B[i - m][0], B[i - m][1]);
        }
    }
    __syncwarp();
    const uint32_t ya = ut + 256 + (lane & 7) * 32 + ((lane >> 3) & 1) * 16 + (lane >> 4) * 256;
#pragma unroll
    for (int i = 0; i < 16; i += 2)
        stsm4t(ya + i * 256, pack_bf16(acc[i][0], acc[i][1]), pack_bf16(acc[i][2], acc[i][3]),
               pack_bf16(acc[i + 1][0], acc[i + 1][1]), pack_bf16(acc[i + 1][2], acc[i + 1][3]));
}

__global__ void __launch_bounds__(384, 1)
helper_kernel(const __grid_constant__ CUtensorMap tmU, const __grid_constant__ CUtensorMap tmY, const __grid_constant__ CUtensorMap tmWo,
              const bf16* __restrict__ logA, const bf16* __restrict__ Aim, const bf16* __restrict__ Cre, const bf16* __restrict__ Cim,
              const bf16* __restrict__ logdt, const bf16* __restrict__ Dskip, bf16* __restrict__ out) {
    extern __shared__ __align__(1024) uint8_t smem[];
    const uint32_t sb = smem_u32(smem);
    const int tid = threadIdx.x, lane = tid & 31;
    const int w = __shfl_sync(0xffffffffu, tid >> 5, 0);
    const int d0 = blockIdx.x * 16;
    HSTAMP(0);
    if (tid == 0) {
        mbar_init(sb + HB_U, 1); mbar_init(sb + HB_WO, 1);
        for (int i = 0; i < 3; i++) mbar_init(sb + HB_EMPTY + 8 * i, 8);
        for (int i = 0; i < 24; i++) mbar_init(sb + HB_FULL + 8 * i, 1);
        for (int i = 0; i < 4; i++) { mbar_init(sb + HB_FIN + 8 * i, 2); mbar_init(sb + HB_SENT + 8 * i, 8); }
        fence_async_smem();
    }
    __syncthreads();
    if (tid == 352) {
        const unsigned t0 = gtime();
        while (gtime() - t0 < U0_NS) __nanosleep(200);
        mbar_expect(sb + HB_U, 65536);
        for (int i = 0; i < 8; i++) { if (EVF & 2) tma2d_once(sb + H_U + i * 8192, &tmU, d0, i * 256, sb + HB_U); else tma2d(sb + H_U + i * 8192, &tmU, d0, i * 256, sb + HB_U); if (U_NS) __nanosleep(U_NS); }
    }
    __syncwarp();
    const int m = lane >> 3, r = lane & 7;
    const uint32_t kw = sb + H_KW + w * KW_BYTES;
    if (w < 8) {
        s4d_kernel(kw, sb + H_KD + w * 1296, d0 + w, lane, logA, Aim, Cre, Cim, logdt);
        bar_sync<1, 384>();
        HSTAMP(1);
        {
            uint4* dst = g_part + ((blockIdx.x % 9) * 16 + (w >> 2) * 8 + blockIdx.x / 9) * 128 + (tid & 127);
            s4d_expand(kw, sb + H_KD + w * 1296, sb + H_IDX, lane);
            bar_arrive<2, 384>();
            s4d_conv<true>(sb + H_UT + w * UT_PITCH, kw, lane, dst);
        }
        bar_sync<3, 384>();
        s4d_expand(kw, sb + H_KD + w * 1296, sb + H_IDX, lane);
        s4d_conv<false>(sb + H_UT + (8 + w) * UT_PITCH, kw, lane, nullptr);
    } else {
        for (int l = tid - 256; l < SEQ; l += 128) {
            const int jx = l < 128 ? l : (int)__bfloat16_as_ushort(__float2bfloat16_rn((float)l)) - (133 << 7);
            asm volatile("st.shared.u16 [%0], %1;" ::"r"(sb + H_IDX + l * 2), "h"((unsigned short)(jx * 2)) : "memory");
        }
        for (int i = tid - 256; i < 256; i += 128) sts128(sb + H_UT + (i >> 4) * UT_PITCH + (i & 15) * 16, 0, 0, 0, 0);
        mbar_wait(sb + HB_U, 0);
        const uint32_t src = sb + H_U + ((m & 1) * 8 + r) * 32 + (((m >> 1) ^ (r >> 2)) << 4);
        const uint32_t dst = sb + H_UT + 256 + (lane >> 2) * UT_PITCH + (lane & 3) * 8;
#pragma unroll 4
        for (int grp = w - 8; grp < 128; grp += 4) {
            uint32_t v[4];
            ldsm4t(v, src + grp * 512);
            sts64(dst + grp * 32, v[0], v[1]);
            sts64(dst + 8 * UT_PITCH + grp * 32, v[2], v[3]);
        }
        bar_arrive<1, 384>();
        bar_sync<2, 384>();
#pragma unroll 1
        for (int c = w - 8; c < 8; c += 4) s4d_kernel(sb + H_PAR + (w - 8) * 3072, sb + H_KD + c * 1296, d0 + 8 + c, lane, logA, Aim, Cre, Cim, logdt);
        bar_arrive<3, 384>();
    }
    __syncthreads();
    HSTAMP(2);
    const int cc = blockIdx.x % 9, kq = blockIdx.x / 9;
    {
        const __nv_bfloat162 D0 = *reinterpret_cast<const __nv_bfloat162*>(Dskip + d0 + (lane & 3) * 2);
        const __nv_bfloat162 D1 = *reinterpret_cast<const __nv_bfloat162*>(Dskip + d0 + 8 + (lane & 3) * 2);
        const uint32_t ua = sb + H_U + ((m & 1) * 8 + r) * 32 + (((m >> 1) ^ (r >> 2)) << 4);
        const uint32_t ya = sb + H_UT + 256 + ((m >> 1) * 8 + r) * UT_PITCH + (m & 1) * 16;
        for (int grp = w; grp < 128; grp += 12) {
            uint32_t u[4], y[4];
            ldsm4(u, ua + grp * 512);
            ldsm4t(y, ya + grp * 32);
#pragma unroll
            for (int i = 0; i < 4; i++) {
                const __nv_bfloat162 o = __hadd2_rn(*reinterpret_cast<__nv_bfloat162*>(&y[i]), __hmul2_rn(*reinterpret_cast<__nv_bfloat162*>(&u[i]), i < 2 ? D0 : D1));
                y[i] = *reinterpret_cast<const uint32_t*>(&o);
            }
            stsm4(ua + grp * 512, y[0], y[1], y[2], y[3]);
        }
        fence_async_smem();
        __syncthreads();
        if (tid == 0) {
            mbar_expect(sb + HB_WO, 131072);
            for (int i = 0; i < 8; i++) {
                if (YST) asm volatile("cp.async.bulk.tensor.2d.global.shared::cta.bulk_group [%0, {%1,%2}], [%3];" ::"l"(&tmY), "r"(DM + d0), "r"(i * 256), "r"(sb + H_U + i * 8192) : "memory");
                if (EVF & 2) tma2d_once(sb + 65536 + i * 16384, &tmWo, cc * 64, (kq * 8 + i) * 128, sb + HB_WO);
                else tma2d(sb + 65536 + i * 16384, &tmWo, cc * 64, (kq * 8 + i) * 128, sb + HB_WO);
                if (TRICKLE_NS) __nanosleep(TRICKLE_NS);
            }
            bulk_commit();
            asm volatile("cp.async.bulk.wait_group.read 0;" ::: "memory");
        }
    }
    __syncwarp();
    if (w < 8) {
        asm volatile("setmaxnreg.inc.sync.aligned.u32 208;");
        const int wg = w >> 2;
        uint32_t wo[32][4];
        mbar_wait_long(sb + HB_WO, 0);
        const uint32_t a = sb + 65536 + wg * 65536 + ((m >> 1) * 8 + r) * 128 + (((2 * (w & 3) + (m & 1)) ^ r) << 4);
#pragma unroll
        for (int i = 0; i < 32; i++) ldsm4t(wo[i], a + i * 2048);
        __syncthreads();
        HSTAMP(3);
        const int t = tid & 127;
        int st = 0, ph = 0;
#pragma unroll 1
        for (int s = 0; s < NSEG; s++) {
            const uint32_t desc = (((sb + H_STAGE + st * 65536 + wg * 32768) & 0x3FFFF) >> 4) | (8u << 16);
            float d[16];
#pragma unroll
            for (int q = 0; q < HSPLIT; q++) {
                mbar_wait_long(sb + HB_FULL + ((st * 2 + wg) * 4 + q) * 8, ph);
                wg_fence();
#pragma unroll
                for (int i = q * (32 / HSPLIT); i < (q + 1) * (32 / HSPLIT); i++) {
                    if (i == 0) wg_rs_n32<0, 16, 1>(d, wo[i], desc); else wg_rs_n32<1, 16, 1>(d, wo[i], desc + i * 64);
                }
                wg_commit();
            }
            if (s >= 4) mbar_wait_long(sb + HB_FIN + (s & 3) * 8, ((s - 4) >> 2) & 1);
            const uint32_t ra = sb + H_RED + (s & 1) * 8192 + t * 16;
            uint4* dst = g_part + (((s % RING) * 9 + cc) * 16 + wg * 8 + kq) * 128 + t;
            const uint32_t own = sb + H_OWN + (s & 3) * 2048 + t * 16;
            wg_wait<0>();
#pragma unroll
            for (int i = 0; i < 8; i++) { const float a0 = d[i], a1 = d[8 + i]; d[i] = wg ? a1 : a0; d[8 + i] = wg ? a0 : a1; }
#pragma unroll
            for (int i = 0; i < 2; i++) sts128(ra + wg * 4096 + i * 2048, __float_as_uint(d[8 + 4 * i]), __float_as_uint(d[9 + 4 * i]), __float_as_uint(d[10 + 4 * i]), __float_as_uint(d[11 + 4 * i]));
            mbar_arrive_if0(sb + HB_EMPTY + st * 8, lane);
            bar_sync<4, 256>();
            uint32_t p[8];
#pragma unroll
            for (int i = 0; i < 2; i++) lds128(p + 4 * i, ra + (wg ^ 1) * 4096 + i * 2048);
#pragma unroll
            for (int i = 0; i < 2; i++) {
#pragma unroll
                for (int k = 4 * i; k < 4 * i + 4; k++) p[k] = ((__float_as_uint(__uint_as_float(p[k]) + d[k]) + 64) & ~127u) | (s + 1);
                asm volatile("{.reg .pred q; setp.eq.u32 q, %6, %7;\n"
                             "@!q st.relaxed.gpu.global.v4.u32 [%0], {%2,%3,%4,%5};\n"
                             "@q st.shared.v4.u32 [%1], {%2,%3,%4,%5};}"
                             ::"l"(dst + i * 512), "r"(own), "r"(p[4 * i]), "r"(p[4 * i + 1]), "r"(p[4 * i + 2]), "r"(p[4 * i + 3]), "r"(kq), "r"(2 * wg + i) : "memory");
            }
            __syncwarp();
            mbar_arrive_if0(sb + HB_SENT + (s & 3) * 8, lane);
            HSTAMP4(s);
            if (++st == 3) { st = 0; ph ^= 1; }
        }
        if (tid == 0) bulk_wait0();
    } else {
        asm volatile("setmaxnreg.dec.sync.aligned.u32 88;");
        __syncthreads();
        if (w == 8) {
            const uint64_t pol = evict_first();
            int st = 0, ph = 1, ready = 0;
            for (int s = 0; s < NSEG; s++) {
                unsigned c = 0;
                while (ready <= s) {
                    const unsigned f = ld_acquire(&g_flag[kq * NSEG + min(s + (lane & 3), NSEG - 1)]);
                    ready = s + __ffs(~(__ballot_sync(0xffffffffu, f >= 8) & 15)) - 1;
                    if (++c >= LONG_LIM) break;
                    if (ready <= s && FLAG_NS) __nanosleep(FLAG_NS);
                }
                __syncwarp();
                if (lane == 0) {
                    asm volatile("fence.proxy.async.global;" ::: "memory");
                    HSTAMP3(s);
                    mbar_wait_long(sb + HB_EMPTY + st * 8, ph);
#pragma unroll
                    for (int k = 0; k < 2 * HSPLIT; k++) {
                        const int g = k & 1, q = k >> 1;
                        constexpr uint32_t bytes = 32768 / HSPLIT;
                        const uint32_t bar = sb + HB_FULL + ((st * 2 + g) * 4 + q) * 8;
                        mbar_expect(bar, bytes);
                        asm volatile("cp.async.bulk.shared::cluster.global.mbarrier::complete_tx::bytes.L2::cache_hint [%0], [%1], %2, [%3], %4;"
                                     ::"r"(sb + H_STAGE + st * 65536 + g * 32768 + q * bytes), "l"(g_ox + (s * NH + kq * 8 + g * 4) * 512 + q * (bytes / 16)), "r"(bytes), "r"(bar), "l"(pol) : "memory");
                    }
                }
                __syncwarp();
                if (++st == 3) { st = 0; ph ^= 1; }
            }
            unsigned last = 0;
            if (lane == 0) asm volatile("atom.acq_rel.gpu.global.inc.u32 %0, [%1], %2;" : "=r"(last) : "l"(&g_done_cnt), "r"(NHELP - 1) : "memory");
            if (__shfl_sync(0xffffffffu, last, 0) == NHELP - 1) {
                reinterpret_cast<uint4*>(g_flag)[lane] = make_uint4(0, 0, 0, 0);
                reinterpret_cast<uint4*>(g_flag)[32 + lane] = make_uint4(0, 0, 0, 0);
            }
        } else if (w < 11) {
            const int f = w - 9;
            const uint32_t fa = sb + H_FIN + f * 512;
            for (int s = 0; s < NSEG; s++) {
                mbar_wait_long(sb + HB_SENT + (s & 3) * 8, (s >> 2) & 1);
                const uint4* src = g_part + (((s % RING) * 9 + cc) * 16 + kq * 4) * 128 + f * 64 + lane;
                uint4 v[8];
                lds128(&v[6].x, sb + H_OWN + (s & 3) * 2048 + (f * 64 + lane) * 16);
                lds128(&v[7].x, sb + H_OWN + (s & 3) * 2048 + (f * 64 + 32 + lane) * 16);
                if (FIN0_NS) __nanosleep(FIN0_NS);
                unsigned c = 0;
                while (true) {
                    uint32_t bad = 0;
#pragma unroll
                    for (int i = 0; i < 6; i++) v[i] = ld_poll(src + ((kq + 1 + (i >> 1)) & 3) * 128 + (i & 1) * 32);
#pragma unroll
                    for (int i = 0; i < 6; i++) bad |= (v[i].x ^ (s + 1)) | (v[i].y ^ (s + 1)) | (v[i].z ^ (s + 1)) | (v[i].w ^ (s + 1));
                    if (!__any_sync(0xffffffffu, (bad & 127) != 0) || ++c >= LONG_LIM) break;
                    if (FIN_NS) __nanosleep(FIN_NS);
                }
                mbar_arrive_if0(sb + HB_FIN + (s & 3) * 8, lane);
                uint32_t pk[4];
#pragma unroll
                for (int u = 0; u < 2; u++) {
                    float o[4] = {0.f, 0.f, 0.f, 0.f};
#pragma unroll
                    for (int k = 0; k < 4; k++) {
                        o[0] += __uint_as_float(v[2 * k + u].x & ~127u); o[1] += __uint_as_float(v[2 * k + u].y & ~127u);
                        o[2] += __uint_as_float(v[2 * k + u].z & ~127u); o[3] += __uint_as_float(v[2 * k + u].w & ~127u);
                    }
                    pk[2 * u] = pack_bf16(o[0], o[1]); pk[2 * u + 1] = pack_bf16(o[2], o[3]);
                }
                stsm4t(fa + r * 64 + ((m ^ (r >> 1)) << 4), pk[0], pk[1], pk[2], pk[3]);
                __syncwarp();
                uint32_t o4[4];
                lds128(o4, fa + (lane >> 2) * 64 + (((lane & 3) ^ (lane >> 3)) << 4));
                *reinterpret_cast<uint4*>(out + (s * SEG + kq * 8 + (lane >> 2)) * OUTW + cc * 64 + f * 32 + (lane & 3) * 8) = make_uint4(o4[0], o4[1], o4[2], o4[3]);
                __syncwarp();
                HSTAMP2(s);
            }
            asm volatile("griddepcontrol.wait;" ::: "memory");
        }
    }
}

typedef CUresult (*EncodeFn)(CUtensorMap*, CUtensorMapDataType, cuuint32_t, void*, const cuuint64_t*, const cuuint64_t*, const cuuint32_t*,
                             const cuuint32_t*, CUtensorMapInterleave, CUtensorMapSwizzle, CUtensorMapL2promotion, CUtensorMapFloatOOBfill);

void make_map(EncodeFn fn, CUtensorMap* m, const void* p, int rank, const cuuint64_t* dims, const cuuint64_t* strides, const cuuint32_t* box,
              CUtensorMapSwizzle sw = CU_TENSOR_MAP_SWIZZLE_128B, CUtensorMapL2promotion pr = CU_TENSOR_MAP_L2_PROMOTION_L2_128B) {
    const cuuint32_t es[3] = {1, 1, 1};
    fn(m, CU_TENSOR_MAP_DATA_TYPE_BFLOAT16, rank, const_cast<void*>(p), dims, strides, box, es, CU_TENSOR_MAP_INTERLEAVE_NONE,
       sw, pr, CU_TENSOR_MAP_FLOAT_OOB_FILL_NONE);
}

}

extern "C" void kernel_launch(void* const* d_in, const int* in_sizes, int n_in, void* d_out, int out_size) {
    const bf16* x = (const bf16*)d_in[0];
    const bf16* mem0 = (const bf16*)d_in[1];
    const bf16* Wo = (const bf16*)d_in[5];
    bf16* out = (bf16*)d_out;

    static EncodeFn enc = nullptr;
    static char* acc = nullptr;
    if (!enc) {
        void* p = nullptr;
        cudaGetSymbolAddress(&p, g_acc);
        acc = reinterpret_cast<char*>((reinterpret_cast<uintptr_t>(p) + 32767) & ~(uintptr_t)32767);
        void* fn = nullptr;
        cudaDriverEntryPointQueryResult st;
        cudaGetDriverEntryPoint("cuTensorMapEncodeTiled", &fn, cudaEnableDefault, &st);
        enc = (EncodeFn)fn;
        cudaFuncSetAttribute(chain_kernel, cudaFuncAttributeMaxDynamicSharedMemorySize, A_SMEM);
        cudaFuncSetAttribute(helper_kernel, cudaFuncAttributeMaxDynamicSharedMemorySize, B_SMEM);
    }
    CUtensorMap tmW[3], tmWo, tmX;
    {
        const cuuint64_t dims[2] = {4096, 576}, str[1] = {8192};
        const cuuint32_t box[2] = {64, 192};
        for (int i = 0; i < 3; i++) make_map(enc, &tmW[i], d_in[2 + i], 2, dims, str, box, CU_TENSOR_MAP_SWIZZLE_128B, W_PROMO);
    }
    {
        const cuuint64_t dims[2] = {576, 4096}, str[1] = {1152};
        const cuuint32_t box[2] = {64, 128};
        make_map(enc, &tmWo, Wo, 2, dims, str, box);
    }
    {
        const cuuint64_t dims[3] = {64, 2048, 9}, str[2] = {1152, 128};
        const cuuint32_t box[3] = {64, 32, 9};
        make_map(enc, &tmX, x, 3, dims, str, box);
    }
    CUtensorMap tmU, tmY;
    {
        const cuuint64_t dimsU[2] = {576, 2048}, strU[1] = {1152}, dimsY[2] = {1152, 2048}, strY[1] = {2304};
        const cuuint32_t box[2] = {16, 256};
        make_map(enc, &tmU, d_in[7], 2, dimsU, strU, box, CU_TENSOR_MAP_SWIZZLE_32B, U_PROMO);
        make_map(enc, &tmY, out, 2, dimsY, strY, box, CU_TENSOR_MAP_SWIZZLE_32B, CU_TENSOR_MAP_L2_PROMOTION_NONE);
    }
    cudaStream_t st = cudaStreamPerThread;
    {
        cudaLaunchConfig_t cfg = {};
        cfg.gridDim = dim3(96); cfg.blockDim = dim3(384); cfg.dynamicSmemBytes = A_SMEM; cfg.stream = st;
        cudaLaunchAttribute at[1];
        at[0].id = cudaLaunchAttributeClusterDimension;
        at[0].val.clusterDim.x = 3; at[0].val.clusterDim.y = 1; at[0].val.clusterDim.z = 1;
        cfg.attrs = at; cfg.numAttrs = 1;
        cudaLaunchKernelEx(&cfg, chain_kernel, tmW[0], tmW[1], tmW[2], tmWo, tmX, mem0, acc);
    }
    {
        cudaLaunchConfig_t cfg = {};
        cfg.gridDim = dim3(NHELP); cfg.blockDim = dim3(384); cfg.dynamicSmemBytes = B_SMEM; cfg.stream = st;
        cudaLaunchAttribute at[1];
        at[0].id = cudaLaunchAttributeProgrammaticStreamSerialization;
        at[0].val.programmaticStreamSerializationAllowed = 1;
        cfg.attrs = at; cfg.numAttrs = 1;
        cudaLaunchKernelEx(&cfg, helper_kernel, tmU, tmY, tmWo, (const bf16*)d_in[8], (const bf16*)d_in[9], (const bf16*)d_in[10],
                           (const bf16*)d_in[11], (const bf16*)d_in[12], (const bf16*)d_in[13], out);
    }
}
```

```cpp
#include <cuda_runtime.h>
#include <cuda_bf16.h>
#include <cuda_fp16.h>
#include <cuda.h>
#include <stdint.h>

typedef __nv_bfloat16 bf16;

namespace {

constexpr int DM = 576, NH = 32, SEG = 32, NSEG = 64, SEQ = 2048, NST = 128;
constexpr int OUTW = 2 * DM;
constexpr unsigned SPIN_LIM = 1u << 15;

__device__ __align__(1024) uint4 g_acc[33 * 2048];
__device__ __align__(128) unsigned g_time[NSEG * 96];
__device__ __align__(1024) uint4 g_ox[NSEG * NH * 512];
__device__ __align__(1024) uint4 g_vx[NH * 2 * 512];
__device__ __align__(128) unsigned g_flag[NSEG * 4];
__device__ unsigned g_done_cnt;
__device__ unsigned g_zero_cnt;

__device__ __forceinline__ uint32_t smem_u32(const void* p) { return (uint32_t)__cvta_generic_to_shared(p); }
__device__ __forceinline__ unsigned clk() { unsigned c; asm volatile("mov.u32 %0, %%clock;" : "=r"(c)::"memory"); return c; }
__device__ __forceinline__ unsigned gtime() { unsigned t; asm volatile("mov.u32 %0, %%globaltimer_lo;" : "=r"(t)::"memory"); return t; }
__device__ __forceinline__ uint32_t slot_off(int s) { return (s >> 1) * 32768 + (s & 1) * 512; }
__device__ __forceinline__ uint32_t lane_off(uint32_t L16) { return (L16 & 0x180) * 8 + (L16 & 0x40) * 4 + (L16 & 0x30); }
__device__ __forceinline__ uint32_t mapa(uint32_t a, uint32_t r) { uint32_t o; asm("mapa.shared::cluster.u32 %0, %1, %2;" : "=r"(o) : "r"(a), "r"(r)); return o; }
__device__ __forceinline__ void mbar_init(uint32_t b, uint32_t n) { asm volatile("mbarrier.init.shared::cta.b64 [%0], %1;" ::"r"(b), "r"(n) : "memory"); }
__device__ __forceinline__ void mbar_expect(uint32_t b, uint32_t tx) { asm volatile("mbarrier.arrive.expect_tx.shared::cta.b64 _, [%0], %1;" ::"r"(b), "r"(tx) : "memory"); }
__device__ __forceinline__ bool mbar_test(uint32_t b, uint32_t par) {
    uint32_t ok;
    asm volatile("{.reg .pred p; mbarrier.test_wait.parity.shared::cta.b64 p, [%1], %2; selp.u32 %0, 1, 0, p;}" : "=r"(ok) : "r"(b), "r"(par) : "memory");
    return ok;
}
__device__ __forceinline__ void mbar_wait(uint32_t b, uint32_t par) {
    asm volatile("{.reg .pred p, q; .reg .u32 c; mov.u32 c, 0;\n"
                 "W: add.u32 c, c, 1; setp.ge.u32 q, c, %2;\n @q bra D;\n mbarrier.try_wait.parity.shared::cta.b64 p, [%0], %1;\n"
                 "@!p bra W;\n D:\n}" ::"r"(b), "r"(par), "n"(SPIN_LIM) : "memory");
}
constexpr unsigned LONG_LIM = 1u << 17;
__device__ __forceinline__ void mbar_wait_long(uint32_t b, uint32_t par) {
    asm volatile("{.reg .pred p, q; .reg .u32 c; mov.u32 c, 0;\n"
                 "W: mbarrier.try_wait.parity.shared::cta.b64 p, [%0], %1;\n"
                 "@p bra D;\n add.u32 c, c, 1; setp.lt.u32 q, c, %2;\n @q bra W;\n D:\n}" ::"r"(b), "r"(par), "n"(LONG_LIM) : "memory");
}
__device__ __forceinline__ void fence_async_smem() { asm volatile("fence.proxy.async.shared::cta;" ::: "memory"); }
__device__ __forceinline__ void ldsm4(uint32_t* r, uint32_t a) { asm volatile("ldmatrix.sync.aligned.m8n8.x4.shared.b16 {%0,%1,%2,%3},[%4];" : "=r"(r[0]), "=r"(r[1]), "=r"(r[2]), "=r"(r[3]) : "r"(a) : "memory"); }
__device__ __forceinline__ void ldsm4t(uint32_t* r, uint32_t a) { asm volatile("ldmatrix.sync.aligned.m8n8.x4.trans.shared.b16 {%0,%1,%2,%3},[%4];" : "=r"(r[0]), "=r"(r[1]), "=r"(r[2]), "=r"(r[3]) : "r"(a) : "memory"); }
__device__ __forceinline__ void stsm1(uint32_t a, uint32_t r0) { asm volatile("stmatrix.sync.aligned.m8n8.x1.shared.b16 [%0],{%1};" ::"r"(a), "r"(r0) : "memory"); }
__device__ __forceinline__ void stsm2t(uint32_t a, uint32_t r0, uint32_t r1) { asm volatile("stmatrix.sync.aligned.m8n8.x2.trans.shared.b16 [%0],{%1,%2};" ::"r"(a), "r"(r0), "r"(r1) : "memory"); }
__device__ __forceinline__ void stsm4t(uint32_t a, uint32_t r0, uint32_t r1, uint32_t r2, uint32_t r3) { asm volatile("stmatrix.sync.aligned.m8n8.x4.trans.shared.b16 [%0],{%1,%2,%3,%4};" ::"r"(a), "r"(r0), "r"(r1), "r"(r2), "r"(r3) : "memory"); }
__device__ __forceinline__ void stsm4(uint32_t a, uint32_t r0, uint32_t r1, uint32_t r2, uint32_t r3) { asm volatile("stmatrix.sync.aligned.m8n8.x4.shared.b16 [%0],{%1,%2,%3,%4};" ::"r"(a), "r"(r0), "r"(r1), "r"(r2), "r"(r3) : "memory"); }
__device__ __forceinline__ void sts32(uint32_t a, uint32_t v) { asm volatile("st.shared.b32 [%0], %1;" ::"r"(a), "r"(v) : "memory"); }
__device__ __forceinline__ void sts64(uint32_t a, uint32_t x, uint32_t y) { asm volatile("st.shared.v2.b32 [%0], {%1,%2};" ::"r"(a), "r"(x), "r"(y) : "memory"); }
__device__ __forceinline__ void sts128(uint32_t a, uint32_t x, uint32_t y, uint32_t z, uint32_t w) { asm volatile("st.shared.v4.b32 [%0], {%1,%2,%3,%4};" ::"r"(a), "r"(x), "r"(y), "r"(z), "r"(w) : "memory"); }
__device__ __forceinline__ void lds64(uint32_t* r, uint32_t a) { asm volatile("ld.shared.v2.b32 {%0,%1},[%2];" : "=r"(r[0]), "=r"(r[1]) : "r"(a) : "memory"); }
__device__ __forceinline__ float2 lds64f(uint32_t a) { float2 v; asm volatile("ld.shared.v2.f32 {%0,%1},[%2];" : "=f"(v.x), "=f"(v.y) : "r"(a) : "memory"); return v; }
__device__ __forceinline__ void lds128(uint32_t* r, uint32_t a) { asm volatile("ld.shared.v4.b32 {%0,%1,%2,%3},[%4];" : "=r"(r[0]), "=r"(r[1]), "=r"(r[2]), "=r"(r[3]) : "r"(a) : "memory"); }
__device__ __forceinline__ void st_async64(uint32_t a, uint32_t x, uint32_t y, uint32_t bar) {
    asm volatile("st.async.weak.shared::cluster.mbarrier::complete_tx::bytes.v2.b32 [%0], {%1,%2}, [%3];" ::"r"(a), "r"(x), "r"(y), "r"(bar) : "memory");
}
__device__ __forceinline__ void st_async32(uint32_t a, uint32_t x, uint32_t bar) {
    asm volatile("st.async.weak.shared::cluster.mbarrier::complete_tx::bytes.b32 [%0], %1, [%2];" ::"r"(a), "r"(x), "r"(bar) : "memory");
}
__device__ __forceinline__ void ldsm2(uint32_t* r, uint32_t a) { asm volatile("ldmatrix.sync.aligned.m8n8.x2.shared.b16 {%0,%1},[%2];" : "=r"(r[0]), "=r"(r[1]) : "r"(a) : "memory"); }
__device__ __forceinline__ uint32_t pack_f16_sat(float lo, float hi) { uint32_t r; asm("cvt.rn.satfinite.f16x2.f32 %0, %1, %2;" : "=r"(r) : "f"(hi), "f"(lo)); return r; }
__device__ __forceinline__ __half2 as_h2(uint32_t x) { return *reinterpret_cast<__half2*>(&x); }
__device__ __forceinline__ uint32_t as_u32(__half2 x) { return *reinterpret_cast<uint32_t*>(&x); }
__device__ __forceinline__ uint32_t pack_bf16(float lo, float hi) { uint32_t r; asm("cvt.rn.bf16x2.f32 %0, %1, %2;" : "=r"(r) : "f"(hi), "f"(lo)); return r; }
__device__ __forceinline__ float ex2(float x) { float r; asm("ex2.approx.ftz.f32 %0, %1;" : "=f"(r) : "f"(x)); return r; }
__device__ __forceinline__ float rcp(float x) { float r; asm("rcp.approx.ftz.f32 %0, %1;" : "=f"(r) : "f"(x)); return r; }
__device__ __forceinline__ void mma16(float* d, const uint32_t* a, uint32_t b0, uint32_t b1) {
    asm volatile("mma.sync.aligned.m16n8k16.row.col.f32.bf16.bf16.f32 {%0,%1,%2,%3},{%4,%5,%6,%7},{%8,%9},{%0,%1,%2,%3};"
                 : "+f"(d[0]), "+f"(d[1]), "+f"(d[2]), "+f"(d[3]) : "r"(a[0]), "r"(a[1]), "r"(a[2]), "r"(a[3]), "r"(b0), "r"(b1));
}
__device__ __forceinline__ void mma16z(float* d, const uint32_t* a, uint32_t b0, uint32_t b1) {
    asm volatile("mma.sync.aligned.m16n8k16.row.col.f32.bf16.bf16.f32 {%0,%1,%2,%3},{%4,%5,%6,%7},{%8,%9},{%10,%10,%10,%10};"
                 : "=f"(d[0]), "=f"(d[1]), "=f"(d[2]), "=f"(d[3]) : "r"(a[0]), "r"(a[1]), "r"(a[2]), "r"(a[3]), "r"(b0), "r"(b1), "f"(0.f));
}
__device__ __forceinline__ void mma8(float* d, uint32_t a0, uint32_t a1, uint32_t b0) {
    asm volatile("mma.sync.aligned.m16n8k8.row.col.f32.bf16.bf16.f32 {%0,%1,%2,%3},{%4,%5},{%6},{%0,%1,%2,%3};"
                 : "+f"(d[0]), "+f"(d[1]), "+f"(d[2]), "+f"(d[3]) : "r"(a0), "r"(a1), "r"(b0));
}
template <int ACC>
__device__ __forceinline__ void mma_sp(float* d, const uint32_t* a, const uint32_t* b) {
    if (ACC)
        asm volatile("mma.sp::ordered_metadata.sync.aligned.m16n8k32.row.col.f32.bf16.bf16.f32 {%0,%1,%2,%3},{%4,%5,%6,%7},{%8,%9,%10,%11},{%0,%1,%2,%3},%12,0x0;"
                     : "+f"(d[0]), "+f"(d[1]), "+f"(d[2]), "+f"(d[3])
                     : "r"(a[0]), "r"(a[1]), "r"(a[2]), "r"(a[3]), "r"(b[0]), "r"(b[1]), "r"(b[2]), "r"(b[3]), "r"(0xEEEE4444u));
    else
        asm volatile("mma.sp::ordered_metadata.sync.aligned.m16n8k32.row.col.f32.bf16.bf16.f32 {%0,%1,%2,%3},{%4,%5,%6,%7},{%8,%9,%10,%11},{%13,%13,%13,%13},%12,0x0;"
                     : "=f"(d[0]), "=f"(d[1]), "=f"(d[2]), "=f"(d[3])
                     : "r"(a[0]), "r"(a[1]), "r"(a[2]), "r"(a[3]), "r"(b[0]), "r"(b[1]), "r"(b[2]), "r"(b[3]), "r"(0xEEEE4444u), "f"(0.f));
}
__device__ __forceinline__ void mbar_arrive_if0(uint32_t b, uint32_t z) { asm volatile("{.reg .pred p; setp.eq.u32 p, %1, 0; @p mbarrier.arrive.shared::cta.b64 _, [%0];}" ::"r"(b), "r"(z) : "memory"); }
__device__ __forceinline__ void mbar_expect_if0(uint32_t b, uint32_t tx, uint32_t z) { asm volatile("{.reg .pred p; setp.eq.u32 p, %2, 0; @p mbarrier.arrive.expect_tx.shared::cta.b64 _, [%0], %1;}" ::"r"(b), "r"(tx), "r"(z) : "memory"); }
__device__ __forceinline__ float lds32f(uint32_t a) { float v; asm volatile("ld.shared.f32 %0,[%1];" : "=f"(v) : "r"(a) : "memory"); return v; }
__device__ __forceinline__ void wg_fence() { asm volatile("wgmma.fence.sync.aligned;" ::: "memory"); }
__device__ __forceinline__ void wg_commit() { asm volatile("wgmma.commit_group.sync.aligned;" ::: "memory"); }
template <int N> __device__ __forceinline__ void wg_wait() { asm volatile("wgmma.wait_group.sync.aligned %0;" ::"n"(N) : "memory"); }
__device__ __forceinline__ void delay(unsigned n) { if (n) { const unsigned t0 = clk(); while (clk() - t0 < n) {} } }
template <int ACC, uint32_t DHI = 0x40000040u, int TB = 0>
__device__ __forceinline__ void wg_rs_n32(float* d, const uint32_t* a, uint32_t dlo) {
    if (ACC)
        asm volatile("{.reg .b64 db; mov.b64 db, {%20, %21};\n"
                     "wgmma.mma_async.sync.aligned.m64n32k16.f32.bf16.bf16 {%0,%1,%2,%3,%4,%5,%6,%7,%8,%9,%10,%11,%12,%13,%14,%15},{%16,%17,%18,%19},db,1,1,1,%22;}"
                     : "+f"(d[0]), "+f"(d[1]), "+f"(d[2]), "+f"(d[3]), "+f"(d[4]), "+f"(d[5]), "+f"(d[6]), "+f"(d[7]),
                       "+f"(d[8]), "+f"(d[9]), "+f"(d[10]), "+f"(d[11]), "+f"(d[12]), "+f"(d[13]), "+f"(d[14]), "+f"(d[15])
                     : "r"(a[0]), "r"(a[1]), "r"(a[2]), "r"(a[3]), "r"(dlo), "r"(DHI), "n"(TB));
    else
        asm volatile("{.reg .b64 db; mov.b64 db, {%20, %21};\n"
                     "wgmma.mma_async.sync.aligned.m64n32k16.f32.bf16.bf16 {%0,%1,%2,%3,%4,%5,%6,%7,%8,%9,%10,%11,%12,%13,%14,%15},{%16,%17,%18,%19},db,0,1,1,%22;}"
                     : "=f"(d[0]), "=f"(d[1]), "=f"(d[2]), "=f"(d[3]), "=f"(d[4]), "=f"(d[5]), "=f"(d[6]), "=f"(d[7]),
                       "=f"(d[8]), "=f"(d[9]), "=f"(d[10]), "=f"(d[11]), "=f"(d[12]), "=f"(d[13]), "=f"(d[14]), "=f"(d[15])
                     : "r"(a[0]), "r"(a[1]), "r"(a[2]), "r"(a[3]), "r"(dlo), "r"(DHI), "n"(TB));
}
__device__ __forceinline__ uint32_t desc_lo(uint32_t addr) { return ((addr & 0x3FFFF) >> 4) | (1u << 16); }
__device__ __forceinline__ void tma2d(uint32_t dst, const CUtensorMap* m, int c0, int c1, uint32_t bar) {
    asm volatile("cp.async.bulk.tensor.2d.shared::cluster.global.mbarrier::complete_tx::bytes [%0], [%1, {%2,%3}], [%4];"
                 ::"r"(dst), "l"(m), "r"(c0), "r"(c1), "r"(bar) : "memory");
}
__device__ __forceinline__ uint64_t evict_first() { uint64_t p; asm("createpolicy.fractional.L2::evict_first.b64 %0, 1.0;" : "=l"(p)); return p; }
__device__ __forceinline__ void tma2d_once(uint32_t dst, const CUtensorMap* m, int c0, int c1, uint32_t bar) {
    const uint64_t pol = evict_first();
    asm volatile("cp.async.bulk.tensor.2d.shared::cluster.global.mbarrier::complete_tx::bytes.L2::cache_hint [%0], [%1, {%2,%3}], [%4], %5;"
                 ::"r"(dst), "l"(m), "r"(c0), "r"(c1), "r"(bar), "l"(pol) : "memory");
}
__device__ __forceinline__ void tma3d(uint32_t dst, const CUtensorMap* m, int c0, int c1, int c2, uint32_t bar) {
    asm volatile("cp.async.bulk.tensor.3d.shared::cluster.global.mbarrier::complete_tx::bytes [%0], [%1, {%2,%3,%4}], [%5];"
                 ::"r"(dst), "l"(m), "r"(c0), "r"(c1), "r"(c2), "r"(bar) : "memory");
}
__device__ __forceinline__ void tma3d_mc(uint32_t dst, const CUtensorMap* m, int c0, int c1, int c2, uint32_t bar, uint16_t mask) {
    asm volatile("cp.async.bulk.tensor.3d.shared::cluster.global.mbarrier::complete_tx::bytes.multicast::cluster.L2::cache_hint [%0], [%1, {%2,%3,%4}], [%5], %6, %7;"
                 ::"r"(dst), "l"(m), "r"(c0), "r"(c1), "r"(c2), "r"(bar), "h"(mask), "l"(evict_first()) : "memory");
}
__device__ __forceinline__ void bulk_g2s_mc(uint32_t dst, const void* src, uint32_t bytes, uint32_t bar, uint16_t mask) {
    asm volatile("cp.async.bulk.shared::cluster.global.mbarrier::complete_tx::bytes.multicast::cluster [%0], [%1], %2, [%3], %4;"
                 ::"r"(dst), "l"(src), "r"(bytes), "r"(bar), "h"(mask) : "memory");
}
__device__ __forceinline__ void bulk_s2c(uint32_t dst, uint32_t src, uint32_t bytes, uint32_t bar) {
    asm volatile("cp.async.bulk.shared::cluster.shared::cta.mbarrier::complete_tx::bytes [%0], [%1], %2, [%3];" ::"r"(dst), "r"(src), "r"(bytes), "r"(bar) : "memory");
}
__device__ __forceinline__ void bulk_s2g(void* dst, uint32_t src, uint32_t bytes) {
    asm volatile("cp.async.bulk.global.shared::cta.bulk_group [%0], [%1], %2;" ::"l"(dst), "r"(src), "r"(bytes) : "memory");
}
__device__ __forceinline__ void bulk_commit() { asm volatile("cp.async.bulk.commit_group;" ::: "memory"); }
__device__ __forceinline__ void bulk_wait0() { asm volatile("cp.async.bulk.wait_group 0;" ::: "memory"); }
__device__ __forceinline__ uint4 ld_poll(const void* p) {
    uint4 v;
    asm volatile("ld.relaxed.gpu.global.v4.u32 {%0,%1,%2,%3},[%4];" : "=r"(v.x), "=r"(v.y), "=r"(v.z), "=r"(v.w) : "l"(p) : "memory");
    return v;
}
template <int IMM>
__device__ __forceinline__ void ld_poll_at(uint4& v, const void* p) {
    asm volatile("ld.relaxed.gpu.global.v4.u32 {%0,%1,%2,%3},[%4+%5];" : "=r"(v.x), "=r"(v.y), "=r"(v.z), "=r"(v.w) : "l"(p), "n"(IMM) : "memory");
}
__device__ __forceinline__ void look(uint4 (&v)[6], const void* p) {
    ld_poll_at<0>(v[0], p); ld_poll_at<16384>(v[1], p); ld_poll_at<64>(v[2], p);
    ld_poll_at<16384 + 64>(v[3], p); ld_poll_at<128>(v[4], p); ld_poll_at<16384 + 128>(v[5], p);
}
__device__ __forceinline__ unsigned ld_acquire(const unsigned* p) { unsigned v; asm volatile("ld.acquire.gpu.global.u32 %0,[%1];" : "=r"(v) : "l"(p) : "memory"); return v; }

template <int ID, int N> __device__ __forceinline__ void bar_sync() { asm volatile("bar.sync %0, %1;" ::"n"(ID), "n"(N) : "memory"); }
template <int ID, int N> __device__ __forceinline__ void bar_arrive() { asm volatile("bar.arrive %0, %1;" ::"n"(ID), "n"(N) : "memory"); }
__device__ __forceinline__ void cluster_arrive() { asm volatile("barrier.cluster.arrive.relaxed.aligned;" ::: "memory"); }
__device__ __forceinline__ void cluster_wait() { asm volatile("barrier.cluster.wait.aligned;" ::: "memory"); }

constexpr uint32_t XB_BYTES = 36864;
constexpr uint32_t S_XB = 0;
constexpr uint32_t S_QM = 73728;
constexpr uint32_t S_KM = 74752;
constexpr uint32_t S_OM = 75776;
constexpr uint32_t S_SP = 77824;
constexpr uint32_t S_SUM = 80384;
constexpr uint32_t S_TGT = 81408;
constexpr uint32_t S_VM = 147456;
constexpr uint32_t S_QX = 86016;
constexpr uint32_t S_PX = S_QX;
constexpr uint32_t S_KX = 94208;
constexpr uint32_t S_VX = 102400;
constexpr uint32_t S_SX = 135168;
constexpr uint32_t S_OX = 155648;
constexpr uint32_t S_MEM = 172032;
constexpr uint32_t S_WO = 181248;
constexpr uint32_t S_BAR = 230400;
constexpr uint32_t S_ZERO = S_BAR + 128;
constexpr uint32_t A_SMEM = S_ZERO + 1024;
__host__ __device__ constexpr uint32_t s_w(int c) { return c == 0 ? S_WO : 73728 + (c - 1) * 49152; }
constexpr uint32_t B_W = S_BAR, B_WO = S_BAR + 24, B_X = S_BAR + 32, B_S = S_BAR + 48, B_VX = S_BAR + 56, B_SX = S_BAR + 72, B_M = S_BAR + 88, B_T = S_BAR + 112;
constexpr int NB_QK = 1, NB_O = 2, NB_RED = 3, NB_P = 4, NB_AUX = 5, NB_PRO = 6, NB_X = 7, NB_GO = 8, NB_L = 9, NB_PV = 10, NB_T0 = 11;

constexpr float SM_SCALE = 0.08838834764831845f * 1.4426950408889634f;
constexpr uint32_t ONES = 0x3F803F80u;
constexpr uint32_t FULL_COUNT = 0x4200u;
#define TGT_NS 1028
#define FIRST_NS 150
constexpr int LOOK_NS = 100, XTMA_NS = 50, U0_NS = 4500, TRICKLE_NS = 700, POLL_NS = 40;
constexpr int HAND_AT = 26;
constexpr int NCH = 2;
constexpr int HSPLIT = 2;
constexpr int REG_MAIN = 232, REG_AUX = 40;
static_assert(2 * REG_MAIN + REG_AUX <= 504, "the three warpgroups share 3 x 168 registers");
#define HSTAMP(i) do {} while (0)
#define HSTAMP2(i) do {} while (0)
#define HSTAMP3(i) do {} while (0)
#define HSTAMP4(i) do {} while (0)
#define TSTAMP(i, e) do {} while (0)

__device__ __forceinline__ void load_scores(uint32_t a, __half2 (&hs)[5]) {
    uint32_t r[10];
    ldsm4(r, a);
    ldsm4(r + 4, a + 512);
    ldsm2(r + 8, a + 1024);
    const __half2 hf = as_h2(0x38003800u);
#pragma unroll
    for (int T = 0; T < 5; T++) hs[T] = __hfma2(as_h2(r[2 * T]), hf, __hmul2(as_h2(r[2 * T + 1]), hf));
}
__device__ __forceinline__ void softmax_exp(const __half2 (&hs)[5], float (&ev)[10]) {
    __half2 m = __hmax2(__hmax2(__hmax2(hs[0], hs[1]), __hmax2(hs[2], hs[3])), hs[4]);
    const uint32_t mu = as_u32(m);
    const uint32_t m1 = __shfl_xor_sync(0xffffffffu, mu, 1), m2 = __shfl_xor_sync(0xffffffffu, mu, 2), m3 = __shfl_xor_sync(0xffffffffu, mu, 3);
    m = __hmax2(__hmax2(m, as_h2(m1)), __hmax2(as_h2(m2), as_h2(m3)));
    const float mc = -fmaxf(__low2float(m), __high2float(m)) * (2.f * SM_SCALE);
#pragma unroll
    for (int T = 0; T < 5; T++) {
        ev[2 * T] = ex2(fmaf(__low2float(hs[T]), 2.f * SM_SCALE, mc));
        ev[2 * T + 1] = ex2(fmaf(__high2float(hs[T]), 2.f * SM_SCALE, mc));
    }
}

__device__ __forceinline__ void x_scores(uint32_t sb, int seg, int wq, uint32_t L16, float (&ev)[10]) {
    __half2 hs[5];
    load_scores(sb + S_SX + (seg & 1) * 5120 + wq * 1280 + L16, hs);
    const int dg = (int)(L16 >> 6) - (int)((L16 >> 3) & 6) + 8 * wq;
#pragma unroll
    for (int T = 0; T < 4; T++) {
        uint32_t u = as_u32(hs[T]);
        if (dg < 8 * T + 1) u = (u & 0xFFFFu) | 0xFC000000u;
        if (dg < 8 * T) u = 0xFC00FC00u;
        hs[T] = as_h2(u);
    }
    softmax_exp(hs, ev);
}
__device__ __forceinline__ void x_probs(uint32_t sb, int seg, int wq, uint32_t L16, const float (&ev)[10]) {
    float l = ((ev[0] + ev[1]) + (ev[2] + ev[3])) + ((ev[4] + ev[5]) + (ev[6] + ev[7])) + (ev[8] + ev[9]);
    const float l1 = __shfl_xor_sync(0xffffffffu, l, 1), l2 = __shfl_xor_sync(0xffffffffu, l, 2), l3 = __shfl_xor_sync(0xffffffffu, l, 3);
    const float r = rcp((l + l1) + (l2 + l3));
    const uint32_t a = sb + S_PX + (seg & 1) * 4096 + wq * 640 + (L16 >> 2);
#pragma unroll
    for (int i = 0; i < 5; i++) sts32(a + i * 128, pack_bf16(ev[2 * i] * r, ev[2 * i + 1] * r));
}
__device__ __forceinline__ void x_pv_load(uint32_t sb, int seg, int w, uint32_t L16, uint32_t (&a)[3][4]) {
    lds128(a[0], sb + S_VX + (seg & 3) * 8192 + w * 1024 + L16);
    lds128(a[1], sb + S_VX + (seg & 3) * 8192 + w * 1024 + 512 + L16);
    lds64(a[2], sb + S_VM + (seg & 3) * 2048 + w * 256 + (L16 >> 1));
    a[2][2] = 0; a[2][3] = 0;
}
__device__ __forceinline__ void x_pv_run(uint32_t sb, int seg, const uint32_t (&a)[3][4], uint32_t (&pk)[8]) {
    const uint32_t d = ((sb + S_PX + (seg & 1) * 4096) & 0x3FFFF) >> 4;
    float o[16];
    wg_fence();
    wg_rs_n32<0, 40>(o, a[0], d | (8u << 16));
    wg_rs_n32<1, 40>(o, a[1], (d + 16) | (8u << 16));
    wg_rs_n32<1, 40>(o, a[2], d + 32);
    wg_commit();
    wg_wait<0>();
#pragma unroll
    for (int i = 0; i < 8; i++) pk[i] = pack_bf16(o[2 * i], o[2 * i + 1]);
}
__device__ __forceinline__ void x_pv_store(uint32_t sb, int seg, int w, uint32_t L16, const uint32_t (&pk)[8]) {
    const uint32_t a = sb + S_OX + (seg & 1) * 8192 + w * 1024 + L16;
    stsm4(a, pk[0], pk[1], pk[2], pk[3]);
    stsm4(a + 512, pk[4], pk[5], pk[6], pk[7]);
}
template <int BAR, int CNT>
__device__ __forceinline__ void x_pv_both(uint32_t sb, int seg, int wq, uint32_t L16) {
    uint32_t pva[3][4], pk[8];
    x_pv_load(sb, seg, wq + 4, L16, pva);
    bar_sync<BAR, CNT>();
    x_pv_run(sb, seg, pva, pk);
    x_pv_load(sb, seg, wq, L16, pva);
    x_pv_store(sb, seg, wq + 4, L16, pk);
    x_pv_run(sb, seg, pva, pk);
    x_pv_store(sb, seg, wq, L16, pk);
}
__device__ __forceinline__ void ox_store(uint32_t sb, int seg, uint32_t h) {
    fence_async_smem();
    bulk_s2g(g_ox + (seg * NH + h) * 512, sb + S_OX + (seg & 1) * 8192, 8192);
    bulk_commit();
}
__device__ __forceinline__ void ox_publish(int seg, uint32_t h) {
    bulk_wait0();
    asm volatile("fence.proxy.async.global;" ::: "memory");
    asm volatile("red.relaxed.gpu.global.add.u32 [%0], 1;" ::"l"(&g_flag[(h >> 3) * NSEG + seg]) : "memory");
}
__device__ __forceinline__ void vx_store(uint32_t sb, int seg, uint32_t h) {
    fence_async_smem();
    bulk_s2g(g_vx + (h * 2 + (seg & 1)) * 512, sb + S_VX + (seg & 3) * 8192, 8192);
    bulk_commit();
}
__device__ __forceinline__ void vx_fetch(uint32_t sb, int seg, uint32_t h) {
    bulk_wait0();
    bulk_g2s_mc(sb + S_VX + (seg & 3) * 8192, g_vx + (h * 2 + (seg & 1)) * 512, 8192, sb + B_VX + (seg & 1) * 8, 3);
}

__device__ __forceinline__ void x_pack(const float (&d)[16], uint32_t (&pk)[8]) {
#pragma unroll
    for (int i = 0; i < 8; i++) pk[i] = pack_bf16(d[2 * i], d[2 * i + 1]);
}
__device__ __forceinline__ void x_write(uint32_t sb, const uint32_t (&pk)[8], int seg, bool isv, int w, uint32_t L16) {
    if (!isv) {
        const uint32_t a = sb + S_QX + (w >> 2) * 8192 + (seg & 1) * 4096 + (w & 3) * 256 + (L16 & 0xF0) + (L16 & 0x100) * 4;
        stsm4t(a, pk[0], pk[1], pk[2], pk[3]);
        stsm4t(a + 2048, pk[4], pk[5], pk[6], pk[7]);
    } else {
        const uint32_t a = sb + S_VX + (seg & 3) * 8192 + w * 1024 + L16;
        sts128(a, pk[0], pk[1], pk[2], pk[3]);
        sts128(a + 512, pk[4], pk[5], pk[6], pk[7]);
    }
}

template <int K0, int K1>
__device__ __forceinline__ void x_project(float (&d)[16], const uint32_t (&wA)[36][4], uint32_t desc) {
#pragma unroll
    for (int i = K0; i < K1; i++) {
        const uint32_t db = desc + (((i >> 2) * 4096 + (i & 3) * 32) >> 4);
        if (i == 0) wg_rs_n32<0>(d, wA[i], db); else wg_rs_n32<1>(d, wA[i], db);
    }
}

__device__ __forceinline__ void mem_scores(uint32_t sb, uint32_t peerA, uint32_t peerB, uint32_t off, const uint32_t (&q0)[4], const uint32_t (&q1)[4],
                                           const uint32_t (&k0)[4], const uint32_t (&k1)[4]) {
    float e0[4], o0[4], e1[4], o1[4];
    mma16z(e0, q0, k0[0], k0[1]);
    mma16z(o0, q0, k0[2], k0[3]);
    mma16z(e1, q1, k1[0], k1[1]);
    mma16z(o1, q1, k1[2], k1[3]);
    const uint32_t sc = pack_f16_sat((e0[0] + o0[2]) + (e1[0] + o1[2]), (e0[1] + o0[3]) + (e1[1] + o1[3]));
    st_async32(peerB + off, sc, peerB + B_S);
    st_async32(peerA + off, sc, peerA + B_S);
    sts32(sb + off, sc);
    __syncwarp();
}

__device__ __forceinline__ unsigned post_time(int s, uint32_t L16, unsigned early) {
    delay(1);
    const unsigned t = (gtime() & ~3u) | 1 | (early ? 2 : 0);
    if (L16 == 0) asm volatile("st.relaxed.gpu.global.u32 [%0], %1;" ::"l"(g_time + s * 96 + blockIdx.x), "r"(t) : "memory");
    return t;
}
__device__ __forceinline__ void plan_look(uint32_t sb, int s, uint32_t L16, unsigned t, int& state) {
    const char* p = reinterpret_cast<const char*>(g_time) + s * 384 + (L16 < 384 ? L16 : 0);
    uint4 v;
    unsigned c = 0;
    do { v = ld_poll(p); } while (__any_sync(0xffffffffu, (v.x & v.y & v.z & v.w & 1) == 0) && ++c < SPIN_LIM);
    const int d = max(max((int)(v.x - t), (int)(v.y - t)), max((int)(v.z - t), (int)(v.w - t))) + (s == 0 ? FIRST_NS : 0);
    if (s >= 3) {
        const bool bad = __popc(__ballot_sync(0xffffffffu, (v.x | v.y | v.z | v.w) & 2)) >= 4;
        int e = state & 63, x = state >> 6;
        e = bad ? max(e, 16) + 9 : e - 1;
        if (e >= 32) { x = min(x + 32, 256); e = 16; }
        if (e <= 0) { x = max(x - 32, 0); e = 16; }
        state = x * 64 + e;
    }
    t = (t & ~3u) + (state >> 6);
    const unsigned tgt = t + min(__reduce_max_sync(0xffffffffu, d), 20000) + TGT_NS;
    if (L16 < 48) { const uint32_t r = mapa(sb, L16 >> 4); st_async32(r + S_TGT, tgt, r + B_T); }
}

__device__ __forceinline__ void load_wo(uint32_t sb, int w, uint32_t L16, uint32_t (&woA)[8][4], uint32_t (&woB)[4][4]) {
    mbar_wait(sb + B_WO, 0);
    if (w < 4) TSTAMP(73, 0);
    const int m = L16 >> 7, r = (L16 >> 4) & 7;
    const int ca = 3 * w + (m & 1), cb = 3 * w + 2;
    const uint32_t aA = sb + S_WO + (ca >> 3) * 16384 + ((m >> 1) * 8 + r) * 128 + (((ca & 7) ^ r) << 4);
    const int eB = ((m & 2) + ((r >> 1) & 1)) * 8 + 4 * (m & 1) + 2 * (r >> 2) + (r & 1);
    const uint32_t aB = sb + S_WO + (cb >> 3) * 16384 + eB * 128 + (((cb & 7) ^ (eB & 7)) << 4);
#pragma unroll
    for (int i = 0; i < 8; i++) ldsm4t(woA[i], aA + i * 2048);
#pragma unroll
    for (int i = 0; i < 4; i++) ldsm4t(woB[i], aB + i * 4096);
}

template <int ROLE>
__device__ __forceinline__ void chain_main(const uint32_t sb, const uint32_t lane16, const int wq, const uint32_t j, const uint32_t h,
                                           const uint32_t peerA, const uint32_t peerB, char* const acc) {
    uint32_t L16 = lane16;
    constexpr bool isv = ROLE >= 2;
    constexpr int wg = ROLE & 1;
    const int w = wg * 4 + wq;
    const uint32_t xdesc = desc_lo(sb + S_XB);
    uint32_t wA[36][4], woA[8][4], woB[4][4];
    float xd[16];
    {
        const int m = L16 >> 7, r = (L16 >> 4) & 7;
        const int blk = (ROLE == 1) ? ((wq & 2) * 2 + (wq & 1) + (m & 1) * 2) : (2 * wq + (m & 1));
        const uint32_t a = sb + wg * 24576 + ((m >> 1) * 8 + r) * 128 + ((blk ^ r) << 4);
        float x0[16];
#pragma unroll
        for (int c = 0; c < 3; c++) {
            mbar_wait(sb + B_W + 8 * c, 0);
            if (wg == 0) TSTAMP(70 + c, 0);
#pragma unroll
            for (int i = 0; i < 12; i++) ldsm4t(wA[12 * c + i], a + s_w(c) + i * 2048);
            if (c == 2) bar_arrive<NB_PRO, 288>();
            if (c == 0) { mbar_wait(sb + B_X, 0); mbar_wait(sb + B_X + 8, 0); }
            if (c == 2) { bar_sync<NB_O, 256>(); cluster_arrive(); }
            wg_fence();
            if (c == 0) { x_project<0, 12>(x0, wA, xdesc); x_project<0, 12>(xd, wA, xdesc + (XB_BYTES >> 4)); wg_commit(); wg_wait<0>(); }
            if (c == 1) { x_project<12, 24>(x0, wA, xdesc); x_project<12, 24>(xd, wA, xdesc + (XB_BYTES >> 4)); wg_commit(); wg_wait<0>(); }
            if (c == 2) { x_project<24, 36>(x0, wA, xdesc); wg_commit(); wg_wait<0>(); }
        }
        uint32_t pk[8];
        x_pack(x0, pk);
        x_write(sb, pk, 0, isv, w, L16);
        bar_arrive<NB_AUX, 288>();
        wg_fence();
        x_project<24, 36>(xd, wA, xdesc + (XB_BYTES >> 4));
        wg_commit();
        cluster_wait();
        bar_sync<NB_O, 256>();
        if (wg == 0) TSTAMP(74, 0);
        load_wo(sb, w, L16, woA, woB);
    }
    int s = 0;
#pragma unroll 1
    while (true) {
        const uint32_t par = s & 1;
        const uint32_t kx = sb + S_KX + par * 4096;
        asm volatile("" : "+r"(L16));
        uint32_t pk[8];
        if (wg == 0) { wg_wait<0>(); x_pack(xd, pk); x_write(sb, pk, s + 1, isv, w, L16); }
        float c0[4], c1[4];
        uint32_t k0[4], k1[4];
        {
            const uint32_t a = sb + S_MEM + L16;
            constexpr int CH = 18 / NCH;
            uint32_t b[3][4];
            bool ready = true;
            mbar_wait(sb + B_M, par);
            ldsm4(b[0], a);
            ldsm4(b[1], a + 512);
            if (wg == 1) { wg_wait<0>(); x_pack(xd, pk); }
            bar_arrive<NB_GO, 288>();
#pragma unroll
            for (int i = 0; i < 18; i++) {
                if ((i + 4) % CH == 0 && i + 4 < 18) ready = mbar_test(sb + B_M + ((i + 4) / CH) * 8, par);
                if ((i + 2) % CH == 0 && i + 2 < 18) { if (__builtin_expect(!ready, 0)) mbar_wait(sb + B_M + ((i + 2) / CH) * 8, par); }
                if (i + 2 < 18) ldsm4(b[(i + 2) % 3], a + (i + 2) * 512);
                if (ROLE == 0 && i == 16) ldsm4(k0, kx + wq * 1024 + L16);
                if (ROLE == 0 && i == 17) ldsm4(k1, kx + wq * 1024 + 512 + L16);
                if (i == 0) { mma16z(c0, wA[0], b[0][0], b[0][1]); mma16z(c1, wA[1], b[0][2], b[0][3]); }
                else { mma16(c0, wA[2 * i], b[i % 3][0], b[i % 3][1]); mma16(c1, wA[2 * i + 1], b[i % 3][2], b[i % 3][3]); }
            }
        }
        const uint32_t p0 = pack_bf16(c0[0] + c1[0], c0[1] + c1[1]), p1 = pack_bf16(c0[2] + c1[2], c0[3] + c1[3]);
        if (!isv) {
            stsm2t(sb + S_QM + w * 256 + L16, p0, p1);
            bar_sync<NB_QK, 384>();
            if (ROLE == 0) {
                uint32_t q0[4], q1[4];
                ldsm4(q0, sb + S_QM + L16);
                ldsm4(q1, sb + S_QM + 512 + L16);
                mem_scores(sb, peerA, peerB, S_SP + j * 128 + wq * 256 + (L16 >> 2), q0, q1, k0, k1);
                mbar_arrive_if0(sb + B_S, L16);
            } else {
                if (s + 2 < NSEG) mbar_wait(sb + B_X + par * 8, ((s + 2) >> 1) & 1);
                x_write(sb, pk, s + 1, isv, w, L16);
                if (wq != 0) {
                    const int rt = (wq == 3) ? 0 : 1;
                    const uint32_t qa = sb + S_QX + par * 4096 + rt * 2048 + (L16 & 0x80) * 8 + (L16 & 0x170);
                    const uint32_t kb0 = (wq == 2 ? kx + 2048 : sb + S_KM) + L16;
                    const uint32_t kb1 = (wq == 2 ? kx + 3072 : kx) + L16;
                    const uint32_t kb2 = kx + 1024 + L16;
                    float a0[4], a1[4], a2[4];
#pragma unroll
                    for (int hf = 0; hf < 2; hf++) {
                        uint32_t qa0[4], qa1[4], b[4];
                        ldsm4(qa0, qa + hf * 512);
                        ldsm4(qa1, qa + hf * 512 + 128);
                        ldsm4(b, kb0 + hf * 512);
                        if (hf == 0) mma16z(a0, qa0, b[0], b[1]); else mma16(a0, qa0, b[0], b[1]);
                        mma16(a0, qa1, b[2], b[3]);
                        ldsm4(b, kb1 + hf * 512);
                        if (hf == 0) mma16z(a1, qa0, b[0], b[1]); else mma16(a1, qa0, b[0], b[1]);
                        mma16(a1, qa1, b[2], b[3]);
                        ldsm4(b, kb2 + hf * 512);
                        if (hf == 0) mma16z(a2, qa0, b[0], b[1]); else mma16(a2, qa0, b[0], b[1]);
                        mma16(a2, qa1, b[2], b[3]);
                    }
                    mbar_wait(sb + B_S, par);
                    const uint32_t dst = peerB + S_SX + par * 5120 + j * 128 + rt * 2560 + (L16 >> 2);
                    const uint32_t bar = peerB + B_SX + par * 8;
                    const uint32_t T0 = (wq == 2 ? 2 : 4) * 256, T1 = (wq == 2 ? 3 : 0) * 256;
                    st_async32(dst + T0, pack_f16_sat(a0[0], a0[1]), bar);
                    st_async32(dst + 1280 + T0, pack_f16_sat(a0[2], a0[3]), bar);
                    if (wq != 2) st_async32(dst + T1, pack_f16_sat(a1[0], a1[1]), bar);
                    st_async32(dst + 1280 + T1, pack_f16_sat(a1[2], a1[3]), bar);
                    if (wq == 1) st_async32(dst + 256, pack_f16_sat(a2[0], a2[1]), bar);
                    if (wq != 2) st_async32(dst + 1280 + 256, pack_f16_sat(a2[2], a2[3]), bar);
                }
            }
        } else {
            const uint32_t off = S_VM + (s & 3) * 2048 + w * 256 + (L16 >> 1);
            st_async64(peerA + off, p0, p1, peerA + B_S);
            st_async64(peerB + off, p0, p1, peerB + B_S);
            sts64(sb + off, p0, p1);
            __syncwarp();
            mbar_expect_if0(sb + B_S, 160, L16);
            if (ROLE == 2) bar_arrive<NB_P, 384>();
            else {
                if (s == NSEG - 1) break;
                x_write(sb, pk, s + 1, isv, w, L16);
                x_pv_both<NB_P, 384>(sb, s + 2, wq, L16);
                bar_arrive<NB_PV, 160>();
                if (s + 2 < NSEG) mbar_wait(sb + B_X + par * 8, ((s + 2) >> 1) & 1);
            }
        }
        if (s == NSEG - 1) break;
        if (wg == 0) {
            if (!isv) mbar_wait(sb + B_VX + par * 8, (s >> 1) & 1);
            uint32_t va[4][4];
            const uint32_t vx = sb + S_VX + (s & 3) * 8192 + wq * 2048 + L16;
            const uint32_t vm = sb + S_VM + (s & 3) * 2048 + wq * 512 + (L16 >> 1);
            lds128(va[0], vx);
            lds128(va[2], vx + 1024);
            mbar_wait(sb + B_S, par);
            __half2 hs[5];
            load_scores(sb + S_SP + L16, hs);
            float ev[10];
            softmax_exp(hs, ev);
            lds128(va[1], vx + 512);
            lds128(va[3], vx + 1536);
            uint32_t p[5];
#pragma unroll
            for (int i = 0; i < 5; i++) p[i] = pack_bf16(ev[2 * i], ev[2 * i + 1]);
            uint32_t vm0[2], vm1[2];
            const uint32_t ones[4] = {ONES, ONES, ONES, ONES};
            float sum[4], o0[4], o1[4];
            mma16z(o0, va[0], p[0], p[1]);
            mma16z(o1, va[2], p[0], p[1]);
            mma16z(sum, ones, p[0], p[1]);
            lds64(vm0, vm);
            lds64(vm1, vm + 256);
            mma16(o0, va[1], p[2], p[3]);
            mma16(o1, va[3], p[2], p[3]);
            mma16(sum, ones, p[2], p[3]);
            mma8(sum, ONES, ONES, p[4]);
            mma8(o0, vm0[0], vm0[1], p[4]);
            mma8(o1, vm1[0], vm1[1], p[4]);
            stsm4t(sb + S_OM + wq * 512 + L16, pack_bf16(o0[0], o0[1]), pack_bf16(o0[2], o0[3]), pack_bf16(o1[0], o1[1]), pack_bf16(o1[2], o1[3]));
            sts64(sb + S_SUM + wq * 256 + (L16 >> 1), __float_as_uint(rcp(sum[0])), __float_as_uint(rcp(sum[1])));
        }
        bar_sync<NB_O, 256>();
        {
            float a0[4], a1[4], e[4];
            float2 rc;
            float rr;
#pragma unroll
            for (int i = 0; i < 4; i++) {
                uint32_t b[4];
                ldsm4(b, sb + S_OM + i * 512 + L16);
                if (i == 0) {
                    mma16z(a0, woA[0], b[0], b[1]); mma16z(a1, woA[1], b[2], b[3]);
                    mma_sp<0>(e, b, woB[0]);
                } else {
                    if (i == 1) { rc = lds64f(sb + S_SUM + (L16 >> 1)); rr = lds32f(sb + S_SUM + ((L16 >> 4) & 0x1C)); }
                    mma16(a0, woA[2 * i], b[0], b[1]); mma16(a1, woA[2 * i + 1], b[2], b[3]);
                    mma_sp<1>(e, b, woB[i]);
                }
            }
            if (wg == 1) bar_arrive<NB_X, 256>();
            asm volatile("" : "+r"(L16));
            char* const rslot = acc + (slot_off(s + 1) + j * 64 + w * 4096) + lane_off(L16);
            asm volatile("red.relaxed.gpu.global.add.noftz.v4.bf16x2 [%0], {%1,%2,%3,%4};"
                         ::"l"(rslot), "r"(pack_bf16((a0[0] + a1[0]) * rc.x, (a0[1] + a1[1]) * rc.y)), "r"(pack_bf16((a0[2] + a1[2]) * rc.x, (a0[3] + a1[3]) * rc.y)),
                           "r"(pack_bf16((e[0] + e[2]) * rr, (e[1] + e[3]) * rr)), "r"(0x3F80u) : "memory");
        }
        bar_arrive<NB_RED, 384>();
        if (wg == 0) {
            bar_sync<NB_X, 256>();
            wg_fence();
            x_project<0, HAND_AT>(xd, wA, xdesc + par * (XB_BYTES >> 4));
            bar_arrive<NB_L, 256>();
            x_project<HAND_AT, 36>(xd, wA, xdesc + par * (XB_BYTES >> 4));
            wg_commit();
        } else {
            if (s < NSEG - 2) {
                bar_sync<NB_L, 256>();
                wg_fence();
                x_project<0, 36>(xd, wA, xdesc + par * (XB_BYTES >> 4));
                wg_commit();
            } else {
                if (isv) {
                    x_pv_both<NB_T0, 256>(sb, NSEG - 3, wq, L16);
                    bar_sync<NB_AUX, 128>();
                    if (wq == 0 && L16 == 0) ox_store(sb, NSEG - 3, h);
                    __syncwarp();
                    x_pv_both<NB_T0 + 1, 256>(sb, NSEG - 2, wq, L16);
                    bar_sync<NB_AUX, 128>();
                    if (L16 == 0) {
                        if (wq == 0) ox_publish(NSEG - 3, h);
                        if (wq == 1) ox_store(sb, NSEG - 2, h);
                    }
                    __syncwarp();
                }
                wg_fence();
                x_project<0, 1>(xd, wA, xdesc);
                wg_commit();
            }
        }
        s++;
    }
    if (isv) {
        if (w == 5 && L16 == 0) ox_publish(NSEG - 2, h);
        __syncwarp();
        uint32_t pva[3][4], pk[8];
        x_pv_load(sb, NSEG - 1, w, L16, pva);
        bar_sync<NB_T0 + 2, 384>();
        x_pv_run(sb, NSEG - 1, pva, pk);
        x_pv_store(sb, NSEG - 1, w, L16, pk);
        bar_sync<NB_O, 256>();
        if (w == 0 && L16 == 0) { ox_store(sb, NSEG - 1, h); ox_publish(NSEG - 1, h); }
        __syncwarp();
    }
}

template <bool isv>
__device__ __forceinline__ void chain_aux(const uint32_t sb, const uint32_t lane16, const int wq, const uint32_t j, const uint32_t h,
                                          const uint32_t peerA, const uint32_t peerB, const CUtensorMap* tmWo, const CUtensorMap* tmX,
                                          char* const acc, const CUtensorMap* m0, const CUtensorMap* m1) {
    const int t = wq * 32 + (lane16 >> 4);
    cluster_arrive();
    {
        for (int c2 = 0; c2 < 3; c2++) mbar_arrive_if0(sb + B_M + c2 * 8, lane16);
        asm volatile("griddepcontrol.launch_dependents;" ::: "memory");
        if (wq == 0) {
            mbar_wait(sb + B_W, 0);
            if (t == 0) {
                mbar_expect(sb + B_W + 16, 49152);
                tma2d_once(sb + s_w(2), m0, h * 128 + (isv ? 0 : 64 * j), 384, sb + B_W + 16);
                tma2d_once(sb + s_w(2) + 24576, m1, h * 128 + (isv ? 64 : 64 * j), 384, sb + B_W + 16);
            }
            __syncwarp();
            bar_sync<NB_PRO, 288>();
            if (t == 0) {
                fence_async_smem();
                mbar_expect(sb + B_WO, 49152);
                for (int b = 0; b < 3; b++) tma2d(sb + S_WO + b * 16384, tmWo, 192 * j + 64 * b, h * 128, sb + B_WO);
            }
        } else if (wq == 3) {
            bulk_wait0();
            asm volatile("fence.proxy.async.global;" ::: "memory");
            __syncwarp();
            if (lane16 == 0) {
                if (h == 0) asm volatile("red.relaxed.gpu.global.add.u32 [%0], 1;" ::"l"(&g_zero_cnt) : "memory");
            }
            __syncwarp();
            unsigned c = 0;
            while (ld_acquire(&g_zero_cnt) < 3 && ++c < SPIN_LIM) __nanosleep(100);
            TSTAMP(76, 0);
        }
        __syncwarp();
        cluster_wait();
        if (wq == 0) bar_sync<NB_AUX, 288>();
        if (t == 0) {
            fence_async_smem();
            if (!isv) mbar_expect(sb + B_VX, 8192);
            else {
                bulk_s2c(peerA + S_VX, sb + S_VX, 8192, peerA + B_VX);
                bulk_s2c(peerB + S_VX, sb + S_VX, 8192, peerB + B_VX);
            }
            mbar_expect(sb + B_X, XB_BYTES);
            tma3d(sb + S_XB, tmX, 0, 64, 0, sb + B_X);
        }
        __syncwarp();
    }
    TSTAMP(0, 0);
    uint32_t L16 = lane16;
    const char* slot = acc + wq * 4096 + lane_off(L16);
    float ev[10];
    unsigned early = 0;
    int state = 16;
    int s = 0;
#pragma unroll 1
    while (true) {
        const uint32_t par = s & 1;
        asm volatile("" : "+r"(L16));
        if (!isv) {
            if (wq == 0) {
                bar_sync<NB_QK, 384>();
                uint32_t q0[4], q1[4], k0[4], k1[4];
                ldsm4(q0, sb + S_QM + L16);
                ldsm4(k0, sb + S_KM + L16);
                ldsm4(q1, sb + S_QM + 512 + L16);
                ldsm4(k1, sb + S_KM + 512 + L16);
                mem_scores(sb, peerA, peerB, S_SP + j * 128 + 1024 + (L16 >> 2), q0, q1, k0, k1);
                mbar_expect_if0(sb + B_S, 640 + 2048, L16);
            } else if (wq == 3) {
                bar_sync<NB_GO, 288>();
                const unsigned t = post_time(s, L16, early);
                bar_sync<NB_QK, 384>();
                if (j == 0 && s < NSEG - 1) {
                    __nanosleep(LOOK_NS);
                    plan_look(sb, s, L16, t, state);
                }
            } else {
                bar_arrive<NB_QK, 384>();
                if (wq == 2) {
                    if (L16 == 0) {
                        if (s + 3 < NSEG) mbar_expect(sb + B_X + (par ^ 1) * 8, XB_BYTES);
                        mbar_expect(sb + B_VX + (par ^ 1) * 8, 8192);
                        mbar_expect(sb + B_T, 4);
                        if (s == 2 && h == 0 && j == 0) g_zero_cnt = 0;
                    }
                } else if (s + 3 < NSEG && j == 1) {
                    mbar_wait(sb + B_S, par);
                    __nanosleep(XTMA_NS);
                    if (L16 == 0) tma3d_mc(sb + S_XB + (par ^ 1) * XB_BYTES, tmX, 0, (s + 3) * SEG, 0, sb + B_X + (par ^ 1) * 8, 7);
                }
                __syncwarp();
            }
        } else {
            if (wq == 3) {
                bar_sync<NB_GO, 288>();
                post_time(s, L16, early);
            } else if (L16 == 0) {
                if (wq == 0) {
                    if (s >= 1) vx_fetch(sb, s, h);
                } else if (wq == 1) {
                    if (s >= 3 && s < NSEG - 1) ox_publish(s - 3, h);
                } else {
                    mbar_expect(sb + B_SX + par * 8, 3584);
                    mbar_expect(sb + B_T, 4);
                    if (s + 3 < NSEG) mbar_expect(sb + B_X + (par ^ 1) * 8, XB_BYTES);
                }
            }
            __syncwarp();
            if (s == NSEG - 1) break;
            if (s >= 1) mbar_wait(sb + B_SX + (par ^ 1) * 8, ((s - 1) >> 1) & 1);
            fence_async_smem();
            bar_sync<NB_P, 384>();
            if (wq == 0) { if (L16 == 0) vx_store(sb, s + 1, h); __syncwarp(); }
            x_scores(sb, s + 1, wq, L16, ev);
            if (wq == 1) {
                bar_sync<NB_PV, 160>();
                if (L16 == 0 && s >= 2) ox_store(sb, s - 2, h);
                __syncwarp();
            }
            x_probs(sb, s + 1, wq, L16, ev);
        }
        if (s == NSEG - 1) break;
        mbar_wait(sb + B_T, par);
        const unsigned tgt = __float_as_uint(lds32f(sb + S_TGT));
        if (isv && s == NSEG - 2) { fence_async_smem(); bar_arrive<NB_T0, 256>(); }
        bar_sync<NB_RED, 384>();
        if (isv) {
            if (wq == 1 && s == NSEG - 2) {
                if (L16 == 0) ox_publish(s - 2, h);
                __syncwarp();
            }
            if (s == NSEG - 2) {
                mbar_wait(sb + B_SX, (s >> 1) & 1);
                x_scores(sb, s, wq, L16, ev);
                x_probs(sb, s, wq, L16, ev);
                fence_async_smem();
                bar_arrive<NB_T0 + 1, 256>();
            }
        }
        asm volatile("" : "+r"(L16));
        slot += par ? 32768 - 512 : 512;
        while ((int)(gtime() - tgt) < 0) {}
        uint4 v[6];
        look(v, slot);
        s++;
        const uint32_t ma = sb + S_MEM + wq * 384 + L16;
        unsigned c = 0;
        constexpr int CW = 6 / NCH;
        int done = NCH;
#pragma unroll
        for (int k = 0; k < NCH; k++) {
            uint32_t bad = 0;
#pragma unroll
            for (int i = CW * k; i < CW * k + CW; i++) { stsm2t(ma + i * 1536, v[i].x, v[i].y); stsm1(ma + i * 1536 + 256, v[i].z); bad |= v[i].w ^ FULL_COUNT; }
            const bool again = __any_sync(0xffffffffu, bad != 0);
            mbar_arrive_if0(sb + B_M + k * 8, L16 | (uint32_t)again);
            if (again) { done = k; break; }
        }
        if (done < NCH) {
            uint32_t bad;
            do {
                look(v, slot);
                bad = 0;
#pragma unroll
                for (int i = 0; i < 6; i++) { stsm2t(ma + i * 1536, v[i].x, v[i].y); stsm1(ma + i * 1536 + 256, v[i].z); bad |= v[i].w ^ FULL_COUNT; }
            } while (++c < SPIN_LIM && __any_sync(0xffffffffu, bad != 0));
            __syncwarp();
#pragma unroll
            for (int k = 0; k < NCH; k++) if (k >= done) mbar_arrive_if0(sb + B_M + k * 8, L16);
        }
        early = c;
        TSTAMP(s, c | t_pack);
    }
    if (!isv) {
        mbar_wait(sb + B_VX + 8, ((NSEG - 1) >> 1) & 1);
        mbar_wait(sb + B_S, 1);
    } else {
        mbar_wait(sb + B_SX + 8, ((NSEG - 1) >> 1) & 1);
        x_scores(sb, NSEG - 1, wq, L16, ev);
        x_probs(sb, NSEG - 1, wq, L16, ev);
        fence_async_smem();
        bar_arrive<NB_T0 + 2, 384>();
        mbar_wait(sb + B_S, 1);
    }
}

__global__ void __launch_bounds__(384, 1)
chain_kernel(const __grid_constant__ CUtensorMap tmWq, const __grid_constant__ CUtensorMap tmWk, const __grid_constant__ CUtensorMap tmWv,
             const __grid_constant__ CUtensorMap tmWo, const __grid_constant__ CUtensorMap tmX, const bf16* __restrict__ mem0, char* const acc) {
    extern __shared__ __align__(1024) uint8_t smem[];
    const uint32_t sb = smem_u32(smem);
    const int tid = threadIdx.x;
    const uint32_t L16 = __shfl_sync(0xffffffffu, (tid & 31) * 16, tid & 31);
    const int w = __shfl_sync(0xffffffffu, tid >> 5, 0), wg = w >> 2, wq = w & 3;
    uint32_t j, h;
    asm("mov.u32 %0, %%cluster_ctarank;" : "=r"(j));
    asm("mov.u32 %0, %%clusterid.x;" : "=r"(h));
    const bool isv = (j == 2);
    const uint32_t peerA = mapa(sb, isv ? 0 : (j ^ 1)), peerB = mapa(sb, isv ? 1 : 2);
    if (w == 11) {
        sts128(sb + S_ZERO + L16, 0, 0, 0, 0);
        sts128(sb + S_ZERO + 512 + L16, 0, 0, 0, 0);
        fence_async_smem();
        __syncwarp();
        const int i = L16 >> 4, kb = j * 11 + i;
        if (i < 11 && kb < 32) bulk_s2g(acc + h * 32768 + kb * 1024, sb + S_ZERO, 1024);
        if (i == 11) bulk_s2g(g_time + blockIdx.x * 64, sb + S_ZERO, 256);
        bulk_commit();
    }
    if (tid == 256) {
        for (int c = 0; c < 3; c++) { mbar_init(sb + B_W + 8 * c, 1); mbar_init(sb + B_M + 8 * c, 4); }
        mbar_init(sb + B_WO, 1); mbar_init(sb + B_T, 1);
        mbar_init(sb + B_X, 1); mbar_init(sb + B_X + 8, 1);
        mbar_init(sb + B_S, isv ? 8 : 5);
        mbar_init(sb + B_VX, 1); mbar_init(sb + B_VX + 8, 1);
        mbar_init(sb + B_SX, 1); mbar_init(sb + B_SX + 8, 1);
        asm volatile("fence.mbarrier_init.release.cluster;" ::: "memory");
        const CUtensorMap* m0 = isv ? &tmWv : &tmWq;
        const CUtensorMap* m1 = isv ? &tmWv : &tmWk;
        const int c0 = h * 128 + (isv ? 0 : 64 * j), c1 = h * 128 + (isv ? 64 : 64 * j);
#pragma unroll
        for (int c = 0; c < 2; c++) {
            if (c == 1) {
                mbar_expect(sb + B_X, XB_BYTES);
                tma3d(sb + S_XB, &tmX, 0, 0, 0, sb + B_X);
                mbar_expect(sb + B_X + 8, XB_BYTES);
                tma3d(sb + S_XB + XB_BYTES, &tmX, 0, 32, 0, sb + B_X + 8);
            }
            mbar_expect(sb + B_W + 8 * c, 49152);
            tma2d_once(sb + s_w(c), m0, c0, c * 192, sb + B_W + 8 * c);
            tma2d_once(sb + s_w(c) + 24576, m1, c1, c * 192, sb + B_W + 8 * c);
        }
    } else if (tid < 256) {
        uint4 v0, v1, v2;
        v0 = *reinterpret_cast<const uint4*>(mem0 + (tid & 7) * DM + (tid >> 3) * 8);
        v1 = *reinterpret_cast<const uint4*>(mem0 + (tid & 7) * DM + (tid >> 3) * 8 + 256);
        if (tid < 64) v2 = *reinterpret_cast<const uint4*>(mem0 + (tid & 7) * DM + (tid >> 3) * 8 + 512);
        sts128(sb + S_MEM + tid * 16, v0.x, v0.y, v0.z, v0.w);
        sts128(sb + S_MEM + 4096 + tid * 16, v1.x, v1.y, v1.z, v1.w);
        if (tid < 64) sts128(sb + S_MEM + 8192 + tid * 16, v2.x, v2.y, v2.z, v2.w);
    }
    __syncthreads();
    if (wg == 2) {
        asm volatile("setmaxnreg.dec.sync.aligned.u32 %0;" ::"n"(REG_AUX));
        if (!isv) chain_aux<false>(sb, L16, wq, j, h, peerA, peerB, &tmWo, &tmX, acc, &tmWq, &tmWk);
        else chain_aux<true>(sb, L16, wq, j, h, peerA, peerB, &tmWo, &tmX, acc, &tmWv, &tmWv);
        __syncwarp();
        cluster_arrive(); cluster_wait();
        TSTAMP(65, 0);
    } else if (wg == 0) {
        asm volatile("setmaxnreg.inc.sync.aligned.u32 %0;" ::"n"(REG_MAIN));
        if (!isv) chain_main<0>(sb, L16, wq, j, h, peerA, peerB, acc);
        else chain_main<2>(sb, L16, wq, j, h, peerA, peerB, acc);
        cluster_arrive(); cluster_wait();
    } else {
        asm volatile("setmaxnreg.inc.sync.aligned.u32 %0;" ::"n"(REG_MAIN));
        if (!isv) chain_main<1>(sb, L16, wq, j, h, peerA, peerB, acc);
        else chain_main<3>(sb, L16, wq, j, h, peerA, peerB, acc);
        cluster_arrive(); cluster_wait();
    }
}

constexpr int NHELP = 36;
constexpr uint32_t H_U = 0;
constexpr uint32_t UT_PITCH = 4368;
constexpr uint32_t H_UT = 65536;
constexpr uint32_t KW_BYTES = 8320;
constexpr uint32_t H_KW = 135424;
constexpr uint32_t H_PAR = 201984;
constexpr uint32_t H_KD = 214272;
constexpr uint32_t H_IDX = 224640;
constexpr uint32_t H_STAGE = 0;
constexpr uint32_t H_RED = 196608;
constexpr uint32_t H_FIN = 212992;
constexpr uint32_t H_OWN = 214016;
constexpr uint32_t H_BAR = 229376;
constexpr uint32_t B_SMEM = H_BAR + 384;
constexpr uint32_t HB_U = H_BAR, HB_WO = H_BAR + 8, HB_EMPTY = H_BAR + 16, HB_FIN = H_BAR + 96, HB_FULL = H_BAR + 128, HB_SENT = H_BAR + 320;
constexpr int RING = 8;
__device__ __align__(1024) uint4 g_part[RING * 9 * 4 * 4 * 128];

__device__ __forceinline__ float2 cmul(float2 a, float2 b) { return make_float2(fmaf(a.x, b.x, -a.y * b.y), fmaf(a.x, b.y, a.y * b.x)); }
__device__ __forceinline__ float2 csqr(float2 a) { return make_float2(fmaf(a.x, a.x, -a.y * a.y), (a.x + a.x) * a.y); }
__device__ __forceinline__ float2 cexp(float zr, float zi, float p) {
    const float m = ex2(zr * p);
    const float r = zi * p;
    const float a = (fabsf(r) < 4194304.f ? r - ((r + 12582912.f) - 12582912.f) : 0.f) * 6.283185307179586f;
    return make_float2(m * __cosf(a), m * __sinf(a));
}
__device__ __forceinline__ uint32_t pack_f16(float lo, float hi) { uint32_t r; asm("cvt.rn.f16x2.f32 %0, %1, %2;" : "=r"(r) : "f"(hi), "f"(lo)); return r; }
__device__ __forceinline__ void mma16h(float* d, const uint32_t* a, uint32_t b0, uint32_t b1) {
    asm volatile("mma.sync.aligned.m16n8k16.row.col.f32.f16.f16.f32 {%0,%1,%2,%3},{%4,%5,%6,%7},{%8,%9},{%0,%1,%2,%3};"
                 : "+f"(d[0]), "+f"(d[1]), "+f"(d[2]), "+f"(d[3]) : "r"(a[0]), "r"(a[1]), "r"(a[2]), "r"(a[3]), "r"(b0), "r"(b1));
}
__device__ __forceinline__ float bf_round(float x) { return __bfloat162float(__float2bfloat16_rn(x)); }
__device__ __forceinline__ uint32_t lds32(uint32_t a) { uint32_t v; asm volatile("ld.shared.b32 %0,[%1];" : "=r"(v) : "r"(a) : "memory"); return v; }
__device__ __forceinline__ uint32_t lds16(uint32_t a) { uint16_t v; asm volatile("ld.shared.u16 %0,[%1];" : "=h"(v) : "r"(a) : "memory"); return v; }

__device__ __forceinline__ void s4d_kernel(uint32_t par, uint32_t kd, int d, int lane, const bf16* __restrict__ logA, const bf16* __restrict__ Aim,
                                           const bf16* __restrict__ Cre, const bf16* __restrict__ Cim, const bf16* __restrict__ logdt) {
    const float dt = bf_round(expf(__bfloat162float(logdt[d])));
    float4 q[4];
    float cmax = 0.f, last = 0.f;
#pragma unroll
    for (int i = 0; i < 4; i++) {
        const int n = d * NST + i * 32 + lane;
        q[i].x = -bf_round(expf(__bfloat162float(logA[n]))) * dt * 1.4426950408889634f;
        q[i].y = __bfloat162float(Aim[n]) * dt * 0.15915494309189535f;
        q[i].z = 2.f * (__bfloat162float(Cre[n]) * dt);
        q[i].w = 2.f * (__bfloat162float(Cim[n]) * dt);
        cmax = fmaxf(cmax, fmaxf(fabsf(q[i].z), fabsf(q[i].w)));
        const float2 e = cexp(q[i].x, q[i].y, 2048.f);
        last += q[i].z * e.x - q[i].w * e.y;
        const float2 w64 = cexp(q[i].x, q[i].y, 64.f);
        sts64(par + 2048 + (i * 32 + lane) * 8, __float_as_uint(w64.x), __float_as_uint(w64.y));
    }
#pragma unroll
    for (int o = 16; o; o >>= 1) { cmax = fmaxf(cmax, __shfl_xor_sync(0xffffffffu, cmax, o)); last += __shfl_xor_sync(0xffffffffu, last, o); }
    const float cs = __uint_as_float(max(__float_as_uint(cmax) & 0x7F800000u, 0x00800000u));
    const float ci = 1.f / cs;
#pragma unroll
    for (int i = 0; i < 4; i++) sts128(par + (i * 32 + lane) * 16, __float_as_uint(q[i].x), __float_as_uint(q[i].y), __float_as_uint(q[i].z * ci), __float_as_uint(q[i].w * ci));
    __syncwarp();
    float acc[5][4];
#pragma unroll
    for (int i = 0; i < 5; i++) acc[i][0] = acc[i][1] = acc[i][2] = acc[i][3] = 0.f;
    const float g = (float)(lane >> 2);
#pragma unroll 2
    for (int ks = 0; ks < 16; ks++) {
        uint32_t A[5][4], B[4][2];
#pragma unroll
        for (int hf = 0; hf < 2; hf++) {
            uint32_t r[4];
            const int n = ks * 8 + hf * 4 + (lane & 3);
            lds128(r, par + n * 16);
            const float2 w64 = lds64f(par + 2048 + n * 8);
            const float2 c = make_float2(__uint_as_float(r[2]), __uint_as_float(r[3]));
            float2 y = cexp(__uint_as_float(r[0]), __uint_as_float(r[1]), g);
#pragma unroll
            for (int k = 0; k < 4; k++) {
                const float2 cy = cmul(c, y);
                B[k][hf] = pack_f16(cy.x, -cy.y);
                if (k < 3) y = csqr(y);
            }
            const float2 xl = cmul(y, w64);
            float2 x0 = cmul(xl, w64), x1 = cmul(x0, w64);
            A[0][2 * hf] = pack_f16(y.x, y.y);
            A[0][2 * hf + 1] = pack_f16(xl.x, xl.y);
#pragma unroll
            for (int k = 0; k < 4; k++) {
                A[k + 1][2 * hf] = pack_f16(x0.x, x0.y);
                A[k + 1][2 * hf + 1] = pack_f16(x1.x, x1.y);
                if (k < 3) { x0 = csqr(x0); x1 = csqr(x1); }
            }
        }
        mma16h(acc[0], A[0], B[0][0], B[0][1]);
#pragma unroll
        for (int k = 0; k < 4; k++) mma16h(acc[k + 1], A[k + 1], B[k][0], B[k][1]);
    }
    __syncwarp();
#pragma unroll
    for (int i = 0; i < 5; i++) {
        sts32(kd + i * 256 + lane * 4, pack_bf16(acc[i][0] * cs, acc[i][1] * cs));
        sts32(kd + i * 256 + 128 + lane * 4, pack_bf16(acc[i][2] * cs, acc[i][3] * cs));
    }
    if (lane == 0) sts32(kd + 1280, pack_bf16(last, 0.f));
    __syncwarp();
}
__device__ __forceinline__ void s4d_expand(uint32_t kw, uint32_t kd, uint32_t idx, int lane) {
    if (lane < 16) sts32(kw + lane * 4, 0);
#pragma unroll 4
    for (int it = 0; it < 16; it++) {
        const int l = (it * 32 + lane) * 4;
        uint32_t j[2];
        lds64(j, idx + l * 2);
        const uint32_t jm = l ? lds16(idx + l * 2 - 2) : 1282;
        const uint32_t vm = lds16(kd + jm), v0 = lds16(kd + (j[0] & 0xFFFF)), v1 = lds16(kd + (j[0] >> 16)), v2 = lds16(kd + (j[1] & 0xFFFF)), v3 = lds16(kd + (j[1] >> 16));
        sts128(kw + 64 + l * 4, v0 | (vm << 16), v1 | (v0 << 16), v2 | (v1 << 16), v3 | (v2 << 16));
    }
    __syncwarp();
}

template <bool CLEAR>
__device__ __forceinline__ void s4d_conv(uint32_t ut, uint32_t kw, int lane, uint4* clr) {
    float acc[16][4];
#pragma unroll
    for (int i = 0; i < 16; i++) acc[i][0] = acc[i][1] = acc[i][2] = acc[i][3] = 0.f;
    const uint32_t ka = kw + 64 + ((lane >> 2) - 2 * (lane & 3)) * 4;
    const uint32_t ua = ut + 256 + lane * 8;
#pragma unroll 1
    for (int rho = 0; rho < 8; rho++) {
        if (CLEAR) { clr[rho * (9 * 16 * 128)] = make_uint4(0, 0, 0, 0); clr[rho * (9 * 16 * 128) + 512] = make_uint4(0, 0, 0, 0); }
        uint32_t B[16][2];
#pragma unroll
        for (int q = 0; q < 16; q++) lds64(B[q], ua + q * 256 - rho * 32);
#pragma unroll
        for (int m = 0; m < 16; m++) {
            uint32_t A[4];
            const uint32_t x = ka + m * 512 + rho * 64;
            A[0] = lds32(x); A[1] = lds32(x + 32); A[2] = lds32(x - 32); A[3] = A[0];
#pragma unroll
            for (int i = m; i < 16; i++) mma16(acc[i], A, B[i - m][0], B[i - m][1]);
        }
    }
    __syncwarp();
    const uint32_t ya = ut + 256 + (lane & 7) * 32 + ((lane >> 3) & 1) * 16 + (lane >> 4) * 256;
#pragma unroll
    for (int i = 0; i < 16; i += 2)
        stsm4t(ya + i * 256, pack_bf16(acc[i][0], acc[i][1]), pack_bf16(acc[i][2], acc[i][3]),
               pack_bf16(acc[i + 1][0], acc[i + 1][1]), pack_bf16(acc[i + 1][2], acc[i + 1][3]));
}

__global__ void __launch_bounds__(384, 1)
helper_kernel(const __grid_constant__ CUtensorMap tmU, const __grid_constant__ CUtensorMap tmY, const __grid_constant__ CUtensorMap tmWo,
              const bf16* __restrict__ logA, const bf16* __restrict__ Aim, const bf16* __restrict__ Cre, const bf16* __restrict__ Cim,
              const bf16* __restrict__ logdt, const bf16* __restrict__ Dskip, bf16* __restrict__ out) {
    extern __shared__ __align__(1024) uint8_t smem[];
    const uint32_t sb = smem_u32(smem);
    const int tid = threadIdx.x, lane = tid & 31;
    const int w = __shfl_sync(0xffffffffu, tid >> 5, 0);
    const int d0 = blockIdx.x * 16;
    HSTAMP(0);
    if (tid == 0) {
        mbar_init(sb + HB_U, 1); mbar_init(sb + HB_WO, 1);
        for (int i = 0; i < 3; i++) mbar_init(sb + HB_EMPTY + 8 * i, 8);
        for (int i = 0; i < 24; i++) mbar_init(sb + HB_FULL + 8 * i, 1);
        for (int i = 0; i < 4; i++) { mbar_init(sb + HB_FIN + 8 * i, 2); mbar_init(sb + HB_SENT + 8 * i, 8); }
        fence_async_smem();
    }
    __syncthreads();
    if (tid == 352) {
        const unsigned t0 = gtime();
        while (gtime() - t0 < U0_NS) __nanosleep(200);
        mbar_expect(sb + HB_U, 65536);
        for (int i = 0; i < 8; i++) tma2d_once(sb + H_U + i * 8192, &tmU, d0, i * 256, sb + HB_U);
    }
    __syncwarp();
    const int m = lane >> 3, r = lane & 7;
    const uint32_t kw = sb + H_KW + w * KW_BYTES;
    if (w < 8) {
        s4d_kernel(kw, sb + H_KD + w * 1296, d0 + w, lane, logA, Aim, Cre, Cim, logdt);
        bar_sync<1, 384>();
        HSTAMP(1);
        {
            uint4* dst = g_part + ((blockIdx.x % 9) * 16 + (w >> 2) * 8 + blockIdx.x / 9) * 128 + (tid & 127);
            s4d_expand(kw, sb + H_KD + w * 1296, sb + H_IDX, lane);
            bar_arrive<2, 384>();
            s4d_conv<true>(sb + H_UT + w * UT_PITCH, kw, lane, dst);
        }
        bar_sync<3, 384>();
        s4d_expand(kw, sb + H_KD + w * 1296, sb + H_IDX, lane);
        s4d_conv<false>(sb + H_UT + (8 + w) * UT_PITCH, kw, lane, nullptr);
    } else {
        for (int l = tid - 256; l < SEQ; l += 128) {
            const int jx = l < 128 ? l : (int)__bfloat16_as_ushort(__float2bfloat16_rn((float)l)) - (133 << 7);
            asm volatile("st.shared.u16 [%0], %1;" ::"r"(sb + H_IDX + l * 2), "h"((unsigned short)(jx * 2)) : "memory");
        }
        for (int i = tid - 256; i < 256; i += 128) sts128(sb + H_UT + (i >> 4) * UT_PITCH + (i & 15) * 16, 0, 0, 0, 0);
        mbar_wait(sb + HB_U, 0);
        const uint32_t src = sb + H_U + ((m & 1) * 8 + r) * 32 + (((m >> 1) ^ (r >> 2)) << 4);
        const uint32_t dst = sb + H_UT + 256 + (lane >> 2) * UT_PITCH + (lane & 3) * 8;
#pragma unroll 4
        for (int grp = w - 8; grp < 128; grp += 4) {
            uint32_t v[4];
            ldsm4t(v, src + grp * 512);
            sts64(dst + grp * 32, v[0], v[1]);
            sts64(dst + 8 * UT_PITCH + grp * 32, v[2], v[3]);
        }
        bar_arrive<1, 384>();
        bar_sync<2, 384>();
#pragma unroll 1
        for (int c = w - 8; c < 8; c += 4) s4d_kernel(sb + H_PAR + (w - 8) * 3072, sb + H_KD + c * 1296, d0 + 8 + c, lane, logA, Aim, Cre, Cim, logdt);
        bar_arrive<3, 384>();
    }
    __syncthreads();
    HSTAMP(2);
    const int cc = blockIdx.x % 9, kq = blockIdx.x / 9;
    {
        const __nv_bfloat162 D0 = *reinterpret_cast<const __nv_bfloat162*>(Dskip + d0 + (lane & 3) * 2);
        const __nv_bfloat162 D1 = *reinterpret_cast<const __nv_bfloat162*>(Dskip + d0 + 8 + (lane & 3) * 2);
        const uint32_t ua = sb + H_U + ((m & 1) * 8 + r) * 32 + (((m >> 1) ^ (r >> 2)) << 4);
        const uint32_t ya = sb + H_UT + 256 + ((m >> 1) * 8 + r) * UT_PITCH + (m & 1) * 16;
        for (int grp = w; grp < 128; grp += 12) {
            uint32_t u[4], y[4];
            ldsm4(u, ua + grp * 512);
            ldsm4t(y, ya + grp * 32);
#pragma unroll
            for (int i = 0; i < 4; i++) {
                const __nv_bfloat162 o = __hadd2_rn(*reinterpret_cast<__nv_bfloat162*>(&y[i]), __hmul2_rn(*reinterpret_cast<__nv_bfloat162*>(&u[i]), i < 2 ? D0 : D1));
                y[i] = *reinterpret_cast<const uint32_t*>(&o);
            }
            stsm4(ua + grp * 512, y[0], y[1], y[2], y[3]);
        }
        fence_async_smem();
        __syncthreads();
        if (tid == 0) {
            mbar_expect(sb + HB_WO, 131072);
            for (int i = 0; i < 8; i++) {
                asm volatile("cp.async.bulk.tensor.2d.global.shared::cta.bulk_group [%0, {%1,%2}], [%3];" ::"l"(&tmY), "r"(DM + d0), "r"(i * 256), "r"(sb + H_U + i * 8192) : "memory");
                tma2d_once(sb + 65536 + i * 16384, &tmWo, cc * 64, (kq * 8 + i) * 128, sb + HB_WO);
                __nanosleep(TRICKLE_NS);
            }
            bulk_commit();
            asm volatile("cp.async.bulk.wait_group.read 0;" ::: "memory");
        }
    }
    __syncwarp();
    if (w < 8) {
        asm volatile("setmaxnreg.inc.sync.aligned.u32 208;");
        const int wg = w >> 2;
        uint32_t wo[32][4];
        mbar_wait_long(sb + HB_WO, 0);
        const uint32_t a = sb + 65536 + wg * 65536 + ((m >> 1) * 8 + r) * 128 + (((2 * (w & 3) + (m & 1)) ^ r) << 4);
#pragma unroll
        for (int i = 0; i < 32; i++) ldsm4t(wo[i], a + i * 2048);
        __syncthreads();
        HSTAMP(3);
        const int t = tid & 127;
        int st = 0, ph = 0;
#pragma unroll 1
        for (int s = 0; s < NSEG; s++) {
            const uint32_t desc = (((sb + H_STAGE + st * 65536 + wg * 32768) & 0x3FFFF) >> 4) | (8u << 16);
            float d[16];
#pragma unroll
            for (int q = 0; q < HSPLIT; q++) {
                mbar_wait_long(sb + HB_FULL + ((st * 2 + wg) * 4 + q) * 8, ph);
                wg_fence();
#pragma unroll
                for (int i = q * (32 / HSPLIT); i < (q + 1) * (32 / HSPLIT); i++) {
                    if (i == 0) wg_rs_n32<0, 16, 1>(d, wo[i], desc); else wg_rs_n32<1, 16, 1>(d, wo[i], desc + i * 64);
                }
                wg_commit();
            }
            if (s >= 4) mbar_wait_long(sb + HB_FIN + (s & 3) * 8, ((s - 4) >> 2) & 1);
            const uint32_t ra = sb + H_RED + (s & 1) * 8192 + t * 16;
            uint4* dst = g_part + (((s % RING) * 9 + cc) * 16 + wg * 8 + kq) * 128 + t;
            const uint32_t own = sb + H_OWN + (s & 3) * 2048 + t * 16;
            wg_wait<0>();
#pragma unroll
            for (int i = 0; i < 8; i++) { const float a0 = d[i], a1 = d[8 + i]; d[i] = wg ? a1 : a0; d[8 + i] = wg ? a0 : a1; }
#pragma unroll
            for (int i = 0; i < 2; i++) sts128(ra + wg * 4096 + i * 2048, __float_as_uint(d[8 + 4 * i]), __float_as_uint(d[9 + 4 * i]), __float_as_uint(d[10 + 4 * i]), __float_as_uint(d[11 + 4 * i]));
            mbar_arrive_if0(sb + HB_EMPTY + st * 8, lane);
            bar_sync<4, 256>();
            uint32_t p[8];
#pragma unroll
            for (int i = 0; i < 2; i++) lds128(p + 4 * i, ra + (wg ^ 1) * 4096 + i * 2048);
#pragma unroll
            for (int i = 0; i < 2; i++) {
#pragma unroll
                for (int k = 4 * i; k < 4 * i + 4; k++) p[k] = ((__float_as_uint(__uint_as_float(p[k]) + d[k]) + 64) & ~127u) | (s + 1);
                asm volatile("{.reg .pred q; setp.eq.u32 q, %6, %7;\n"
                             "@!q st.relaxed.gpu.global.v4.u32 [%0], {%2,%3,%4,%5};\n"
                             "@q st.shared.v4.u32 [%1], {%2,%3,%4,%5};}"
                             ::"l"(dst + i * 512), "r"(own), "r"(p[4 * i]), "r"(p[4 * i + 1]), "r"(p[4 * i + 2]), "r"(p[4 * i + 3]), "r"(kq), "r"(2 * wg + i) : "memory");
            }
            __syncwarp();
            mbar_arrive_if0(sb + HB_SENT + (s & 3) * 8, lane);
            HSTAMP4(s);
            if (++st == 3) { st = 0; ph ^= 1; }
        }
        if (tid == 0) bulk_wait0();
    } else {
        asm volatile("setmaxnreg.dec.sync.aligned.u32 88;");
        __syncthreads();
        if (w == 8) {
            const uint64_t pol = evict_first();
            int st = 0, ph = 1, ready = 0;
            for (int s = 0; s < NSEG; s++) {
                unsigned c = 0;
                while (ready <= s) {
                    const unsigned f = ld_acquire(&g_flag[kq * NSEG + min(s + (lane & 3), NSEG - 1)]);
                    ready = s + __ffs(~(__ballot_sync(0xffffffffu, f >= 8) & 15)) - 1;
                    if (++c >= LONG_LIM) break;
                    if (ready <= s) __nanosleep(POLL_NS);
                }
                __syncwarp();
                if (lane == 0) {
                    asm volatile("fence.proxy.async.global;" ::: "memory");
                    HSTAMP3(s);
                    mbar_wait_long(sb + HB_EMPTY + st * 8, ph);
#pragma unroll
                    for (int k = 0; k < 2 * HSPLIT; k++) {
                        const int g = k & 1, q = k >> 1;
                        constexpr uint32_t bytes = 32768 / HSPLIT;
                        const uint32_t bar = sb + HB_FULL + ((st * 2 + g) * 4 + q) * 8;
                        mbar_expect(bar, bytes);
                        asm volatile("cp.async.bulk.shared::cluster.global.mbarrier::complete_tx::bytes.L2::cache_hint [%0], [%1], %2, [%3], %4;"
                                     ::"r"(sb + H_STAGE + st * 65536 + g * 32768 + q * bytes), "l"(g_ox + (s * NH + kq * 8 + g * 4) * 512 + q * (bytes / 16)), "r"(bytes), "r"(bar), "l"(pol) : "memory");
                    }
                }
                __syncwarp();
                if (++st == 3) { st = 0; ph ^= 1; }
            }
            unsigned last = 0;
            if (lane == 0) asm volatile("atom.acq_rel.gpu.global.inc.u32 %0, [%1], %2;" : "=r"(last) : "l"(&g_done_cnt), "r"(NHELP - 1) : "memory");
            if (__shfl_sync(0xffffffffu, last, 0) == NHELP - 1) {
                reinterpret_cast<uint4*>(g_flag)[lane] = make_uint4(0, 0, 0, 0);
                reinterpret_cast<uint4*>(g_flag)[32 + lane] = make_uint4(0, 0, 0, 0);
            }
        } else if (w < 11) {
            const int f = w - 9;
            const uint32_t fa = sb + H_FIN + f * 512;
            for (int s = 0; s < NSEG; s++) {
                mbar_wait_long(sb + HB_SENT + (s & 3) * 8, (s >> 2) & 1);
                const uint4* src = g_part + (((s % RING) * 9 + cc) * 16 + kq * 4) * 128 + f * 64 + lane;
                uint4 v[8];
                lds128(&v[6].x, sb + H_OWN + (s & 3) * 2048 + (f * 64 + lane) * 16);
                lds128(&v[7].x, sb + H_OWN + (s & 3) * 2048 + (f * 64 + 32 + lane) * 16);
                unsigned c = 0;
                while (true) {
                    uint32_t bad = 0;
#pragma unroll
                    for (int i = 0; i < 6; i++) v[i] = ld_poll(src + ((kq + 1 + (i >> 1)) & 3) * 128 + (i & 1) * 32);
#pragma unroll
                    for (int i = 0; i < 6; i++) bad |= (v[i].x ^ (s + 1)) | (v[i].y ^ (s + 1)) | (v[i].z ^ (s + 1)) | (v[i].w ^ (s + 1));
                    if (!__any_sync(0xffffffffu, (bad & 127) != 0) || ++c >= LONG_LIM) break;
                    __nanosleep(POLL_NS);
                }
                mbar_arrive_if0(sb + HB_FIN + (s & 3) * 8, lane);
                uint32_t pk[4];
#pragma unroll
                for (int u = 0; u < 2; u++) {
                    float o[4] = {0.f, 0.f, 0.f, 0.f};
#pragma unroll
                    for (int k = 0; k < 4; k++) {
                        o[0] += __uint_as_float(v[2 * k + u].x & ~127u); o[1] += __uint_as_float(v[2 * k + u].y & ~127u);
                        o[2] += __uint_as_float(v[2 * k + u].z & ~127u); o[3] += __uint_as_float(v[2 * k + u].w & ~127u);
                    }
                    pk[2 * u] = pack_bf16(o[0], o[1]); pk[2 * u + 1] = pack_bf16(o[2], o[3]);
                }
                stsm4t(fa + r * 64 + ((m ^ (r >> 1)) << 4), pk[0], pk[1], pk[2], pk[3]);
                __syncwarp();
                uint32_t o4[4];
                lds128(o4, fa + (lane >> 2) * 64 + (((lane & 3) ^ (lane >> 3)) << 4));
                *reinterpret_cast<uint4*>(out + (s * SEG + kq * 8 + (lane >> 2)) * OUTW + cc * 64 + f * 32 + (lane & 3) * 8) = make_uint4(o4[0], o4[1], o4[2], o4[3]);
                __syncwarp();
                HSTAMP2(s);
            }
            asm volatile("griddepcontrol.wait;" ::: "memory");
        }
    }
}

typedef CUresult (*EncodeFn)(CUtensorMap*, CUtensorMapDataType, cuuint32_t, void*, const cuuint64_t*, const cuuint64_t*, const cuuint32_t*,
                             const cuuint32_t*, CUtensorMapInterleave, CUtensorMapSwizzle, CUtensorMapL2promotion, CUtensorMapFloatOOBfill);

void make_map(EncodeFn fn, CUtensorMap* m, const void* p, int rank, const cuuint64_t* dims, const cuuint64_t* strides, const cuuint32_t* box,
              CUtensorMapSwizzle sw = CU_TENSOR_MAP_SWIZZLE_128B, CUtensorMapL2promotion pr = CU_TENSOR_MAP_L2_PROMOTION_L2_128B) {
    const cuuint32_t es[3] = {1, 1, 1};
    fn(m, CU_TENSOR_MAP_DATA_TYPE_BFLOAT16, rank, const_cast<void*>(p), dims, strides, box, es, CU_TENSOR_MAP_INTERLEAVE_NONE,
       sw, pr, CU_TENSOR_MAP_FLOAT_OOB_FILL_NONE);
}

}

extern "C" void kernel_launch(void* const* d_in, const int* in_sizes, int n_in, void* d_out, int out_size) {
    const bf16* x = (const bf16*)d_in[0];
    const bf16* mem0 = (const bf16*)d_in[1];
    const bf16* Wo = (const bf16*)d_in[5];
    bf16* out = (bf16*)d_out;

    static EncodeFn enc = nullptr;
    static char* acc = nullptr;
    if (!enc) {
        void* p = nullptr;
        cudaGetSymbolAddress(&p, g_acc);
        acc = reinterpret_cast<char*>((reinterpret_cast<uintptr_t>(p) + 32767) & ~(uintptr_t)32767);
        void* fn = nullptr;
        cudaDriverEntryPointQueryResult st;
        cudaGetDriverEntryPoint("cuTensorMapEncodeTiled", &fn, cudaEnableDefault, &st);
        enc = (EncodeFn)fn;
        cudaFuncSetAttribute(chain_kernel, cudaFuncAttributeMaxDynamicSharedMemorySize, A_SMEM);
        cudaFuncSetAttribute(helper_kernel, cudaFuncAttributeMaxDynamicSharedMemorySize, B_SMEM);
    }
    CUtensorMap tmW[3], tmWo, tmX;
    {
        const cuuint64_t dims[2] = {4096, 576}, str[1] = {8192};
        const cuuint32_t box[2] = {64, 192};
        for (int i = 0; i < 3; i++) make_map(enc, &tmW[i], d_in[2 + i], 2, dims, str, box);
    }
    {
        const cuuint64_t dims[2] = {576, 4096}, str[1] = {1152};
        const cuuint32_t box[2] = {64, 128};
        make_map(enc, &tmWo, Wo, 2, dims, str, box);
    }
    {
        const cuuint64_t dims[3] = {64, 2048, 9}, str[2] = {1152, 128};
        const cuuint32_t box[3] = {64, 32, 9};
        make_map(enc, &tmX, x, 3, dims, str, box);
    }
    CUtensorMap tmU, tmY;
    {
        const cuuint64_t dimsU[2] = {576, 2048}, strU[1] = {1152}, dimsY[2] = {1152, 2048}, strY[1] = {2304};
        const cuuint32_t box[2] = {16, 256};
        make_map(enc, &tmU, d_in[7], 2, dimsU, strU, box, CU_TENSOR_MAP_SWIZZLE_32B);
        make_map(enc, &tmY, out, 2, dimsY, strY, box, CU_TENSOR_MAP_SWIZZLE_32B, CU_TENSOR_MAP_L2_PROMOTION_NONE);
    }
    cudaStream_t st = cudaStreamPerThread;
    {
        cudaLaunchConfig_t cfg = {};
        cfg.gridDim = dim3(96); cfg.blockDim = dim3(384); cfg.dynamicSmemBytes = A_SMEM; cfg.stream = st;
        cudaLaunchAttribute at[1];
        at[0].id = cudaLaunchAttributeClusterDimension;
        at[0].val.clusterDim.x = 3; at[0].val.clusterDim.y = 1; at[0].val.clusterDim.z = 1;
        cfg.attrs = at; cfg.numAttrs = 1;
        cudaLaunchKernelEx(&cfg, chain_kernel, tmW[0], tmW[1], tmW[2], tmWo, tmX, mem0, acc);
    }
    {
        cudaLaunchConfig_t cfg = {};
        cfg.gridDim = dim3(NHELP); cfg.blockDim = dim3(384); cfg.dynamicSmemBytes = B_SMEM; cfg.stream = st;
        cudaLaunchAttribute at[1];
        at[0].id = cudaLaunchAttributeProgrammaticStreamSerialization;
        at[0].val.programmaticStreamSerializationAllowed = 1;
        cfg.attrs = at; cfg.numAttrs = 1;
        cudaLaunchKernelEx(&cfg, helper_kernel, tmU, tmY, tmWo, (const bf16*)d_in[8], (const bf16*)d_in[9], (const bf16*)d_in[10],
                           (const bf16*)d_in[11], (const bf16*)d_in[12], (const bf16*)d_in[13], out);
    }
}
```
